```python
import torch

def _softmax(x, axis=-1):
    return torch.softmax(x, dim=axis)

def _gelu(x):
    return torch.nn.functional.gelu(x, approximate='tanh')

def _silu(x):
    return torch.nn.functional.silu(x)

def _sigmoid(x):
    return torch.sigmoid(x)

def _layernorm(x, axis=-1, eps=1e-05):
    m = x.mean(dim=axis, keepdim=True)
    v = x.var(dim=axis, keepdim=True, unbiased=False)
    return (x - m) / torch.sqrt(v + eps)

def _scatter_add(tgt, idx, src, axis=0):
    return tgt.clone().index_add_(axis, idx, src)

def _segment_sum(src, seg, n):
    out = torch.zeros((n,) + src.shape[1:], dtype=src.dtype)
    return out.index_add_(0, seg, src)

def _pad(x, pw):
    flat = tuple((v for pair in reversed(pw) for v in pair))
    return torch.nn.functional.pad(x, flat)
kernel_name = 'recurrent_scan__memory_aug_recurrent_mem_tr__mixer_channel_mlp__prompt'

def setup_inputs():

    _w = lambda a: (lambda t: t.to(torch.bfloat16) if t.is_floating_point() else t)(torch.as_tensor(a))

    def _A_setup():
        B, S, Dm = (1, 2048, 512)
        H, Dh = (32, 128)
        M, seg = (8, 32)
        seg = min(seg, S)
        S = S // seg * seg
        return {'x': _w((lambda *s: torch.randn(*s, dtype=torch.bfloat16) * 0.05)(B, S, Dm)), 'mem0': _w((lambda *s: torch.randn(*s, dtype=torch.bfloat16) * 0.8)(B, M, Dm)), 'Wq': _w((lambda *s: torch.randn(*s, dtype=torch.bfloat16) * 0.8)(Dm, H, Dh) * Dm ** (-0.5)), 'Wk': _w((lambda *s: torch.randn(*s, dtype=torch.bfloat16) * 0.8)(Dm, H, Dh) * Dm ** (-0.5)), 'Wv': _w((lambda *s: torch.randn(*s, dtype=torch.bfloat16) * 0.8)(Dm, H, Dh) * Dm ** (-0.5)), 'Wo': _w((lambda *s: torch.randn(*s, dtype=torch.bfloat16) * 0.8)(H, Dh, Dm) * (H * Dh) ** (-0.5)), 'seg_len': seg}
    _A_in = _A_setup()

    def _B_setup():
        B, S, D, F = (1, 2048, 512, 1792)
        return {'x': _w((lambda *s: torch.randn(*s, dtype=torch.bfloat16) * 0.05)(B, S, D)), 'w1': _w((lambda *s: torch.randn(*s, dtype=torch.bfloat16) * 0.8)(D, F) * D ** (-0.5)), 'b1': _w((lambda *s: torch.randn(*s, dtype=torch.bfloat16) * 0.4)(F)), 'w2': _w((lambda *s: torch.randn(*s, dtype=torch.bfloat16) * 0.2)(F, D) * F ** (-0.5)), 'b2': _w((lambda *s: torch.randn(*s, dtype=torch.bfloat16) * 0.2)(D))}
    _B_in = _B_setup()
    return {'A_x': _A_in['x'], 'A_mem0': _A_in['mem0'], 'A_Wq': _A_in['Wq'], 'A_Wk': _A_in['Wk'], 'A_Wv': _A_in['Wv'], 'A_Wo': _A_in['Wo'], 'A_seg_len': _A_in['seg_len'], 'B_x': _B_in['x'], 'B_w1': _B_in['w1'], 'B_b1': _B_in['b1'], 'B_w2': _B_in['w2'], 'B_b2': _B_in['b2']}

def reference(A_x, A_mem0, A_Wq, A_Wk, A_Wv, A_Wo, A_seg_len, B_x, B_w1, B_b1, B_w2, B_b2):

    def _A_ref(x, mem0, Wq, Wk, Wv, Wo, seg_len):
        B, S, Dm = x.shape
        H, Dh = (Wq.shape[1], Wq.shape[2])
        M = mem0.shape[1]
        scale = Dh ** (-0.5)
        n_seg = S // seg_len
        L = M + seg_len
        idx = torch.arange(L)
        mask = (idx[:, None] < M) | (idx[:, None] >= idx[None, :])
        mem = mem0
        outs = []
        for s in range(n_seg):
            xs = x[:, s * seg_len:(s + 1) * seg_len, :].clone()
            h = torch.concatenate([mem, xs], axis=1)
            q = torch.einsum('btd,dhe->bhte', h, Wq)
            k = torch.einsum('btd,dhe->bhte', h, Wk)
            v = torch.einsum('btd,dhe->bhte', h, Wv)
            scores = torch.einsum('bhqe,bhke->bhqk', q, k) * scale
            scores = torch.where(mask[None, None], scores, -1000000000.0)
            p = _softmax(scores, axis=-1)
            o = torch.einsum('bhqk,bhke->bhqe', p, v)
            o = torch.einsum('bhte,hed->btd', o, Wo)
            mem = o[:, :M, :].clone()
            outs.append(o[:, M:, :])
        return torch.concatenate(outs, axis=1)

    def _B_ref(x, w1, b1, w2, b2):
        y = _layernorm(x, axis=-1)
        h = _gelu(torch.einsum('bsd,df->bsf', y, w1) + b1)
        return torch.einsum('bsf,fd->bsd', h, w2) + b2
    x = A_x
    xn = _layernorm(x, axis=-1)
    s = _A_ref(xn, A_mem0, A_Wq, A_Wk, A_Wv, A_Wo, A_seg_len)
    g = _silu(_B_ref(xn, B_w1, B_b1, B_w2, B_b2))
    return x + s * g
```

```cpp
#include <cuda_runtime.h>
#include <cuda_bf16.h>
#include <cuda.h>
#include <stdint.h>

typedef __nv_bfloat16 bf16;
constexpr int SEQ = 2048, DM = 512, FF = 1792, QW = 12288, NSTEP = 64;
constexpr int NREC = 64, NBULK = 68, NCTA = 132;
constexpr int SPIN_LIMIT = 1 << 22;

__device__ bf16 g_xn[SEQ * DM];
__device__ bf16 g_y[SEQ * DM];
__device__ bf16 g_qkv[(size_t)SEQ * QW];
__device__ bf16 g_hid[SEQ * FF];
__device__ bf16 g_o[(size_t)SEQ * 4096];
__device__ float g_z[SEQ * DM];
__device__ float g_s[SEQ * DM];
__device__ float4 g_acc[NSTEP][2][768];
__device__ bf16 g_km[NSTEP * 32 * 8 * 128];
__device__ bf16 g_vmT[NSTEP * 32 * 128 * 8];
struct Flags { int tile[16][48]; int hid[16]; int z[16][2]; int o[16][8]; int s[16][2]; int prog[16][32]; };
__device__ Flags g_fl;

struct Maps { CUtensorMap xn, y, hid, o, qkv, wk, wv, wq, w1, w2, wo; };

__device__ __forceinline__ uint32_t smem_u32(const void* p) { return (uint32_t)__cvta_generic_to_shared(p); }
__device__ __forceinline__ uint32_t mapa(uint32_t a, uint32_t r) { uint32_t o; asm volatile("mapa.shared::cluster.u32 %0, %1, %2;" : "=r"(o) : "r"(a), "r"(r)); return o; }
__device__ __forceinline__ void st_async_v4(uint32_t addr, float a, float b, float c, float d, uint32_t mbar) {
  asm volatile("st.async.weak.shared::cluster.mbarrier::complete_tx::bytes.v4.b32 [%0], {%1,%2,%3,%4}, [%5];" ::"r"(addr), "r"(__float_as_uint(a)), "r"(__float_as_uint(b)), "r"(__float_as_uint(c)), "r"(__float_as_uint(d)), "r"(mbar) : "memory"); }
__device__ __forceinline__ void mbar_init(uint32_t m, int c) { asm volatile("mbarrier.init.shared::cta.b64 [%0], %1;" ::"r"(m), "r"(c) : "memory"); }
__device__ __forceinline__ void mbar_expect(uint32_t m, int bytes) { asm volatile("mbarrier.arrive.expect_tx.shared::cta.b64 _, [%0], %1;" ::"r"(m), "r"(bytes) : "memory"); }
__device__ __forceinline__ void mbar_arrive(uint32_t m) { asm volatile("mbarrier.arrive.shared::cta.b64 _, [%0];" ::"r"(m) : "memory"); }
__device__ __forceinline__ void mbar_wait(uint32_t m, uint32_t parity) {
  uint32_t ok; int it = 0;
  do { asm volatile("{.reg .pred p; mbarrier.try_wait.parity.shared::cta.b64 p, [%1], %2; selp.u32 %0,1,0,p;}" : "=r"(ok) : "r"(m), "r"(parity) : "memory"); } while (!ok && ++it < SPIN_LIMIT); }
__device__ __forceinline__ void mbar_wait_cl(uint32_t m, uint32_t parity) {
  uint32_t ok; int it = 0;
  do { asm volatile("{.reg .pred p; mbarrier.try_wait.parity.acquire.cluster.shared::cta.b64 p, [%1], %2; selp.u32 %0,1,0,p;}" : "=r"(ok) : "r"(m), "r"(parity) : "memory"); } while (!ok && ++it < SPIN_LIMIT); }
__device__ __forceinline__ void bar_sync(int id, int n) { asm volatile("bar.sync %0, %1;" ::"r"(id), "r"(n) : "memory"); }
__device__ __forceinline__ void bar_arrive(int id, int n) { asm volatile("bar.arrive %0, %1;" ::"r"(id), "r"(n) : "memory"); }
__device__ __forceinline__ int ld_acq(const int* p) { int v; asm volatile("ld.acquire.gpu.global.s32 %0, [%1];" : "=r"(v) : "l"(p) : "memory"); return v; }
__device__ __forceinline__ void wait_flag(const int* p, int target) { int it = 0; while (ld_acq(p) < target && ++it < SPIN_LIMIT) { __nanosleep(40); } }
__device__ __forceinline__ void fence_async() { asm volatile("fence.proxy.async.global;" ::: "memory"); }
__device__ __forceinline__ uint4 lds128(uint32_t a) { uint4 v; asm volatile("ld.shared.v4.u32 {%0,%1,%2,%3}, [%4];" : "=r"(v.x), "=r"(v.y), "=r"(v.z), "=r"(v.w) : "r"(a) : "memory"); return v; }
__device__ __forceinline__ void sts128(uint32_t a, uint4 v) { asm volatile("st.shared.v4.u32 [%0], {%1,%2,%3,%4};" ::"r"(a), "r"(v.x), "r"(v.y), "r"(v.z), "r"(v.w) : "memory"); }
__device__ __forceinline__ void sts32(uint32_t a, uint32_t v) { asm volatile("st.shared.u32 [%0], %1;" ::"r"(a), "r"(v) : "memory"); }
__device__ __forceinline__ void sts16(uint32_t a, float f) { unsigned short h = __bfloat16_as_ushort(__float2bfloat16(f)); asm volatile("st.shared.u16 [%0], %1;" ::"r"(a), "h"(h) : "memory"); }
__device__ __forceinline__ void ldsm4(uint32_t* r, uint32_t a) { asm volatile("ldmatrix.sync.aligned.m8n8.x4.shared.b16 {%0,%1,%2,%3}, [%4];" : "=r"(r[0]), "=r"(r[1]), "=r"(r[2]), "=r"(r[3]) : "r"(a) : "memory"); }
__device__ __forceinline__ void ldsm4t(uint32_t* r, uint32_t a) { asm volatile("ldmatrix.sync.aligned.m8n8.x4.trans.shared.b16 {%0,%1,%2,%3}, [%4];" : "=r"(r[0]), "=r"(r[1]), "=r"(r[2]), "=r"(r[3]) : "r"(a) : "memory"); }
__device__ __forceinline__ void mma16(float* c, uint32_t a0, uint32_t a1, uint32_t a2, uint32_t a3, uint32_t b0, uint32_t b1) {
  asm volatile("mma.sync.aligned.m16n8k16.row.col.f32.bf16.bf16.f32 {%0,%1,%2,%3}, {%4,%5,%6,%7}, {%8,%9}, {%0,%1,%2,%3};" : "+f"(c[0]), "+f"(c[1]), "+f"(c[2]), "+f"(c[3]) : "r"(a0), "r"(a1), "r"(a2), "r"(a3), "r"(b0), "r"(b1)); }
__device__ __forceinline__ void mma8(float* c, uint32_t a0, uint32_t a1, uint32_t b0) {
  asm volatile("mma.sync.aligned.m16n8k8.row.col.f32.bf16.bf16.f32 {%0,%1,%2,%3}, {%4,%5}, {%6}, {%0,%1,%2,%3};" : "+f"(c[0]), "+f"(c[1]), "+f"(c[2]), "+f"(c[3]) : "r"(a0), "r"(a1), "r"(b0)); }
__device__ __forceinline__ uint32_t pack2(float a, float b) { __nv_bfloat162 h = __floats2bfloat162_rn(a, b); return *(uint32_t*)&h; }
__device__ __forceinline__ float rbf(float x) { return __bfloat162float(__float2bfloat16(x)); }
__device__ __forceinline__ void cp16(uint32_t d, const void* s) { asm volatile("cp.async.cg.shared.global [%0], [%1], 16;" ::"r"(d), "l"(s) : "memory"); }
__device__ __forceinline__ void tma2d(uint32_t dst, const CUtensorMap* m, int c0, int c1, uint32_t mbar) {
  asm volatile("cp.async.bulk.tensor.2d.shared::cluster.global.mbarrier::complete_tx::bytes [%0], [%1, {%2,%3}], [%4];" ::"r"(dst), "l"(m), "r"(c0), "r"(c1), "r"(mbar) : "memory"); }
__device__ __forceinline__ uint64_t mkdesc(uint32_t addr, uint32_t lbo, uint32_t sbo) {
  return (uint64_t)((addr & 0x3FFFF) >> 4) | ((uint64_t)(lbo >> 4) << 16) | ((uint64_t)(sbo >> 4) << 32) | (1ull << 62); }

#define R8(i) "+f"(d[i]), "+f"(d[i+1]), "+f"(d[i+2]), "+f"(d[i+3]), "+f"(d[i+4]), "+f"(d[i+5]), "+f"(d[i+6]), "+f"(d[i+7])
__device__ __forceinline__ void wgmma256(float* d, uint64_t da, uint64_t db, int acc) {
  asm volatile("{.reg .pred p; setp.ne.b32 p, %130, 0;\n"
    "wgmma.mma_async.sync.aligned.m64n256k16.f32.bf16.bf16 {"
    "%0,%1,%2,%3,%4,%5,%6,%7,%8,%9,%10,%11,%12,%13,%14,%15,%16,%17,%18,%19,%20,%21,%22,%23,%24,%25,%26,%27,%28,%29,%30,%31,"
    "%32,%33,%34,%35,%36,%37,%38,%39,%40,%41,%42,%43,%44,%45,%46,%47,%48,%49,%50,%51,%52,%53,%54,%55,%56,%57,%58,%59,%60,%61,%62,%63,"
    "%64,%65,%66,%67,%68,%69,%70,%71,%72,%73,%74,%75,%76,%77,%78,%79,%80,%81,%82,%83,%84,%85,%86,%87,%88,%89,%90,%91,%92,%93,%94,%95,"
    "%96,%97,%98,%99,%100,%101,%102,%103,%104,%105,%106,%107,%108,%109,%110,%111,%112,%113,%114,%115,%116,%117,%118,%119,%120,%121,%122,%123,%124,%125,%126,%127"
    "}, %128, %129, p, 1, 1, 0, 1;}"
    : R8(0), R8(8), R8(16), R8(24), R8(32), R8(40), R8(48), R8(56), R8(64), R8(72), R8(80), R8(88), R8(96), R8(104), R8(112), R8(120)
    : "l"(da), "l"(db), "r"(acc)); }

__global__ void __launch_bounds__(256) prologue_kernel(const bf16* __restrict__ x, const bf16* __restrict__ mem0) {
  int tid = threadIdx.x, lane = tid & 31, warp = tid >> 5;
  int row = blockIdx.x * 8 + warp;
  {
    const uint4* src = (const uint4*)(x + (size_t)row * DM);
    uint4 u[2] = { src[lane], src[lane + 32] };
    float v[16];
    #pragma unroll
    for (int i = 0; i < 2; i++) { const __nv_bfloat162* h = (const __nv_bfloat162*)&u[i];
      #pragma unroll
      for (int k = 0; k < 4; k++) { float2 f = __bfloat1622float2(h[k]); v[i * 8 + 2 * k] = f.x; v[i * 8 + 2 * k + 1] = f.y; } }
    #pragma unroll
    for (int pass = 0; pass < 2; pass++) {
      float s = 0;
      #pragma unroll
      for (int i = 0; i < 16; i++) s += v[i];
      #pragma unroll
      for (int o = 16; o; o >>= 1) s += __shfl_xor_sync(~0u, s, o);
      float mf = s * (1.f / DM);
      float q = 0;
      #pragma unroll
      for (int i = 0; i < 16; i++) { float dd = v[i] - mf; q += dd * dd; }
      #pragma unroll
      for (int o = 16; o; o >>= 1) q += __shfl_xor_sync(~0u, q, o);
      float m = rbf(mf), var = rbf(q * (1.f / DM));
      float den = rbf(sqrtf(rbf(var + 1e-5f)));
      #pragma unroll
      for (int i = 0; i < 16; i++) v[i] = rbf(rbf(v[i] - m) / den);
      uint4 o4[2];
      #pragma unroll
      for (int i = 0; i < 2; i++) { o4[i].x = pack2(v[i*8], v[i*8+1]); o4[i].y = pack2(v[i*8+2], v[i*8+3]); o4[i].z = pack2(v[i*8+4], v[i*8+5]); o4[i].w = pack2(v[i*8+6], v[i*8+7]); }
      uint4* dst = (uint4*)((pass ? g_y : g_xn) + (size_t)row * DM);
      dst[lane] = o4[0]; dst[lane + 32] = o4[1];
    }
  }
  int gt = blockIdx.x * 256 + tid;
  float4 z4 = make_float4(0, 0, 0, 0);
  #pragma unroll
  for (int i = 0; i < 4; i++) { ((float4*)g_z)[gt + i * 65536] = z4; ((float4*)g_s)[gt + i * 65536] = z4; }
  for (int i = gt; i < NSTEP * 1536; i += 65536) {
    float4 val = z4;
    if (i < 1536) {
      int j = i / 768, c = i % 768, ci = c >> 8, w = (c & 255) >> 5, l = c & 31, g = l >> 2, t = l & 3;
      float e3[3];
      #pragma unroll
      for (int k = 0; k < 3; k++) { int e = ci * 3 + k; int mt = e >> 2, cc = e & 3;
        e3[k] = e < 8 ? __bfloat162float(mem0[(2 * t + (cc & 1)) * DM + 256 * j + 32 * w + 16 * mt + g + 8 * (cc >> 1)]) : 0.f; }
      val = make_float4(e3[0], e3[1], e3[2], 32.f);
    }
    (&g_acc[0][0][0])[i] = val;
  }
  if (gt < (int)(sizeof(Flags) / 4)) ((int*)&g_fl)[gt] = 0;
}

constexpr int R_WO = 0, R_WR = 65536, R_KT = 131072, KT_SZ = 40 * 320, R_VT = R_KT + 2 * KT_SZ, VT_SZ = 48 * 272,
              R_MEM = R_VT + 2 * VT_SZ, R_Q = R_MEM + 8 * 576, R_O = R_Q + 8 * 320, R_S = R_O + 8 * 320,
              R_RQK = R_S + 8 * 48 * 4, R_RV = R_RQK + 8192, R_BAR = R_RV + 4096, R_END = R_BAR + 64;
constexpr int R_STG = R_KT;
constexpr int SMEM_BYTES = 4 * 49152 + 8 * 2304 + 1024 + 256;
static_assert(R_END + 1024 <= SMEM_BYTES, "smem");

__device__ __forceinline__ void recurrence(uint32_t sb, const bf16* __restrict__ Wq, const bf16* __restrict__ Wk, const bf16* __restrict__ Wv, const bf16* __restrict__ Wo) {
  const int tid = threadIdx.x, warp = tid >> 5, lane = tid & 31, g = lane >> 2, t = lane & 3;
  const int h = blockIdx.x >> 1, j = blockIdx.x & 1;
  const uint32_t peer = j ^ 1;
  const uint32_t mQK = sb + R_BAR, mV = sb + R_BAR + 8;
  uint32_t A[2][16][4];
  const uint32_t stg = sb + R_WR;
  const int lm = lane >> 3, lr = lane & 7;
  for (int i = tid; i < 128 * 32; i += 384) { int r = i >> 5, c = i & 31; cp16(stg + r * 528 + c * 16, Wo + ((size_t)(h * 128 + r)) * DM + 256 * j + c * 8); }
  asm volatile("cp.async.wait_all;" ::: "memory"); __syncthreads();
  if (warp < 8) {
    #pragma unroll
    for (int mt = 0; mt < 2; mt++)
      #pragma unroll
      for (int ks = 0; ks < 8; ks++) {
        int k = 32 * (ks >> 1) + 8 * (lr >> 1) + (lr & 1) + 4 * (ks & 1) + 2 * (lm >> 1);
        uint32_t r[4]; ldsm4t(r, stg + k * 528 + (32 * warp + 16 * mt + 8 * (lm & 1)) * 2);
        sts128(sb + R_WO + ((warp * 16 + mt * 8 + ks) * 32 + lane) * 16, make_uint4(r[0], r[1], r[2], r[3]));
      }
  }
  __syncthreads();
  #pragma unroll 1
  for (int m = 0; m < 3; m++) {
    const bf16* W = m == 0 ? Wq : (m == 1 ? Wk : Wv);
    for (int i = tid; i < 256 * 16; i += 384) { int r = i >> 4, c = i & 15; cp16(stg + r * 272 + c * 16, W + ((size_t)(256 * j + r)) * 4096 + h * 128 + c * 8); }
    asm volatile("cp.async.wait_all;" ::: "memory"); __syncthreads();
    if ((warp >> 2) == m) {
      #pragma unroll
      for (int mt = 0; mt < 2; mt++)
        #pragma unroll
        for (int ks = 0; ks < 16; ks++) {
          int k = 32 * (ks >> 1) + 8 * (lr >> 1) + (lr & 1) + 4 * (ks & 1) + 2 * (lm >> 1);
          ldsm4t(A[mt][ks], stg + k * 272 + (32 * (warp & 3) + 16 * mt + 8 * (lm & 1)) * 2);
        }
    }
    __syncthreads();
  }
  if (warp < 8) {
    #pragma unroll
    for (int ks = 0; ks < 16; ks++) sts128(sb + R_WR + ((warp * 16 + ks) * 32 + lane) * 16, make_uint4(A[1][ks][0], A[1][ks][1], A[1][ks][2], A[1][ks][3]));
  }
  for (int i = tid; i < 2 * 8 * 17; i += 384) { int b = i / 136, r = i % 136; sts128(sb + R_VT + b * VT_SZ + 40 * 272 + r * 16, make_uint4(0, 0, 0, 0)); }
  uint32_t moff[2][3];
  #pragma unroll
  for (int u = 0; u < 2; u++) { int c = tid + 384 * u, ci = c >> 8, w = (c & 255) >> 5;
    #pragma unroll
    for (int k = 0; k < 3; k++) { int e = ci * 3 + k; if (e > 7) e = 7; int mt = e >> 2, cc = e & 3;
      moff[u][k] = sb + R_MEM + (2 * t + (cc & 1)) * 576 + (32 * w + 16 * mt + g + 8 * (cc >> 1)) * 2; } }
  const bool last_pad = (tid + 384) >= 512;
  const int vt = tid - 256;
  auto prefetch = [&](int s) {
    if ((s & 3) == 0) { wait_flag(&g_fl.tile[s >> 2][h >> 1], 1); wait_flag(&g_fl.tile[s >> 2][16 + (h >> 1)], 1); }
    const bf16* src = g_qkv + (size_t)(32 * s) * QW + h * 128;
    uint32_t kb = sb + R_KT + (s & 1) * KT_SZ, vb = sb + R_VT + (s & 1) * VT_SZ;
    #pragma unroll
    for (int i = 0; i < 4; i++) { int idx = vt + 128 * i, r = idx >> 4, c = idx & 15;
      cp16(kb + r * 320 + c * 16, src + (size_t)r * QW + c * 8); cp16(vb + r * 272 + c * 16, src + (size_t)r * QW + 4096 + c * 8); }
  };
  auto publish = [&](int s) {
    if (j == 0) { uint4 v = lds128(sb + R_KT + (s & 1) * KT_SZ + (32 + (vt >> 4)) * 320 + (vt & 15) * 16);
      __stcg((uint4*)(g_km + ((size_t)(s * 32 + h)) * 1024) + vt, v); }
    else { uint32_t vb = sb + R_VT + (s & 1) * VT_SZ + 32 * 272 + vt * 2; uint32_t e[8];
      #pragma unroll
      for (int k = 0; k < 8; k++) { unsigned short x; asm volatile("ld.shared.u16 %0, [%1];" : "=h"(x) : "r"(vb + k * 272) : "memory"); e[k] = x; }
      __stcg((uint4*)(g_vmT + ((size_t)(s * 32 + h)) * 1024) + vt, make_uint4(e[0] | (e[1] << 16), e[2] | (e[3] << 16), e[4] | (e[5] << 16), e[6] | (e[7] << 16))); }
    __syncwarp();
    if (lane == 0) { __threadfence(); atomicAdd(&g_fl.prog[s >> 2][h], 1); }
  };
  __syncthreads();
  if (warp >= 8) { prefetch(0); asm volatile("cp.async.wait_all;" ::: "memory"); }
  const float scale = 0.08838834764831845f;

  #pragma unroll 1
  for (int s = 0; s < NSTEP; s++) {
    if (tid == 0) { mbar_expect(mQK, 8192); mbar_expect(mV, 4096); }
    {
      const float4* src = &g_acc[s][j][tid];
      uint4 v0, v1; int it = 0; bool ok;
      do {
        asm volatile("ld.relaxed.gpu.global.v4.u32 {%0,%1,%2,%3}, [%4];" : "=r"(v0.x), "=r"(v0.y), "=r"(v0.z), "=r"(v0.w) : "l"(src) : "memory");
        asm volatile("ld.relaxed.gpu.global.v4.u32 {%0,%1,%2,%3}, [%4];" : "=r"(v1.x), "=r"(v1.y), "=r"(v1.z), "=r"(v1.w) : "l"(src + 384) : "memory");
        ok = (v0.w == 0x42000000u) && (v1.w == 0x42000000u);
      } while (!ok && ++it < SPIN_LIMIT);
      sts16(moff[0][0], __uint_as_float(v0.x)); sts16(moff[0][1], __uint_as_float(v0.y)); sts16(moff[0][2], __uint_as_float(v0.z));
      sts16(moff[1][0], __uint_as_float(v1.x)); sts16(moff[1][1], __uint_as_float(v1.y)); if (!last_pad) sts16(moff[1][2], __uint_as_float(v1.z));
    }
    __syncthreads();
    const uint32_t kb = sb + R_KT + (s & 1) * KT_SZ, vb = sb + R_VT + (s & 1) * VT_SZ;
    if (warp >= 8) bar_sync(4, 384);
    float c[4][4];
    #pragma unroll
    for (int i = 0; i < 4; i++) { c[i][0] = c[i][1] = c[i][2] = c[i][3] = 0.f; }
    #pragma unroll
    for (int p = 0; p < 8; p++) {
      uint4 b = lds128(sb + R_MEM + g * 576 + p * 64 + t * 16);
      mma16(c[0], A[0][2*p][0], A[0][2*p][1], A[0][2*p][2], A[0][2*p][3], b.x, b.y);
      mma16(c[1], A[1][2*p][0], A[1][2*p][1], A[1][2*p][2], A[1][2*p][3], b.x, b.y);
      mma16(c[2], A[0][2*p+1][0], A[0][2*p+1][1], A[0][2*p+1][2], A[0][2*p+1][3], b.z, b.w);
      mma16(c[3], A[1][2*p+1][0], A[1][2*p+1][1], A[1][2*p+1][2], A[1][2*p+1][3], b.z, b.w);
    }
    if (warp < 8) bar_arrive(4, 384);
    #pragma unroll
    for (int i = 0; i < 4; i++) { c[0][i] += c[2][i]; c[1][i] += c[3][i]; }
    const uint32_t rx = sb + R_RQK + (warp * 64 + lane) * 16;
    const uint32_t mb = warp < 8 ? mQK : mV;
    { uint32_t ra = mapa(rx, peer), rm = mapa(mb, peer);
      st_async_v4(ra, c[0][0], c[0][1], c[0][2], c[0][3], rm);
      st_async_v4(ra + 512, c[1][0], c[1][1], c[1][2], c[1][3], rm); }
    const bool more = s < NSTEP - 1;
    if (warp < 8 && more) {
      #pragma unroll
      for (int i = 0; i < 16; i++) { uint4 v = lds128(sb + R_WO + ((warp * 16 + i) * 32 + lane) * 16); A[1][i][0] = v.x; A[1][i][1] = v.y; A[1][i][2] = v.z; A[1][i][3] = v.w; }
    }
    mbar_wait_cl(mb, s & 1);
    {
      uint32_t dst = warp < 4 ? sb + R_Q : (warp < 8 ? kb + 32 * 320 : vb + 32 * 272);
      const uint32_t rs = warp < 8 ? 320 : 272;
      dst += (2 * t) * rs + (32 * (warp & 3) + g) * 2;
      #pragma unroll
      for (int mt = 0; mt < 2; mt++) { uint4 r = lds128(rx + 512 * mt);
        sts16(dst + mt * 32, c[mt][0] + __uint_as_float(r.x)); sts16(dst + mt * 32 + rs, c[mt][1] + __uint_as_float(r.y));
        sts16(dst + mt * 32 + 16, c[mt][2] + __uint_as_float(r.z)); sts16(dst + mt * 32 + rs + 16, c[mt][3] + __uint_as_float(r.w)); }
    }
    if (warp >= 8) {
      if (more) bar_arrive(3, 384);
      if (s > 0) publish(s - 1);
      if (more) { prefetch(s + 1); asm volatile("cp.async.wait_all;" ::: "memory"); }
    } else if (more) {
      bar_sync(1, 256);
      if (warp < 5) {
        float s0[4] = {0, 0, 0, 0}, s1[4] = {0, 0, 0, 0};
        #pragma unroll
        for (int p = 0; p < 4; p++) {
          uint4 qa = lds128(sb + R_Q + g * 320 + p * 64 + t * 16), kq = lds128(kb + (8 * warp + g) * 320 + p * 64 + t * 16);
          mma16(s0, qa.x, 0, qa.y, 0, kq.x, kq.y); mma16(s1, qa.z, 0, qa.w, 0, kq.z, kq.w);
        }
        float a = rbf(rbf(s0[0] + s1[0]) * scale), b = rbf(rbf(s0[1] + s1[1]) * scale);
        asm volatile("st.shared.v2.f32 [%0], {%1,%2};" ::"r"(sb + R_S + g * 192 + (8 * warp + 2 * t) * 4), "f"(a), "f"(b) : "memory");
      }
      bar_sync(2, 256);
      float sv[10];
      #pragma unroll
      for (int i = 0; i < 5; i++) asm volatile("ld.shared.v2.f32 {%0,%1}, [%2];" : "=f"(sv[2*i]), "=f"(sv[2*i+1]) : "r"(sb + R_S + g * 192 + (8 * i + 2 * t) * 4) : "memory");
      float mx = sv[0];
      #pragma unroll
      for (int i = 1; i < 10; i++) mx = fmaxf(mx, sv[i]);
      mx = fmaxf(mx, __shfl_xor_sync(~0u, mx, 1)); mx = fmaxf(mx, __shfl_xor_sync(~0u, mx, 2));
      float sum = 0;
      #pragma unroll
      for (int i = 0; i < 10; i++) { sv[i] = __expf(sv[i] - mx); sum += sv[i]; }
      sum += __shfl_xor_sync(~0u, sum, 1); sum += __shfl_xor_sync(~0u, sum, 2);
      float inv = __frcp_rn(sum);
      uint32_t P[6];
      #pragma unroll
      for (int i = 0; i < 5; i++) P[i] = pack2(sv[2*i] * inv, sv[2*i+1] * inv);
      P[5] = 0;
      float o0[4] = {0, 0, 0, 0}, o1[4] = {0, 0, 0, 0};
      #pragma unroll
      for (int kk = 0; kk < 3; kk++) {
        if (kk == 2) bar_sync(3, 384);
        uint32_t r[4]; ldsm4t(r, vb + (16 * kk + 8 * (lm & 1) + lr) * 272 + (16 * warp + 8 * (lm >> 1)) * 2);
        mma16(o0, P[2*kk], 0, P[2*kk+1], 0, r[0], r[1]); mma16(o1, P[2*kk], 0, P[2*kk+1], 0, r[2], r[3]);
      }
      sts32(sb + R_O + g * 320 + (16 * warp + 2 * t) * 2, pack2(o0[0], o0[1]));
      sts32(sb + R_O + g * 320 + (16 * warp + 8 + 2 * t) * 2, pack2(o1[0], o1[1]));
      bar_sync(1, 256);
      #pragma unroll
      for (int i = 0; i < 4; i++) { c[i][0] = c[i][1] = c[i][2] = c[i][3] = 0.f; }
      #pragma unroll
      for (int p = 0; p < 4; p++) {
        uint4 b = lds128(sb + R_O + g * 320 + p * 64 + t * 16);
        mma16(c[0], A[1][2*p][0], A[1][2*p][1], A[1][2*p][2], A[1][2*p][3], b.x, b.y);
        mma16(c[1], A[1][8+2*p][0], A[1][8+2*p][1], A[1][8+2*p][2], A[1][8+2*p][3], b.x, b.y);
        mma16(c[2], A[1][2*p+1][0], A[1][2*p+1][1], A[1][2*p+1][2], A[1][2*p+1][3], b.z, b.w);
        mma16(c[3], A[1][8+2*p+1][0], A[1][8+2*p+1][1], A[1][8+2*p+1][2], A[1][8+2*p+1][3], b.z, b.w);
      }
      #pragma unroll
      for (int i = 0; i < 4; i++) { c[0][i] += c[2][i]; c[1][i] += c[3][i]; }
      float4* dst = &g_acc[s + 1][j][tid];
      asm volatile("red.relaxed.gpu.global.add.v4.f32 [%0], {%1,%2,%3,%4};" ::"l"(dst), "f"(c[0][0]), "f"(c[0][1]), "f"(c[0][2]), "f"(1.0f) : "memory");
      asm volatile("red.relaxed.gpu.global.add.v4.f32 [%0], {%1,%2,%3,%4};" ::"l"(dst + 256), "f"(c[0][3]), "f"(c[1][0]), "f"(c[1][1]), "f"(1.0f) : "memory");
      asm volatile("red.relaxed.gpu.global.add.v4.f32 [%0], {%1,%2,%3,%4};" ::"l"(dst + 512), "f"(c[1][2]), "f"(c[1][3]), "f"(0.f), "f"(1.0f) : "memory");
      #pragma unroll
      for (int i = 0; i < 16; i++) { uint4 v = lds128(sb + R_WR + ((warp * 16 + i) * 32 + lane) * 16); A[1][i][0] = v.x; A[1][i][1] = v.y; A[1][i][2] = v.z; A[1][i][3] = v.w; }
    }
  }
  __syncthreads();
  if (warp >= 8) publish(NSTEP - 1);
}

constexpr int I_KV = 0, I_M1 = 512, I_Q = 624, I_M2 = 880, I_AT = 1008, I_END = 1008 + 16 * 48;
constexpr int B_STG = 4 * 49152, B_BAR = B_STG + 8 * 2304;
struct Item { int type, rb, nt, ks; };
__device__ __forceinline__ Item decode(int it) {
  Item r; r.ks = 0;
  if (it < I_M1) { r.type = 0; r.rb = it >> 5; r.nt = it & 31; }
  else if (it < I_Q) { int i = it - I_M1; r.type = 1; r.rb = i / 7; r.nt = i % 7; }
  else if (it < I_M2) { int i = it - I_Q; r.type = 0; r.rb = i >> 4; r.nt = 32 + (i & 15); }
  else if (it < I_AT) { int i = it - I_M2; r.type = 2; r.rb = i >> 3; r.nt = (i >> 2) & 1; r.ks = i & 3; }
  else { int i = it - I_AT; r.rb = i / 48; int q = i % 48; if (q < 32) { r.type = 3; r.nt = q; } else { r.type = 4; r.nt = (q - 32) >> 3; r.ks = (q - 32) & 7; } }
  return r;
}
__device__ __forceinline__ float gelu_t(float x) { float u = 0.7978845608028654f * (x + 0.044715f * x * x * x); float e = __expf(2.f * u); float th = 1.f - __fdividef(2.f, e + 1.f); return 0.5f * x * (1.f + th); }

__device__ __forceinline__ void bulk(uint32_t sb, const Maps& mp, const bf16* __restrict__ x, const bf16* __restrict__ b1, const bf16* __restrict__ b2, bf16* __restrict__ out) {
  const int tid = threadIdx.x, warp = tid >> 5, lane = tid & 31, g = lane >> 2, t = lane & 3;
  const int bid = blockIdx.x - NREC;
  const uint32_t full = sb + B_BAR, empty = sb + B_BAR + 32;
  if (warp >= 8) {
    asm volatile("setmaxnreg.dec.sync.aligned.u32 40;");
    if (tid == 256) {
      uint32_t st = 0, ph = 0;
      for (int it = bid; it < I_END; it += NBULK) {
        Item I = decode(it);
        if (I.type == 3) {
          wait_flag(&g_fl.tile[I.rb][I.nt >> 1], 1); wait_flag(&g_fl.tile[I.rb][16 + (I.nt >> 1)], 1); wait_flag(&g_fl.tile[I.rb][32 + (I.nt >> 1)], 1);
          fence_async();
          for (int m = 0; m < 3; m++) {
            mbar_wait(empty + st * 8, ph ^ 1);
            mbar_expect(full + st * 8, 32768);
            int col = (m == 0 ? 8192 : (m == 1 ? 0 : 4096)) + I.nt * 128;
            tma2d(sb + st * 49152, &mp.qkv, col, I.rb * 128, full + st * 8);
            tma2d(sb + st * 49152 + 16384, &mp.qkv, col + 64, I.rb * 128, full + st * 8);
            if (++st == 4) { st = 0; ph ^= 1; }
          }
          continue;
        }
        const CUtensorMap *ma, *mb; int nkb = 8, kb0 = 0, n0;
        if (I.type == 0) { ma = &mp.xn; mb = I.nt < 16 ? &mp.wk : (I.nt < 32 ? &mp.wv : &mp.wq); n0 = (I.nt & 15) * 256; }
        else if (I.type == 1) { ma = &mp.y; mb = &mp.w1; n0 = I.nt * 256; }
        else if (I.type == 2) { ma = &mp.hid; mb = &mp.w2; n0 = I.nt * 256; nkb = 7; kb0 = I.ks * 7; wait_flag(&g_fl.hid[I.rb], 7); fence_async(); }
        else { ma = &mp.o; mb = &mp.wo; n0 = I.nt * 256; kb0 = I.ks * 8; wait_flag(&g_fl.o[I.rb][I.ks], 4); fence_async(); }
        for (int kb = kb0; kb < kb0 + nkb; kb++) {
          mbar_wait(empty + st * 8, ph ^ 1);
          mbar_expect(full + st * 8, 49152);
          uint32_t sa = sb + st * 49152;
          tma2d(sa, ma, kb * 64, I.rb * 128, full + st * 8);
          #pragma unroll
          for (int q = 0; q < 4; q++) tma2d(sa + 16384 + q * 8192, mb, n0 + q * 64, kb * 64, full + st * 8);
          if (++st == 4) { st = 0; ph ^= 1; }
        }
      }
    }
    return;
  }
  asm volatile("setmaxnreg.inc.sync.aligned.u32 232;");
  const int wg = warp >> 2;
  const uint32_t stg = sb + B_STG + warp * 2304;
  const int lm = lane >> 3, lr = lane & 7;
  uint32_t st = 0, ph = 0;
  float d[128];
  #pragma unroll 1
  for (int it = bid; it < I_END; it += NBULK) {
    Item I = decode(it);
    const int row0 = I.rb * 128 + warp * 16;
    if (I.type == 3) {
      const int h = I.nt, seg = warp >> 1, half = warp & 1, step = I.rb * 4 + seg;
      uint32_t sQ = sb + st * 49152; mbar_wait(full + st * 8, ph); uint32_t eQ = empty + st * 8; if (++st == 4) { st = 0; ph ^= 1; }
      uint32_t sK = sb + st * 49152; mbar_wait(full + st * 8, ph); uint32_t eK = empty + st * 8; if (++st == 4) { st = 0; ph ^= 1; }
      float sc[5][4];
      #pragma unroll
      for (int i = 0; i < 5; i++) { sc[i][0] = sc[i][1] = sc[i][2] = sc[i][3] = 0.f; }
      wait_flag(&g_fl.prog[I.rb][h], 32);
      const uint32_t* km = (const uint32_t*)(g_km + ((size_t)(step * 32 + h)) * 1024) + g * 64 + t;
      #pragma unroll
      for (int ks = 0; ks < 8; ks++) {
        uint32_t a[4]; { int r = warp * 16 + 8 * (lm & 1) + lr, c8 = 2 * ks + (lm >> 1); ldsm4(a, sQ + (c8 >> 3) * 16384 + r * 128 + (((c8 & 7) ^ (r & 7)) << 4)); }
        #pragma unroll
        for (int np = 0; np < 2; np++) {
          if (np == 1 && half == 0) continue;
          uint32_t b[4]; int r = seg * 32 + 16 * np + 8 * (lm >> 1) + lr, c8 = 2 * ks + (lm & 1);
          ldsm4(b, sK + (c8 >> 3) * 16384 + r * 128 + (((c8 & 7) ^ (r & 7)) << 4));
          mma16(sc[2*np], a[0], a[1], a[2], a[3], b[0], b[1]); mma16(sc[2*np+1], a[0], a[1], a[2], a[3], b[2], b[3]);
        }
        uint32_t k0 = __ldcg(km + ks * 8), k1 = __ldcg(km + ks * 8 + 4);
        mma16(sc[4], a[0], a[1], a[2], a[3], k0, k1);
      }
      __syncwarp(); if (lane == 0) { mbar_arrive(eQ); mbar_arrive(eK); }
      const float scale = 0.08838834764831845f;
      uint32_t P[5][2];
      #pragma unroll
      for (int rr = 0; rr < 2; rr++) {
        const int qi = 16 * half + g + 8 * rr;
        float mx = -3.0e38f;
        #pragma unroll
        for (int i = 0; i < 5; i++)
          #pragma unroll
          for (int e = 0; e < 2; e++) { float v = rbf(rbf(sc[i][2*rr+e]) * scale); if (i < 4 && 8 * i + 2 * t + e > qi) v = -1.0e9f; sc[i][2*rr+e] = v; mx = fmaxf(mx, v); }
        mx = fmaxf(mx, __shfl_xor_sync(~0u, mx, 1)); mx = fmaxf(mx, __shfl_xor_sync(~0u, mx, 2));
        float sum = 0;
        #pragma unroll
        for (int i = 0; i < 5; i++)
          #pragma unroll
          for (int e = 0; e < 2; e++) { float v = __expf(sc[i][2*rr+e] - mx); sc[i][2*rr+e] = v; sum += v; }
        sum += __shfl_xor_sync(~0u, sum, 1); sum += __shfl_xor_sync(~0u, sum, 2);
        float inv = __frcp_rn(sum);
        #pragma unroll
        for (int i = 0; i < 5; i++) P[i][rr] = pack2(sc[i][2*rr] * inv, sc[i][2*rr+1] * inv);
      }
      uint32_t sV = sb + st * 49152; mbar_wait(full + st * 8, ph); uint32_t eV = empty + st * 8; if (++st == 4) { st = 0; ph ^= 1; }
      const uint32_t* vm = (const uint32_t*)(g_vmT + ((size_t)(step * 32 + h)) * 1024) + g * 4 + t;
      #pragma unroll
      for (int i = 0; i < 64; i++) d[i] = 0.f;
      #pragma unroll
      for (int n2 = 0; n2 < 8; n2++) {
        #pragma unroll
        for (int kk = 0; kk < 2; kk++) {
          if (kk == 1 && half == 0) continue;
          uint32_t b[4]; int r = seg * 32 + 16 * kk + 8 * (lm & 1) + lr, c8 = 2 * n2 + (lm >> 1);
          ldsm4t(b, sV + (c8 >> 3) * 16384 + r * 128 + (((c8 & 7) ^ (r & 7)) << 4));
          mma16(d + 8 * n2, P[2*kk][0], P[2*kk][1], P[2*kk+1][0], P[2*kk+1][1], b[0], b[1]);
          mma16(d + 8 * n2 + 4, P[2*kk][0], P[2*kk][1], P[2*kk+1][0], P[2*kk+1][1], b[2], b[3]);
        }
        mma8(d + 8 * n2, P[4][0], P[4][1], __ldcg(vm + n2 * 64)); mma8(d + 8 * n2 + 4, P[4][0], P[4][1], __ldcg(vm + n2 * 64 + 32));
      }
      __syncwarp(); if (lane == 0) mbar_arrive(eV);
      #pragma unroll
      for (int ch = 0; ch < 2; ch++) {
        #pragma unroll
        for (int i = 0; i < 8; i++) { const float* a = d + ch * 32 + i * 4;
          sts32(stg + g * 144 + i * 16 + t * 4, pack2(a[0], a[1])); sts32(stg + (g + 8) * 144 + i * 16 + t * 4, pack2(a[2], a[3])); }
        __syncwarp();
        #pragma unroll
        for (int i = 0; i < 4; i++) { int r = i * 4 + lm; uint4 v = lds128(stg + r * 144 + lr * 16);
          *(uint4*)(g_o + (size_t)(row0 + r) * 4096 + h * 128 + ch * 64 + lr * 8) = v; }
        __syncwarp();
      }
      fence_async(); bar_sync(1, 256);
      if (tid == 0) { __threadfence(); atomicAdd(&g_fl.o[I.rb][h >> 2], 1); }
      continue;
    }
    const int nkb = I.type == 2 ? 7 : 8;
    uint32_t prev = 0;
    for (int kb = 0; kb < nkb; kb++) {
      mbar_wait(full + st * 8, ph);
      uint32_t sa = sb + st * 49152;
      asm volatile("wgmma.fence.sync.aligned;" ::: "memory");
      #pragma unroll
      for (int k = 0; k < 4; k++)
        wgmma256(d, mkdesc(sa + wg * 8192 + k * 32, 16, 1024), mkdesc(sa + 16384 + k * 2048, 8192, 1024), (kb | k) != 0);
      asm volatile("wgmma.commit_group.sync.aligned;" ::: "memory");
      if (kb > 0) { asm volatile("wgmma.wait_group.sync.aligned 1;" ::: "memory"); if (lane == 0) mbar_arrive(prev); }
      prev = empty + st * 8;
      if (++st == 4) { st = 0; ph ^= 1; }
    }
    asm volatile("wgmma.wait_group.sync.aligned 0;" ::: "memory");
    if (lane == 0) mbar_arrive(prev);
    if (I.type <= 1) {
      bf16* dst; int ld;
      if (I.type == 0) { dst = g_qkv + (size_t)row0 * QW + I.nt * 256; ld = QW; } else { dst = g_hid + (size_t)row0 * FF + I.nt * 256; ld = FF; }
      #pragma unroll
      for (int ch = 0; ch < 4; ch++) {
        #pragma unroll
        for (int i = 0; i < 8; i++) { float* a = d + ch * 32 + i * 4;
          if (I.type == 1) { float2 bb = __bfloat1622float2(*(const __nv_bfloat162*)(b1 + I.nt * 256 + ch * 64 + i * 8 + 2 * t));
            a[0] = gelu_t(rbf(rbf(a[0]) + bb.x)); a[1] = gelu_t(rbf(rbf(a[1]) + bb.y)); a[2] = gelu_t(rbf(rbf(a[2]) + bb.x)); a[3] = gelu_t(rbf(rbf(a[3]) + bb.y)); }
          sts32(stg + g * 144 + i * 16 + t * 4, pack2(a[0], a[1])); sts32(stg + (g + 8) * 144 + i * 16 + t * 4, pack2(a[2], a[3])); }
        __syncwarp();
        #pragma unroll
        for (int i = 0; i < 4; i++) { int r = i * 4 + lm; uint4 v = lds128(stg + r * 144 + lr * 16); *(uint4*)(dst + (size_t)r * ld + ch * 64 + lr * 8) = v; }
        __syncwarp();
      }
      fence_async(); bar_sync(1, 256);
      if (tid == 0) { __threadfence(); atomicAdd(I.type == 0 ? &g_fl.tile[I.rb][I.nt] : &g_fl.hid[I.rb], 1); }
    } else {
      float* dst = (I.type == 2 ? g_z : g_s) + (size_t)(row0 + g) * DM + I.nt * 256 + 2 * t;
      #pragma unroll
      for (int i = 0; i < 32; i++) {
        asm volatile("red.relaxed.gpu.global.add.v2.f32 [%0], {%1,%2};" ::"l"(dst + i * 8), "f"(d[4*i]), "f"(d[4*i+1]) : "memory");
        asm volatile("red.relaxed.gpu.global.add.v2.f32 [%0], {%1,%2};" ::"l"(dst + 8 * DM + i * 8), "f"(d[4*i+2]), "f"(d[4*i+3]) : "memory");
      }
      __threadfence(); bar_sync(1, 256);
      if (I.type == 2) { if (tid == 0) atomicAdd(&g_fl.z[I.rb][I.nt], 1); }
      else {
        volatile int* sh = (volatile int*)(__cvta_shared_to_generic(sb + B_BAR + 64));
        if (tid == 0) { int old = atomicAdd(&g_fl.s[I.rb][I.nt], 1); if (old == 7) wait_flag(&g_fl.z[I.rb][I.nt], 4); __threadfence(); *sh = old; }
        bar_sync(1, 256);
        if (*sh == 7) {
          #pragma unroll 2
          for (int i = 0; i < 16; i++) {
            size_t off = (size_t)(row0 + i) * DM + I.nt * 256 + lane * 8;
            float4 s0 = __ldcg((const float4*)(g_s + off)), s1 = __ldcg((const float4*)(g_s + off + 4));
            float4 z0 = __ldcg((const float4*)(g_z + off)), z1 = __ldcg((const float4*)(g_z + off + 4));
            uint4 xv = *(const uint4*)(x + off), bv = *(const uint4*)(b2 + I.nt * 256 + lane * 8);
            float sa[8] = {s0.x, s0.y, s0.z, s0.w, s1.x, s1.y, s1.z, s1.w}, za[8] = {z0.x, z0.y, z0.z, z0.w, z1.x, z1.y, z1.z, z1.w}, r[8];
            #pragma unroll
            for (int e = 0; e < 8; e++) { float xx = __bfloat162float(((const bf16*)&xv)[e]), bb = __bfloat162float(((const bf16*)&bv)[e]);
              float u = rbf(rbf(za[e]) + bb); float gg = rbf(u / (1.f + __expf(-u))); r[e] = xx + rbf(rbf(sa[e]) * gg); }
            *(uint4*)(out + off) = make_uint4(pack2(r[0], r[1]), pack2(r[2], r[3]), pack2(r[4], r[5]), pack2(r[6], r[7]));
          }
        }
        bar_sync(1, 256);
      }
    }
  }
}

__global__ void __cluster_dims__(2, 1, 1) __launch_bounds__(384, 1)
main_kernel(const __grid_constant__ Maps mp, const bf16* x, const bf16* Wq, const bf16* Wk, const bf16* Wv, const bf16* Wo, const bf16* b1, const bf16* b2, bf16* out) {
  extern __shared__ uint8_t smem_raw[];
  uint32_t sb = (smem_u32(smem_raw) + 1023) & ~1023u;
  if (threadIdx.x == 0) {
    if (blockIdx.x < NREC) { mbar_init(sb + R_BAR, 1); mbar_init(sb + R_BAR + 8, 1); }
    else { for (int i = 0; i < 4; i++) { mbar_init(sb + B_BAR + i * 8, 1); mbar_init(sb + B_BAR + 32 + i * 8, 8); } }
    asm volatile("fence.mbarrier_init.release.cluster;" ::: "memory");
  }
  asm volatile("barrier.cluster.arrive.release.aligned; barrier.cluster.wait.acquire.aligned;" ::: "memory");
  if (blockIdx.x < NREC) recurrence(sb, Wq, Wk, Wv, Wo);
  else bulk(sb, mp, x, b1, b2, out);
}

typedef CUresult (*EncFn)(CUtensorMap*, CUtensorMapDataType, cuuint32_t, void*, const cuuint64_t*, const cuuint64_t*, const cuuint32_t*, const cuuint32_t*, CUtensorMapInterleave, CUtensorMapSwizzle, CUtensorMapL2promotion, CUtensorMapFloatOOBfill);
static void mk(EncFn f, CUtensorMap* m, const void* p, uint64_t rows, uint64_t cols, uint32_t boxr) {
  cuuint64_t dims[2] = {cols, rows}, str[1] = {cols * 2}; cuuint32_t box[2] = {64, boxr}, es[2] = {1, 1};
  f(m, CU_TENSOR_MAP_DATA_TYPE_BFLOAT16, 2, (void*)p, dims, str, box, es, CU_TENSOR_MAP_INTERLEAVE_NONE, CU_TENSOR_MAP_SWIZZLE_128B, CU_TENSOR_MAP_L2_PROMOTION_L2_256B, CU_TENSOR_MAP_FLOAT_OOB_FILL_NONE);
}
extern "C" void kernel_launch(void* const* d_in, const int* in_sizes, int n_in, void* d_out, int out_size) {
  const bf16 *x = (const bf16*)d_in[0], *mem0 = (const bf16*)d_in[1], *Wq = (const bf16*)d_in[2], *Wk = (const bf16*)d_in[3], *Wv = (const bf16*)d_in[4], *Wo = (const bf16*)d_in[5];
  const bf16 *w1 = (const bf16*)d_in[8], *b1 = (const bf16*)d_in[9], *w2 = (const bf16*)d_in[10], *b2 = (const bf16*)d_in[11];
  void* fn = nullptr; cudaDriverEntryPointQueryResult qr;
  cudaGetDriverEntryPoint("cuTensorMapEncodeTiled", &fn, cudaEnableDefault, &qr);
  EncFn f = (EncFn)fn;
  void *pxn, *py, *ph, *po, *pq;
  cudaGetSymbolAddress(&pxn, g_xn); cudaGetSymbolAddress(&py, g_y); cudaGetSymbolAddress(&ph, g_hid); cudaGetSymbolAddress(&po, g_o); cudaGetSymbolAddress(&pq, g_qkv);
  Maps mp;
  mk(f, &mp.xn, pxn, SEQ, DM, 128); mk(f, &mp.y, py, SEQ, DM, 128); mk(f, &mp.hid, ph, SEQ, FF, 128); mk(f, &mp.o, po, SEQ, 4096, 128); mk(f, &mp.qkv, pq, SEQ, QW, 128);
  mk(f, &mp.wk, Wk, DM, 4096, 64); mk(f, &mp.wv, Wv, DM, 4096, 64); mk(f, &mp.wq, Wq, DM, 4096, 64);
  mk(f, &mp.w1, w1, DM, FF, 64); mk(f, &mp.w2, w2, FF, DM, 64); mk(f, &mp.wo, Wo, 4096, DM, 64);
  cudaFuncSetAttribute(main_kernel, cudaFuncAttributeMaxDynamicSharedMemorySize, SMEM_BYTES);
  prologue_kernel<<<256, 256, 0, cudaStreamPerThread>>>(x, mem0);
  main_kernel<<<NCTA, 384, SMEM_BYTES, cudaStreamPerThread>>>(mp, x, Wq, Wk, Wv, Wo, b1, b2, (bf16*)d_out);
}
```

```cpp
#include <cuda_runtime.h>
#include <cuda_bf16.h>
#include <cuda.h>
#include <stdint.h>

typedef __nv_bfloat16 bf16;
constexpr int SEQ = 2048, DM = 512, FF = 1792, QW = 12288, NSTEP = 64;
constexpr int NREC = 64, NBULK = 68, NCTA = 132;
constexpr int SPIN_LIMIT = 1 << 22;

__device__ bf16 g_xn[SEQ * DM];
__device__ bf16 g_y[SEQ * DM];
__device__ bf16 g_qkv[(size_t)SEQ * QW];
__device__ bf16 g_hid[SEQ * FF];
__device__ bf16 g_o[(size_t)SEQ * 4096];
__device__ float g_z[SEQ * DM];
__device__ float g_s[SEQ * DM];
__device__ float4 g_acc[NSTEP][2][768];
__device__ bf16 g_km[NSTEP * 32 * 8 * 128];
__device__ bf16 g_vmT[NSTEP * 32 * 128 * 8];
struct Flags { int tile[16][48]; int hid[16]; int z[16][2]; int o[16][8]; int s[16][2]; int prog[16][32]; int next; };
__device__ Flags g_fl;

#define TR(i)
#define TB(i)
struct Maps { CUtensorMap xn, y, hid, o, qkv, wk, wv, wq, w1, w2, wo; };

__device__ __forceinline__ uint32_t smem_u32(const void* p) { return (uint32_t)__cvta_generic_to_shared(p); }
__device__ __forceinline__ int otid() { int t; asm volatile("mov.u32 %0, %%tid.x;" : "=r"(t)); return t; }
__device__ __forceinline__ uint32_t mapa(uint32_t a, uint32_t r) { uint32_t o; asm volatile("mapa.shared::cluster.u32 %0, %1, %2;" : "=r"(o) : "r"(a), "r"(r)); return o; }
__device__ __forceinline__ void st_async_v4(uint32_t addr, float a, float b, float c, float d, uint32_t mbar) {
  asm volatile("st.async.weak.shared::cluster.mbarrier::complete_tx::bytes.v4.b32 [%0], {%1,%2,%3,%4}, [%5];" ::"r"(addr), "r"(__float_as_uint(a)), "r"(__float_as_uint(b)), "r"(__float_as_uint(c)), "r"(__float_as_uint(d)), "r"(mbar) : "memory"); }
__device__ __forceinline__ void mbar_init(uint32_t m, int c) { asm volatile("mbarrier.init.shared::cta.b64 [%0], %1;" ::"r"(m), "r"(c) : "memory"); }
__device__ __forceinline__ void mbar_expect(uint32_t m, int bytes) { asm volatile("mbarrier.arrive.expect_tx.shared::cta.b64 _, [%0], %1;" ::"r"(m), "r"(bytes) : "memory"); }
__device__ __forceinline__ void mbar_arrive(uint32_t m) { asm volatile("mbarrier.arrive.shared::cta.b64 _, [%0];" ::"r"(m) : "memory"); }
__device__ __forceinline__ void mbar_wait(uint32_t m, uint32_t parity) {
  uint32_t ok; int it = 0;
  do { asm volatile("{.reg .pred p; mbarrier.try_wait.parity.shared::cta.b64 p, [%1], %2; selp.u32 %0,1,0,p;}" : "=r"(ok) : "r"(m), "r"(parity) : "memory"); } while (!ok && ++it < SPIN_LIMIT); }
__device__ __forceinline__ void mbar_wait_cl(uint32_t m, uint32_t parity) {
  uint32_t ok; int it = 0;
  do { asm volatile("{.reg .pred p; mbarrier.try_wait.parity.acquire.cluster.shared::cta.b64 p, [%1], %2; selp.u32 %0,1,0,p;}" : "=r"(ok) : "r"(m), "r"(parity) : "memory"); } while (!ok && ++it < SPIN_LIMIT); }
__device__ __forceinline__ void bar_sync(int id, int n) { asm volatile("bar.sync %0, %1;" ::"r"(id), "r"(n) : "memory"); }
__device__ __forceinline__ void bar_arrive(int id, int n) { asm volatile("bar.arrive %0, %1;" ::"r"(id), "r"(n) : "memory"); }
__device__ __forceinline__ int ld_acq(const int* p) { int v; asm volatile("ld.acquire.gpu.global.s32 %0, [%1];" : "=r"(v) : "l"(p) : "memory"); return v; }
__device__ __forceinline__ void wait_flag(const int* p, int target) { int it = 0; while (ld_acq(p) < target && ++it < SPIN_LIMIT) { __nanosleep(40); } }
__device__ __forceinline__ void fence_async() { asm volatile("fence.proxy.async.global;" ::: "memory"); }
__device__ __forceinline__ uint4 lds128(uint32_t a) { uint4 v; asm volatile("ld.shared.v4.u32 {%0,%1,%2,%3}, [%4];" : "=r"(v.x), "=r"(v.y), "=r"(v.z), "=r"(v.w) : "r"(a) : "memory"); return v; }
__device__ __forceinline__ void sts128(uint32_t a, uint4 v) { asm volatile("st.shared.v4.u32 [%0], {%1,%2,%3,%4};" ::"r"(a), "r"(v.x), "r"(v.y), "r"(v.z), "r"(v.w) : "memory"); }
__device__ __forceinline__ void sts32(uint32_t a, uint32_t v) { asm volatile("st.shared.u32 [%0], %1;" ::"r"(a), "r"(v) : "memory"); }
__device__ __forceinline__ void sts16(uint32_t a, float f) { unsigned short h = __bfloat16_as_ushort(__float2bfloat16(f)); asm volatile("st.shared.u16 [%0], %1;" ::"r"(a), "h"(h) : "memory"); }
__device__ __forceinline__ void ldsm4(uint32_t* r, uint32_t a) { asm volatile("ldmatrix.sync.aligned.m8n8.x4.shared.b16 {%0,%1,%2,%3}, [%4];" : "=r"(r[0]), "=r"(r[1]), "=r"(r[2]), "=r"(r[3]) : "r"(a) : "memory"); }
__device__ __forceinline__ void ldsm4t(uint32_t* r, uint32_t a) { asm volatile("ldmatrix.sync.aligned.m8n8.x4.trans.shared.b16 {%0,%1,%2,%3}, [%4];" : "=r"(r[0]), "=r"(r[1]), "=r"(r[2]), "=r"(r[3]) : "r"(a) : "memory"); }
__device__ __forceinline__ void mma16(float* c, uint32_t a0, uint32_t a1, uint32_t a2, uint32_t a3, uint32_t b0, uint32_t b1) {
  asm volatile("mma.sync.aligned.m16n8k16.row.col.f32.bf16.bf16.f32 {%0,%1,%2,%3}, {%4,%5,%6,%7}, {%8,%9}, {%0,%1,%2,%3};" : "+f"(c[0]), "+f"(c[1]), "+f"(c[2]), "+f"(c[3]) : "r"(a0), "r"(a1), "r"(a2), "r"(a3), "r"(b0), "r"(b1)); }
__device__ __forceinline__ void mma8(float* c, uint32_t a0, uint32_t a1, uint32_t b0) {
  asm volatile("mma.sync.aligned.m16n8k8.row.col.f32.bf16.bf16.f32 {%0,%1,%2,%3}, {%4,%5}, {%6}, {%0,%1,%2,%3};" : "+f"(c[0]), "+f"(c[1]), "+f"(c[2]), "+f"(c[3]) : "r"(a0), "r"(a1), "r"(b0)); }
__device__ __forceinline__ uint32_t pack2(float a, float b) { __nv_bfloat162 h = __floats2bfloat162_rn(a, b); return *(uint32_t*)&h; }
__device__ __forceinline__ float rbf(float x) { return __bfloat162float(__float2bfloat16(x)); }
__device__ __forceinline__ void cp16(uint32_t d, const void* s) { asm volatile("cp.async.cg.shared.global [%0], [%1], 16;" ::"r"(d), "l"(s) : "memory"); }
__device__ __forceinline__ void tma2d(uint32_t dst, const CUtensorMap* m, int c0, int c1, uint32_t mbar) {
  asm volatile("cp.async.bulk.tensor.2d.shared::cluster.global.mbarrier::complete_tx::bytes [%0], [%1, {%2,%3}], [%4];" ::"r"(dst), "l"(m), "r"(c0), "r"(c1), "r"(mbar) : "memory"); }
__device__ __forceinline__ uint64_t mkdesc(uint32_t addr, uint32_t lbo, uint32_t sbo) {
  return (uint64_t)((addr & 0x3FFFF) >> 4) | ((uint64_t)(lbo >> 4) << 16) | ((uint64_t)(sbo >> 4) << 32) | (1ull << 62); }

#define R8(i) "+f"(d[i]), "+f"(d[i+1]), "+f"(d[i+2]), "+f"(d[i+3]), "+f"(d[i+4]), "+f"(d[i+5]), "+f"(d[i+6]), "+f"(d[i+7])
__device__ __forceinline__ void wgmma256(float* d, uint64_t da, uint64_t db, int acc) {
  asm volatile("{.reg .pred p; setp.ne.b32 p, %130, 0;\n"
    "wgmma.mma_async.sync.aligned.m64n256k16.f32.bf16.bf16 {"
    "%0,%1,%2,%3,%4,%5,%6,%7,%8,%9,%10,%11,%12,%13,%14,%15,%16,%17,%18,%19,%20,%21,%22,%23,%24,%25,%26,%27,%28,%29,%30,%31,"
    "%32,%33,%34,%35,%36,%37,%38,%39,%40,%41,%42,%43,%44,%45,%46,%47,%48,%49,%50,%51,%52,%53,%54,%55,%56,%57,%58,%59,%60,%61,%62,%63,"
    "%64,%65,%66,%67,%68,%69,%70,%71,%72,%73,%74,%75,%76,%77,%78,%79,%80,%81,%82,%83,%84,%85,%86,%87,%88,%89,%90,%91,%92,%93,%94,%95,"
    "%96,%97,%98,%99,%100,%101,%102,%103,%104,%105,%106,%107,%108,%109,%110,%111,%112,%113,%114,%115,%116,%117,%118,%119,%120,%121,%122,%123,%124,%125,%126,%127"
    "}, %128, %129, p, 1, 1, 0, 1;}"
    : R8(0), R8(8), R8(16), R8(24), R8(32), R8(40), R8(48), R8(56), R8(64), R8(72), R8(80), R8(88), R8(96), R8(104), R8(112), R8(120)
    : "l"(da), "l"(db), "r"(acc)); }

__global__ void __launch_bounds__(256) prologue_kernel(const bf16* __restrict__ x, const bf16* __restrict__ mem0) {
  int tid = threadIdx.x, lane = tid & 31, warp = tid >> 5;
  int row = blockIdx.x * 8 + warp;
  {
    const uint4* src = (const uint4*)(x + (size_t)row * DM);
    uint4 u[2] = { src[lane], src[lane + 32] };
    float v[16];
    #pragma unroll
    for (int i = 0; i < 2; i++) { const __nv_bfloat162* h = (const __nv_bfloat162*)&u[i];
      #pragma unroll
      for (int k = 0; k < 4; k++) { float2 f = __bfloat1622float2(h[k]); v[i * 8 + 2 * k] = f.x; v[i * 8 + 2 * k + 1] = f.y; } }
    #pragma unroll
    for (int pass = 0; pass < 2; pass++) {
      float s = 0;
      #pragma unroll
      for (int i = 0; i < 16; i++) s += v[i];
      #pragma unroll
      for (int o = 16; o; o >>= 1) s += __shfl_xor_sync(~0u, s, o);
      float mf = s * (1.f / DM);
      float q = 0;
      #pragma unroll
      for (int i = 0; i < 16; i++) { float dd = v[i] - mf; q += dd * dd; }
      #pragma unroll
      for (int o = 16; o; o >>= 1) q += __shfl_xor_sync(~0u, q, o);
      float m = rbf(mf), var = rbf(q * (1.f / DM));
      float den = rbf(sqrtf(rbf(var + 1e-5f)));
      #pragma unroll
      for (int i = 0; i < 16; i++) v[i] = rbf(rbf(v[i] - m) / den);
      uint4 o4[2];
      #pragma unroll
      for (int i = 0; i < 2; i++) { o4[i].x = pack2(v[i*8], v[i*8+1]); o4[i].y = pack2(v[i*8+2], v[i*8+3]); o4[i].z = pack2(v[i*8+4], v[i*8+5]); o4[i].w = pack2(v[i*8+6], v[i*8+7]); }
      uint4* dst = (uint4*)((pass ? g_y : g_xn) + (size_t)row * DM);
      dst[lane] = o4[0]; dst[lane + 32] = o4[1];
    }
  }
  int gt = blockIdx.x * 256 + tid;
  float4 z4 = make_float4(0, 0, 0, 0);
  #pragma unroll
  for (int i = 0; i < 4; i++) { ((float4*)g_z)[gt + i * 65536] = z4; ((float4*)g_s)[gt + i * 65536] = z4; }
  for (int i = gt; i < NSTEP * 1536; i += 65536) {
    float4 val = z4;
    if (i < 1536) {
      int j = i / 768, c = i % 768, ci = c >> 8, w = (c & 255) >> 5, l = c & 31, g = l >> 2, t = l & 3;
      float e3[3];
      #pragma unroll
      for (int k = 0; k < 3; k++) { int e = ci * 3 + k; int mt = e >> 2, cc = e & 3;
        e3[k] = e < 8 ? __bfloat162float(mem0[(2 * t + (cc & 1)) * DM + 256 * j + 32 * w + 16 * mt + g + 8 * (cc >> 1)]) : 0.f; }
      val = make_float4(e3[0], e3[1], e3[2], 32.f);
    }
    (&g_acc[0][0][0])[i] = val;
  }
  if (gt < (int)(sizeof(Flags) / 4)) ((int*)&g_fl)[gt] = 0;
}

constexpr int R_WO = 0, R_WR = 65536, R_KT = 131072, KT_SZ = 40 * 320, R_VT = R_KT + 2 * KT_SZ, VT_SZ = 48 * 272,
              R_MEM = R_VT + 2 * VT_SZ, R_Q = R_MEM + 8 * 576, R_O = R_Q + 8 * 320, R_S = R_O + 8 * 320,
              R_RQK = R_S + 8 * 56 * 4, R_RV = R_RQK + 8192, R_BAR = R_RV + 4096, R_END = R_BAR + 64;
constexpr int SMEM_BYTES = 4 * 49152 + 8 * 2304 + 1024 + 256;
static_assert(R_END + 1024 <= SMEM_BYTES, "smem");

__device__ __forceinline__ void recurrence(uint32_t sb, const bf16* __restrict__ Wq, const bf16* __restrict__ Wk, const bf16* __restrict__ Wv, const bf16* __restrict__ Wo) {
  const int tid = threadIdx.x, warp = tid >> 5, lane = tid & 31, g = lane >> 2, t = lane & 3;
  const int h = blockIdx.x >> 1, j = blockIdx.x & 1;
  const uint32_t peer = j ^ 1;
  const uint32_t mQK = sb + R_BAR, mV = sb + R_BAR + 8;
  uint32_t A[2][16][4];
  const uint32_t stg = sb + R_WR;
  const int lm = lane >> 3, lr = lane & 7;
  for (int i = tid; i < 128 * 32; i += 384) { int r = i >> 5, c = i & 31; cp16(stg + r * 528 + c * 16, Wo + ((size_t)(h * 128 + r)) * DM + 256 * j + c * 8); }
  asm volatile("cp.async.wait_all;" ::: "memory"); __syncthreads();
  if (warp < 8) {
    #pragma unroll
    for (int mt = 0; mt < 2; mt++)
      #pragma unroll
      for (int ks = 0; ks < 8; ks++) {
        int k = 32 * (ks >> 1) + 8 * (lr >> 1) + (lr & 1) + 4 * (ks & 1) + 2 * (lm >> 1);
        uint32_t r[4]; ldsm4t(r, stg + k * 528 + (32 * warp + 16 * mt + 8 * (lm & 1)) * 2);
        sts128(sb + R_WO + ((warp * 16 + mt * 8 + ks) * 32 + lane) * 16, make_uint4(r[0], r[1], r[2], r[3]));
      }
  }
  __syncthreads();
  #pragma unroll 1
  for (int m = 0; m < 3; m++) {
    const bf16* W = m == 0 ? Wq : (m == 1 ? Wk : Wv);
    for (int i = tid; i < 256 * 16; i += 384) { int r = i >> 4, c = i & 15; cp16(stg + r * 272 + c * 16, W + ((size_t)(256 * j + r)) * 4096 + h * 128 + c * 8); }
    asm volatile("cp.async.wait_all;" ::: "memory"); __syncthreads();
    if ((warp >> 2) == m) {
      #pragma unroll
      for (int mt = 0; mt < 2; mt++)
        #pragma unroll
        for (int ks = 0; ks < 16; ks++) {
          int k = 32 * (ks >> 1) + 8 * (lr >> 1) + (lr & 1) + 4 * (ks & 1) + 2 * (lm >> 1);
          ldsm4t(A[mt][ks], stg + k * 272 + (32 * (warp & 3) + 16 * mt + 8 * (lm & 1)) * 2);
        }
    }
    __syncthreads();
  }
  if (warp < 8) {
    #pragma unroll
    for (int ks = 0; ks < 16; ks++) sts128(sb + R_WR + ((warp * 16 + ks) * 32 + lane) * 16, make_uint4(A[1][ks][0], A[1][ks][1], A[1][ks][2], A[1][ks][3]));
  }
  for (int i = tid; i < 2 * 8 * 17; i += 384) { int b = i / 136, r = i % 136; sts128(sb + R_VT + b * VT_SZ + 40 * 272 + r * 16, make_uint4(0, 0, 0, 0)); }
  const int vt = tid - 256;
  __syncthreads();
  const float scale = 0.08838834764831845f;
  if (warp >= 8) {
    auto prefetch = [&](int s) {
      if ((s & 3) == 0) { wait_flag(&g_fl.tile[s >> 2][h >> 1], 1); wait_flag(&g_fl.tile[s >> 2][16 + (h >> 1)], 1); }
      const bf16* src = g_qkv + (size_t)(32 * s) * QW + h * 128;
      uint32_t kb = sb + R_KT + (s & 1) * KT_SZ, vb = sb + R_VT + (s & 1) * VT_SZ;
      #pragma unroll
      for (int i = 0; i < 4; i++) { int idx = vt + 128 * i, r = idx >> 4, c = idx & 15;
        cp16(kb + r * 320 + c * 16, src + (size_t)r * QW + c * 8); cp16(vb + r * 272 + c * 16, src + (size_t)r * QW + 4096 + c * 8); }
      asm volatile("cp.async.wait_all;" ::: "memory");
      bar_arrive(5 + (s & 1), 384);
    };
    auto publish = [&](int s) {
      if (j == 0) { uint4 v = lds128(sb + R_KT + (s & 1) * KT_SZ + (32 + (vt >> 4)) * 320 + (vt & 15) * 16);
        __stcg((uint4*)(g_km + ((size_t)(s * 32 + h)) * 1024) + vt, v); }
      else { uint32_t vb = sb + R_VT + (s & 1) * VT_SZ + 32 * 272 + vt * 2; uint32_t e[8];
        #pragma unroll
        for (int k = 0; k < 8; k++) { unsigned short x; asm volatile("ld.shared.u16 %0, [%1];" : "=h"(x) : "r"(vb + k * 272) : "memory"); e[k] = x; }
        __stcg((uint4*)(g_vmT + ((size_t)(s * 32 + h)) * 1024) + vt, make_uint4(e[0] | (e[1] << 16), e[2] | (e[3] << 16), e[4] | (e[5] << 16), e[6] | (e[7] << 16))); }
    };
    auto flag = [&](int s) { __syncwarp(); if (lane == 0) { __threadfence(); atomicAdd(&g_fl.prog[s >> 2][h], 1); } };
    prefetch(0);
    #pragma unroll 1
    for (int s = 0; s < NSTEP; s++) {
      if (vt == 0) mbar_expect(mV, 4096);
      bar_sync(4, 384);
      float c[4][4];
      #pragma unroll
      for (int i = 0; i < 4; i++) { c[i][0] = c[i][1] = c[i][2] = c[i][3] = 0.f; }
      #pragma unroll
      for (int p = 0; p < 8; p++) {
        uint4 b = lds128(sb + R_MEM + g * 576 + p * 64 + t * 16);
        mma16(c[0], A[0][2*p][0], A[0][2*p][1], A[0][2*p][2], A[0][2*p][3], b.x, b.y);
        mma16(c[1], A[1][2*p][0], A[1][2*p][1], A[1][2*p][2], A[1][2*p][3], b.x, b.y);
        mma16(c[2], A[0][2*p+1][0], A[0][2*p+1][1], A[0][2*p+1][2], A[0][2*p+1][3], b.z, b.w);
        mma16(c[3], A[1][2*p+1][0], A[1][2*p+1][1], A[1][2*p+1][2], A[1][2*p+1][3], b.z, b.w);
      }
      #pragma unroll
      for (int i = 0; i < 4; i++) { c[0][i] += c[2][i]; c[1][i] += c[3][i]; }
      const uint32_t rx = sb + R_RQK + (warp * 64 + lane) * 16;
      { uint32_t ra = mapa(rx, peer), rm = mapa(mV, peer);
        st_async_v4(ra, c[0][0], c[0][1], c[0][2], c[0][3], rm);
        st_async_v4(ra + 512, c[1][0], c[1][1], c[1][2], c[1][3], rm); }
      if (s > 0) publish(s - 1);
      mbar_wait(mV, s & 1);
      uint32_t dst = sb + R_VT + (s & 1) * VT_SZ + (32 + 2 * t) * 272 + (32 * (warp & 3) + g) * 2;
      #pragma unroll
      for (int mt = 0; mt < 2; mt++) { uint4 r = lds128(rx + 512 * mt);
        sts16(dst + mt * 32, c[mt][0] + __uint_as_float(r.x)); sts16(dst + mt * 32 + 272, c[mt][1] + __uint_as_float(r.y));
        sts16(dst + mt * 32 + 16, c[mt][2] + __uint_as_float(r.z)); sts16(dst + mt * 32 + 272 + 16, c[mt][3] + __uint_as_float(r.w)); }
      if (s < NSTEP - 1) { bar_arrive(3, 384); if (s < NSTEP - 2) prefetch(s + 1); }
      if (s > 0) flag(s - 1);
    }
    bar_sync(3, 384);
    publish(NSTEP - 1); flag(NSTEP - 1);
    return;
  }
  #pragma unroll 1
  for (int s = 0; s < NSTEP; s++) {
    TR(0); TR(1);
    {
      const int tid = otid(), l = tid & 31;
      if (tid == 0) mbar_expect(mQK, 8192);
      const float4* src = &g_acc[s][j][tid];
      uint4 v0, v1, v2; int it = 0; bool ok;
      do {
        asm volatile("ld.relaxed.gpu.global.v4.u32 {%0,%1,%2,%3}, [%4];" : "=r"(v0.x), "=r"(v0.y), "=r"(v0.z), "=r"(v0.w) : "l"(src) : "memory");
        asm volatile("ld.relaxed.gpu.global.v4.u32 {%0,%1,%2,%3}, [%4];" : "=r"(v1.x), "=r"(v1.y), "=r"(v1.z), "=r"(v1.w) : "l"(src + 256) : "memory");
        asm volatile("ld.relaxed.gpu.global.v4.u32 {%0,%1,%2,%3}, [%4];" : "=r"(v2.x), "=r"(v2.y), "=r"(v2.z), "=r"(v2.w) : "l"(src + 512) : "memory");
        ok = (v0.w == 0x42000000u) && (v1.w == 0x42000000u) && (v2.w == 0x42000000u);
      } while (!ok && ++it < SPIN_LIMIT);
      const uint32_t m = sb + R_MEM + (l & 3) * 1152 + ((tid >> 5) * 32 + (l >> 2)) * 2;
      sts16(m, __uint_as_float(v0.x)); sts16(m + 576, __uint_as_float(v0.y)); sts16(m + 16, __uint_as_float(v0.z));
      sts16(m + 592, __uint_as_float(v1.x)); sts16(m + 32, __uint_as_float(v1.y)); sts16(m + 608, __uint_as_float(v1.z));
      sts16(m + 48, __uint_as_float(v2.x)); sts16(m + 624, __uint_as_float(v2.y));
    }
    TR(2);
    bar_sync(1, 256);
    TR(3);
    float c[4][4];
    #pragma unroll
    for (int i = 0; i < 4; i++) { c[i][0] = c[i][1] = c[i][2] = c[i][3] = 0.f; }
    { const int l = otid() & 31; const uint32_t mbase = sb + R_MEM + (l >> 2) * 576 + (l & 3) * 16;
      #pragma unroll
      for (int p = 0; p < 8; p++) {
        uint4 b = lds128(mbase + p * 64);
        mma16(c[0], A[0][2*p][0], A[0][2*p][1], A[0][2*p][2], A[0][2*p][3], b.x, b.y);
        mma16(c[1], A[1][2*p][0], A[1][2*p][1], A[1][2*p][2], A[1][2*p][3], b.x, b.y);
        mma16(c[2], A[0][2*p+1][0], A[0][2*p+1][1], A[0][2*p+1][2], A[0][2*p+1][3], b.z, b.w);
        mma16(c[3], A[1][2*p+1][0], A[1][2*p+1][1], A[1][2*p+1][2], A[1][2*p+1][3], b.z, b.w);
      } }
    bar_arrive(4, 384);
    #pragma unroll
    for (int i = 0; i < 4; i++) { c[0][i] += c[2][i]; c[1][i] += c[3][i]; }
    const bool more = s < NSTEP - 1;
    {
      const int tid = otid(), lane = tid & 31, warp = tid >> 5;
      const uint32_t rx = sb + R_RQK + (warp * 64 + lane) * 16;
      { uint32_t ra = mapa(rx, peer), rm = mapa(mQK, peer);
        st_async_v4(ra, c[0][0], c[0][1], c[0][2], c[0][3], rm);
        st_async_v4(ra + 512, c[1][0], c[1][1], c[1][2], c[1][3], rm); }
      TR(4);
      if (more) {
        const uint32_t wb = sb + R_WO + (warp * 512 + lane) * 16;
        #pragma unroll
        for (int i = 0; i < 16; i++) { uint4 v = lds128(wb + i * 512); A[1][i][0] = v.x; A[1][i][1] = v.y; A[1][i][2] = v.z; A[1][i][3] = v.w; }
      }
      mbar_wait(mQK, s & 1);
      TR(5);
      uint32_t dst = (warp < 4 ? sb + R_Q : sb + R_KT + (s & 1) * KT_SZ + 32 * 320) + (lane & 3) * 640 + (32 * (warp & 3) + (lane >> 2)) * 2;
      #pragma unroll
      for (int mt = 0; mt < 2; mt++) { uint4 r = lds128(rx + 512 * mt);
        sts16(dst + mt * 32, c[mt][0] + __uint_as_float(r.x)); sts16(dst + mt * 32 + 320, c[mt][1] + __uint_as_float(r.y));
        sts16(dst + mt * 32 + 16, c[mt][2] + __uint_as_float(r.z)); sts16(dst + mt * 32 + 320 + 16, c[mt][3] + __uint_as_float(r.w)); }
    }
    if (!more) { bar_arrive(3, 384); break; }
    TR(8);
    bar_sync(5 + (s & 1), 384);
    TR(9);
    {
      const int tid = otid(), lane = tid & 31, warp = tid >> 5, g = lane >> 2, t = lane & 3;
      if (warp < 5) {
        float s0[4] = {0, 0, 0, 0}, s1[4] = {0, 0, 0, 0};
        const uint32_t qb = sb + R_Q + g * 320 + t * 16, kq_ = sb + R_KT + (s & 1) * KT_SZ + (8 * warp + g) * 320 + t * 16;
        #pragma unroll
        for (int p = 0; p < 4; p++) {
          uint4 qa = lds128(qb + p * 64), kq = lds128(kq_ + p * 64);
          mma16(s0, qa.x, 0, qa.y, 0, kq.x, kq.y); mma16(s1, qa.z, 0, qa.w, 0, kq.z, kq.w);
        }
        float a = rbf(rbf(s0[0] + s1[0]) * scale), b = rbf(rbf(s0[1] + s1[1]) * scale);
        asm volatile("st.shared.v2.f32 [%0], {%1,%2};" ::"r"(sb + R_S + g * 224 + (8 * warp + 2 * t) * 4), "f"(a), "f"(b) : "memory");
      }
      TR(10);
      bar_sync(2, 256);
      TR(11);
      float sv[10];
      #pragma unroll
      for (int i = 0; i < 5; i++) asm volatile("ld.shared.v2.f32 {%0,%1}, [%2];" : "=f"(sv[2*i]), "=f"(sv[2*i+1]) : "r"(sb + R_S + g * 224 + (8 * i + 2 * t) * 4) : "memory");
      float mx = sv[0];
      #pragma unroll
      for (int i = 1; i < 10; i++) mx = fmaxf(mx, sv[i]);
      mx = fmaxf(mx, __shfl_xor_sync(~0u, mx, 1)); mx = fmaxf(mx, __shfl_xor_sync(~0u, mx, 2));
      float sum = 0;
      #pragma unroll
      for (int i = 0; i < 10; i++) { sv[i] = __expf(sv[i] - mx); sum += sv[i]; }
      sum += __shfl_xor_sync(~0u, sum, 1); sum += __shfl_xor_sync(~0u, sum, 2);
      float inv = __fdividef(1.f, sum);
      uint32_t P[6];
      #pragma unroll
      for (int i = 0; i < 5; i++) P[i] = pack2(sv[2*i] * inv, sv[2*i+1] * inv);
      P[5] = 0;
      TR(6);
      float o0[4] = {0, 0, 0, 0}, o1[4] = {0, 0, 0, 0};
      const uint32_t vb = sb + R_VT + (s & 1) * VT_SZ + (lane & 15) * 272 + (16 * warp + 8 * (lane >> 4)) * 2;
      #pragma unroll
      for (int kk = 0; kk < 3; kk++) {
        if (kk == 2) bar_sync(3, 384);
        uint32_t r[4]; ldsm4t(r, vb + 16 * kk * 272);
        mma16(o0, P[2*kk], 0, P[2*kk+1], 0, r[0], r[1]); mma16(o1, P[2*kk], 0, P[2*kk+1], 0, r[2], r[3]);
      }
      sts32(sb + R_O + g * 320 + (16 * warp + 2 * t) * 2, pack2(o0[0], o0[1]));
      sts32(sb + R_O + g * 320 + (16 * warp + 8 + 2 * t) * 2, pack2(o1[0], o1[1]));
      bar_sync(1, 256);
      #pragma unroll
      for (int i = 0; i < 4; i++) { c[i][0] = c[i][1] = c[i][2] = c[i][3] = 0.f; }
      #pragma unroll
      for (int p = 0; p < 4; p++) {
        uint4 b = lds128(sb + R_O + g * 320 + p * 64 + t * 16);
        mma16(c[0], A[1][2*p][0], A[1][2*p][1], A[1][2*p][2], A[1][2*p][3], b.x, b.y);
        mma16(c[1], A[1][8+2*p][0], A[1][8+2*p][1], A[1][8+2*p][2], A[1][8+2*p][3], b.x, b.y);
        mma16(c[2], A[1][2*p+1][0], A[1][2*p+1][1], A[1][2*p+1][2], A[1][2*p+1][3], b.z, b.w);
        mma16(c[3], A[1][8+2*p+1][0], A[1][8+2*p+1][1], A[1][8+2*p+1][2], A[1][8+2*p+1][3], b.z, b.w);
      }
      #pragma unroll
      for (int i = 0; i < 4; i++) { c[0][i] += c[2][i]; c[1][i] += c[3][i]; }
      TR(7);
      float4* dst = &g_acc[s + 1][j][tid];
      asm volatile("red.relaxed.gpu.global.add.v4.f32 [%0], {%1,%2,%3,%4};" ::"l"(dst), "f"(c[0][0]), "f"(c[0][1]), "f"(c[0][2]), "f"(1.0f) : "memory");
      asm volatile("red.relaxed.gpu.global.add.v4.f32 [%0], {%1,%2,%3,%4};" ::"l"(dst + 256), "f"(c[0][3]), "f"(c[1][0]), "f"(c[1][1]), "f"(1.0f) : "memory");
      asm volatile("red.relaxed.gpu.global.add.v4.f32 [%0], {%1,%2,%3,%4};" ::"l"(dst + 512), "f"(c[1][2]), "f"(c[1][3]), "f"(0.f), "f"(1.0f) : "memory");
      const uint32_t wb = sb + R_WR + (warp * 512 + lane) * 16;
      #pragma unroll
      for (int i = 0; i < 16; i++) { uint4 v = lds128(wb + i * 512); A[1][i][0] = v.x; A[1][i][1] = v.y; A[1][i][2] = v.z; A[1][i][3] = v.w; }
    }
  }
}

constexpr int I_M1 = 512, I_Q = 624, I_M2 = 880, I_AT = 1008, I_G = I_AT + 32, GSZ = 56, I_END = I_G + 15 * GSZ + 24;
constexpr int B_STG = 4 * 49152, B_BAR = B_STG + 8 * 2304;
struct Item { int type, rb, nt, ks; };
__device__ __forceinline__ Item decode(int it) {
  Item r; r.ks = 0;
  if (it < I_M1) { r.type = 0; r.rb = it >> 5; r.nt = it & 31; }
  else if (it < I_Q) { int i = it - I_M1; r.type = 1; r.rb = i / 7; r.nt = i % 7; }
  else if (it < I_M2) { int i = it - I_Q; r.type = 0; r.rb = i >> 4; r.nt = 32 + (i & 15); }
  else if (it < I_AT) { int i = it - I_M2; r.type = 2; r.rb = i >> 3; r.nt = (i >> 2) & 1; r.ks = i & 3; }
  else if (it < I_G) { r.type = 3; r.rb = 0; r.nt = it - I_AT; }
  else {
    int i = it - I_G, gi = i / GSZ, q = i % GSZ; if (gi == 15) q += 32;
    if (q < 32) { r.type = 3; r.rb = gi + 1; r.nt = q; }
    else if (q < 48) { r.type = 4; r.rb = gi; r.nt = (q - 32) >> 3; r.ks = (q - 32) & 7; }
    else { r.type = 5; r.rb = gi; r.nt = q - 48; } }
  return r;
}
__device__ __forceinline__ float gelu_t(float x) { float u = 0.7978845608028654f * (x + 0.044715f * x * x * x); float th; asm("tanh.approx.f32 %0, %1;" : "=f"(th) : "f"(u)); float hx = 0.5f * x; return fmaf(hx, th, hx); }

__device__ __forceinline__ void bulk(uint32_t sb, const Maps& mp, const bf16* __restrict__ x, const bf16* __restrict__ b1, const bf16* __restrict__ b2, bf16* __restrict__ out) {
  const int tid = threadIdx.x, warp = tid >> 5, lane = tid & 31, g = lane >> 2, t = lane & 3;
  const int bid = blockIdx.x - NREC;
  const uint32_t full = sb + B_BAR, empty = sb + B_BAR + 32, ifull = sb + B_BAR + 64, iempty = sb + B_BAR + 80;
  volatile int* ring = (volatile int*)(__cvta_shared_to_generic(sb + B_BAR + 96));
  if (warp >= 8) {
    asm volatile("setmaxnreg.dec.sync.aligned.u32 40;");
    if (tid == 256) {
      uint32_t st = 0, ph = 0;
      for (int n = 0;; n++) {
        int it = n == 0 ? bid : NBULK + atomicAdd(&g_fl.next, 1);
        mbar_wait(iempty + (n & 1) * 8, ((n >> 1) & 1) ^ 1);
        ring[n & 1] = it; mbar_arrive(ifull + (n & 1) * 8);
        if (it >= I_END) break;
        Item I = decode(it);
        if (I.type == 5) continue;
        if (I.type == 3) {
          wait_flag(&g_fl.tile[I.rb][I.nt >> 1], 1); wait_flag(&g_fl.tile[I.rb][16 + (I.nt >> 1)], 1); wait_flag(&g_fl.tile[I.rb][32 + (I.nt >> 1)], 1);
          fence_async();
          for (int m = 0; m < 3; m++) {
            mbar_wait(empty + st * 8, ph ^ 1);
            mbar_expect(full + st * 8, 32768);
            int col = (m == 0 ? 8192 : (m == 1 ? 0 : 4096)) + I.nt * 128;
            tma2d(sb + st * 49152, &mp.qkv, col, I.rb * 128, full + st * 8);
            tma2d(sb + st * 49152 + 16384, &mp.qkv, col + 64, I.rb * 128, full + st * 8);
            if (++st == 4) { st = 0; ph ^= 1; }
          }
          continue;
        }
        const CUtensorMap *ma, *mb; int nkb = 8, kb0 = 0, n0;
        if (I.type == 0) { ma = &mp.xn; mb = I.nt < 16 ? &mp.wk : (I.nt < 32 ? &mp.wv : &mp.wq); n0 = (I.nt & 15) * 256; }
        else if (I.type == 1) { ma = &mp.y; mb = &mp.w1; n0 = I.nt * 256; }
        else if (I.type == 2) { ma = &mp.hid; mb = &mp.w2; n0 = I.nt * 256; nkb = 7; kb0 = I.ks * 7; wait_flag(&g_fl.hid[I.rb], 7); fence_async(); }
        else { ma = &mp.o; mb = &mp.wo; n0 = I.nt * 256; kb0 = I.ks * 8; wait_flag(&g_fl.o[I.rb][I.ks], 4); fence_async(); }
        for (int kb = kb0; kb < kb0 + nkb; kb++) {
          mbar_wait(empty + st * 8, ph ^ 1);
          mbar_expect(full + st * 8, 49152);
          uint32_t sa = sb + st * 49152;
          tma2d(sa, ma, kb * 64, I.rb * 128, full + st * 8);
          #pragma unroll
          for (int q = 0; q < 4; q++) tma2d(sa + 16384 + q * 8192, mb, n0 + q * 64, kb * 64, full + st * 8);
          if (++st == 4) { st = 0; ph ^= 1; }
        }
      }
    } else if (warp == 9) {
      for (int n = 0;; n++) {
        mbar_wait(ifull + (n & 1) * 8, (n >> 1) & 1);
        int it = ring[n & 1];
        if (it >= I_END) break;
        Item I = decode(it);
        bar_sync(6 + (n & 1), 288);
        if (lane == 0) {
          if (I.type != 5) {
            fence_async(); __threadfence();
            int* f = I.type == 0 ? &g_fl.tile[I.rb][I.nt] : I.type == 1 ? &g_fl.hid[I.rb] : I.type == 2 ? &g_fl.z[I.rb][0] : I.type == 3 ? &g_fl.o[I.rb][I.nt >> 2] : &g_fl.s[I.rb][0];
            atomicAdd(f, 1);
          }
          mbar_arrive(iempty + (n & 1) * 8);
        }
      }
    }
    return;
  }
  asm volatile("setmaxnreg.inc.sync.aligned.u32 232;");
  const int wg = warp >> 2;
  const uint32_t stg = sb + B_STG + warp * 2304;
  const int lm = lane >> 3, lr = lane & 7;
  uint32_t st = 0, ph = 0;
  float d[128];
  #pragma unroll 1
  for (int n = 0;; n++) {
    mbar_wait(ifull + (n & 1) * 8, (n >> 1) & 1);
    const int it = ring[n & 1];
    __syncwarp(); if (lane == 0) mbar_arrive(iempty + (n & 1) * 8);
    if (it >= I_END) break;
    Item I = decode(it);
    const int row0 = I.rb * 128 + warp * 16;
    TB(0);
    if (I.type == 5) {
      wait_flag(&g_fl.s[I.rb][0], 16); wait_flag(&g_fl.z[I.rb][0], 8);
      #pragma unroll
      for (int i = 0; i < 4; i++) {
        size_t off = (size_t)(I.rb * 128 + I.nt * 16 + warp * 2 + (i >> 1)) * DM + (i & 1) * 256 + lane * 8;
        float4 s0 = __ldcg((const float4*)(g_s + off)), s1 = __ldcg((const float4*)(g_s + off + 4));
        float4 z0 = __ldcg((const float4*)(g_z + off)), z1 = __ldcg((const float4*)(g_z + off + 4));
        uint4 xv = *(const uint4*)(x + off), bv = *(const uint4*)(b2 + (i & 1) * 256 + lane * 8);
        float sa[8] = {s0.x, s0.y, s0.z, s0.w, s1.x, s1.y, s1.z, s1.w}, za[8] = {z0.x, z0.y, z0.z, z0.w, z1.x, z1.y, z1.z, z1.w}, r[8];
        #pragma unroll
        for (int e = 0; e < 8; e++) { float xx = __bfloat162float(((const bf16*)&xv)[e]), bb = __bfloat162float(((const bf16*)&bv)[e]);
          float u = rbf(rbf(za[e]) + bb); float gg = rbf(__fdividef(u, 1.f + __expf(-u))); r[e] = xx + rbf(rbf(sa[e]) * gg); }
        *(uint4*)(out + off) = make_uint4(pack2(r[0], r[1]), pack2(r[2], r[3]), pack2(r[4], r[5]), pack2(r[6], r[7]));
      }
      bar_arrive(6 + (n & 1), 288);
      continue;
    }
    if (I.type == 3) {
      const int h = I.nt, seg = warp >> 1, half = warp & 1, step = I.rb * 4 + seg;
      wait_flag(&g_fl.prog[I.rb][h], 32);
      uint32_t kmr[16], vmr[16];
      { const uint32_t* km = (const uint32_t*)(g_km + ((size_t)(step * 32 + h)) * 1024) + g * 64 + t;
        const uint32_t* vm = (const uint32_t*)(g_vmT + ((size_t)(step * 32 + h)) * 1024) + g * 4 + t;
        #pragma unroll
        for (int i = 0; i < 16; i++) { kmr[i] = __ldcg(km + i * 4); vmr[i] = __ldcg(vm + i * 32); } }
      uint32_t sQ = sb + st * 49152; mbar_wait(full + st * 8, ph); uint32_t eQ = empty + st * 8; if (++st == 4) { st = 0; ph ^= 1; }
      uint32_t sK = sb + st * 49152; mbar_wait(full + st * 8, ph); uint32_t eK = empty + st * 8; if (++st == 4) { st = 0; ph ^= 1; }
      float sc[5][4];
      #pragma unroll
      for (int i = 0; i < 5; i++) { sc[i][0] = sc[i][1] = sc[i][2] = sc[i][3] = 0.f; }
      #pragma unroll
      for (int ks = 0; ks < 8; ks++) {
        uint32_t a[4]; { int r = warp * 16 + 8 * (lm & 1) + lr, c8 = 2 * ks + (lm >> 1); ldsm4(a, sQ + (c8 >> 3) * 16384 + r * 128 + (((c8 & 7) ^ (r & 7)) << 4)); }
        #pragma unroll
        for (int np = 0; np < 2; np++) {
          if (np == 1 && half == 0) continue;
          uint32_t b[4]; int r = seg * 32 + 16 * np + 8 * (lm >> 1) + lr, c8 = 2 * ks + (lm & 1);
          ldsm4(b, sK + (c8 >> 3) * 16384 + r * 128 + (((c8 & 7) ^ (r & 7)) << 4));
          mma16(sc[2*np], a[0], a[1], a[2], a[3], b[0], b[1]); mma16(sc[2*np+1], a[0], a[1], a[2], a[3], b[2], b[3]);
        }
        mma16(sc[4], a[0], a[1], a[2], a[3], kmr[2*ks], kmr[2*ks+1]);
      }
      __syncwarp(); if (lane == 0) { mbar_arrive(eQ); mbar_arrive(eK); }
      const float scale = 0.08838834764831845f;
      uint32_t P[5][2];
      #pragma unroll
      for (int rr = 0; rr < 2; rr++) {
        const int qi = 16 * half + g + 8 * rr;
        float mx = -3.0e38f;
        #pragma unroll
        for (int i = 0; i < 5; i++)
          #pragma unroll
          for (int e = 0; e < 2; e++) { float v = rbf(rbf(sc[i][2*rr+e]) * scale); if (i < 4 && 8 * i + 2 * t + e > qi) v = -1.0e9f; sc[i][2*rr+e] = v; mx = fmaxf(mx, v); }
        mx = fmaxf(mx, __shfl_xor_sync(~0u, mx, 1)); mx = fmaxf(mx, __shfl_xor_sync(~0u, mx, 2));
        float sum = 0;
        #pragma unroll
        for (int i = 0; i < 5; i++)
          #pragma unroll
          for (int e = 0; e < 2; e++) { float v = __expf(sc[i][2*rr+e] - mx); sc[i][2*rr+e] = v; sum += v; }
        sum += __shfl_xor_sync(~0u, sum, 1); sum += __shfl_xor_sync(~0u, sum, 2);
        float inv = __fdividef(1.f, sum);
        #pragma unroll
        for (int i = 0; i < 5; i++) P[i][rr] = pack2(sc[i][2*rr] * inv, sc[i][2*rr+1] * inv);
      }
      uint32_t sV = sb + st * 49152; mbar_wait(full + st * 8, ph); uint32_t eV = empty + st * 8; if (++st == 4) { st = 0; ph ^= 1; }
      #pragma unroll
      for (int i = 0; i < 64; i++) d[i] = 0.f;
      #pragma unroll
      for (int n2 = 0; n2 < 8; n2++) {
        #pragma unroll
        for (int kk = 0; kk < 2; kk++) {
          if (kk == 1 && half == 0) continue;
          uint32_t b[4]; int r = seg * 32 + 16 * kk + 8 * (lm & 1) + lr, c8 = 2 * n2 + (lm >> 1);
          ldsm4t(b, sV + (c8 >> 3) * 16384 + r * 128 + (((c8 & 7) ^ (r & 7)) << 4));
          mma16(d + 8 * n2, P[2*kk][0], P[2*kk][1], P[2*kk+1][0], P[2*kk+1][1], b[0], b[1]);
          mma16(d + 8 * n2 + 4, P[2*kk][0], P[2*kk][1], P[2*kk+1][0], P[2*kk+1][1], b[2], b[3]);
        }
        mma8(d + 8 * n2, P[4][0], P[4][1], vmr[2*n2]); mma8(d + 8 * n2 + 4, P[4][0], P[4][1], vmr[2*n2+1]);
      }
      __syncwarp(); if (lane == 0) mbar_arrive(eV);
      #pragma unroll
      for (int ch = 0; ch < 2; ch++) {
        #pragma unroll
        for (int i = 0; i < 8; i++) { const float* a = d + ch * 32 + i * 4;
          sts32(stg + g * 144 + i * 16 + t * 4, pack2(a[0], a[1])); sts32(stg + (g + 8) * 144 + i * 16 + t * 4, pack2(a[2], a[3])); }
        __syncwarp();
        #pragma unroll
        for (int i = 0; i < 4; i++) { int r = i * 4 + lm; uint4 v = lds128(stg + r * 144 + lr * 16);
          *(uint4*)(g_o + (size_t)(row0 + r) * 4096 + h * 128 + ch * 64 + lr * 8) = v; }
        __syncwarp();
      }
      bar_arrive(6 + (n & 1), 288);
      continue;
    }
    const int nkb = I.type == 2 ? 7 : 8;
    uint32_t prev = 0;
    for (int kb = 0; kb < nkb; kb++) {
      mbar_wait(full + st * 8, ph);
      uint32_t sa = sb + st * 49152;
      asm volatile("wgmma.fence.sync.aligned;" ::: "memory");
      #pragma unroll
      for (int k = 0; k < 4; k++)
        wgmma256(d, mkdesc(sa + wg * 8192 + k * 32, 16, 1024), mkdesc(sa + 16384 + k * 2048, 8192, 1024), (kb | k) != 0);
      asm volatile("wgmma.commit_group.sync.aligned;" ::: "memory");
      if (kb > 0) { asm volatile("wgmma.wait_group.sync.aligned 1;" ::: "memory"); if (lane == 0) mbar_arrive(prev); }
      prev = empty + st * 8;
      if (++st == 4) { st = 0; ph ^= 1; }
    }
    asm volatile("wgmma.wait_group.sync.aligned 0;" ::: "memory");
    if (lane == 0) mbar_arrive(prev);
    TB(1);
    if (I.type <= 1) {
      bf16* dst; int ld;
      if (I.type == 0) { dst = g_qkv + (size_t)row0 * QW + I.nt * 256; ld = QW; } else { dst = g_hid + (size_t)row0 * FF + I.nt * 256; ld = FF; }
      #pragma unroll
      for (int ch = 0; ch < 4; ch++) {
        #pragma unroll
        for (int i = 0; i < 8; i++) { float* a = d + ch * 32 + i * 4;
          if (I.type == 1) { float2 bb = __bfloat1622float2(*(const __nv_bfloat162*)(b1 + I.nt * 256 + ch * 64 + i * 8 + 2 * t));
            a[0] = gelu_t(rbf(rbf(a[0]) + bb.x)); a[1] = gelu_t(rbf(rbf(a[1]) + bb.y)); a[2] = gelu_t(rbf(rbf(a[2]) + bb.x)); a[3] = gelu_t(rbf(rbf(a[3]) + bb.y)); }
          sts32(stg + g * 144 + i * 16 + t * 4, pack2(a[0], a[1])); sts32(stg + (g + 8) * 144 + i * 16 + t * 4, pack2(a[2], a[3])); }
        __syncwarp();
        #pragma unroll
        for (int i = 0; i < 4; i++) { int r = i * 4 + lm; uint4 v = lds128(stg + r * 144 + lr * 16); *(uint4*)(dst + (size_t)r * ld + ch * 64 + lr * 8) = v; }
        __syncwarp();
      }
    } else {
      float* dst = (I.type == 2 ? g_z : g_s) + (size_t)(row0 + g) * DM + I.nt * 256 + 2 * t;
      #pragma unroll
      for (int i = 0; i < 32; i++) {
        asm volatile("red.relaxed.gpu.global.add.v2.f32 [%0], {%1,%2};" ::"l"(dst + i * 8), "f"(d[4*i]), "f"(d[4*i+1]) : "memory");
        asm volatile("red.relaxed.gpu.global.add.v2.f32 [%0], {%1,%2};" ::"l"(dst + 8 * DM + i * 8), "f"(d[4*i+2]), "f"(d[4*i+3]) : "memory");
      }
    }
    bar_arrive(6 + (n & 1), 288);
  }
}

__global__ void __cluster_dims__(2, 1, 1) __launch_bounds__(384, 1)
main_kernel(const __grid_constant__ Maps mp, const bf16* x, const bf16* Wq, const bf16* Wk, const bf16* Wv, const bf16* Wo, const bf16* b1, const bf16* b2, bf16* out) {
  extern __shared__ __align__(1024) uint8_t smem_raw[];
  const uint32_t sb = smem_u32(smem_raw);
  if (sb & 1023) __trap();
  if (threadIdx.x == 0) {
    if (blockIdx.x < NREC) { mbar_init(sb + R_BAR, 1); mbar_init(sb + R_BAR + 8, 1); }
    else { for (int i = 0; i < 4; i++) { mbar_init(sb + B_BAR + i * 8, 1); mbar_init(sb + B_BAR + 32 + i * 8, 8); }
      for (int i = 0; i < 2; i++) { mbar_init(sb + B_BAR + 64 + i * 8, 1); mbar_init(sb + B_BAR + 80 + i * 8, 9); } }
    asm volatile("fence.mbarrier_init.release.cluster;" ::: "memory");
  }
  asm volatile("barrier.cluster.arrive.release.aligned; barrier.cluster.wait.acquire.aligned;" ::: "memory");
  if (blockIdx.x < NREC) recurrence(sb, Wq, Wk, Wv, Wo);
  else bulk(sb, mp, x, b1, b2, out);
}

typedef CUresult (*EncFn)(CUtensorMap*, CUtensorMapDataType, cuuint32_t, void*, const cuuint64_t*, const cuuint64_t*, const cuuint32_t*, const cuuint32_t*, CUtensorMapInterleave, CUtensorMapSwizzle, CUtensorMapL2promotion, CUtensorMapFloatOOBfill);
static void mk(EncFn f, CUtensorMap* m, const void* p, uint64_t rows, uint64_t cols, uint32_t boxr) {
  cuuint64_t dims[2] = {cols, rows}, str[1] = {cols * 2}; cuuint32_t box[2] = {64, boxr}, es[2] = {1, 1};
  f(m, CU_TENSOR_MAP_DATA_TYPE_BFLOAT16, 2, (void*)p, dims, str, box, es, CU_TENSOR_MAP_INTERLEAVE_NONE, CU_TENSOR_MAP_SWIZZLE_128B, CU_TENSOR_MAP_L2_PROMOTION_L2_256B, CU_TENSOR_MAP_FLOAT_OOB_FILL_NONE);
}
extern "C" void kernel_launch(void* const* d_in, const int* in_sizes, int n_in, void* d_out, int out_size) {
  const bf16 *x = (const bf16*)d_in[0], *mem0 = (const bf16*)d_in[1], *Wq = (const bf16*)d_in[2], *Wk = (const bf16*)d_in[3], *Wv = (const bf16*)d_in[4], *Wo = (const bf16*)d_in[5];
  const bf16 *w1 = (const bf16*)d_in[8], *b1 = (const bf16*)d_in[9], *w2 = (const bf16*)d_in[10], *b2 = (const bf16*)d_in[11];
  void* fn = nullptr; cudaDriverEntryPointQueryResult qr;
  cudaGetDriverEntryPoint("cuTensorMapEncodeTiled", &fn, cudaEnableDefault, &qr);
  EncFn f = (EncFn)fn;
  void *pxn, *py, *ph, *po, *pq;
  cudaGetSymbolAddress(&pxn, g_xn); cudaGetSymbolAddress(&py, g_y); cudaGetSymbolAddress(&ph, g_hid); cudaGetSymbolAddress(&po, g_o); cudaGetSymbolAddress(&pq, g_qkv);
  Maps mp;
  mk(f, &mp.xn, pxn, SEQ, DM, 128); mk(f, &mp.y, py, SEQ, DM, 128); mk(f, &mp.hid, ph, SEQ, FF, 128); mk(f, &mp.o, po, SEQ, 4096, 128); mk(f, &mp.qkv, pq, SEQ, QW, 128);
  mk(f, &mp.wk, Wk, DM, 4096, 64); mk(f, &mp.wv, Wv, DM, 4096, 64); mk(f, &mp.wq, Wq, DM, 4096, 64);
  mk(f, &mp.w1, w1, DM, FF, 64); mk(f, &mp.w2, w2, FF, DM, 64); mk(f, &mp.wo, Wo, 4096, DM, 64);
  cudaFuncSetAttribute(main_kernel, cudaFuncAttributeMaxDynamicSharedMemorySize, SMEM_BYTES);
  prologue_kernel<<<256, 256, 0, cudaStreamPerThread>>>(x, mem0);
  main_kernel<<<NCTA, 384, SMEM_BYTES, cudaStreamPerThread>>>(mp, x, Wq, Wk, Wv, Wo, b1, b2, (bf16*)d_out);
}
```

```cpp
#include <cuda_runtime.h>
#include <cuda_bf16.h>
#include <cuda.h>
#include <stdint.h>

typedef __nv_bfloat16 bf16;
constexpr int SEQ = 2048, DM = 512, FF = 1792, QW = 12288, NSTEP = 64;
constexpr int NREC = 64, NBULK = 68, NCTA = 132;
constexpr int SPIN_LIMIT = 1 << 22;

__device__ bf16 g_xn[SEQ * DM];
__device__ bf16 g_y[SEQ * DM];
__device__ bf16 g_qkv[(size_t)SEQ * QW];
__device__ bf16 g_hid[SEQ * FF];
__device__ bf16 g_o[(size_t)SEQ * 4096];
__device__ float g_z[SEQ * DM];
__device__ float g_s[SEQ * DM];
__device__ float4 g_acc[NSTEP][2][768];
__device__ bf16 g_km[NSTEP * 32 * 8 * 128];
__device__ bf16 g_vmT[NSTEP * 32 * 128 * 8];
struct Flags { int tile[16][48]; int hid[16]; int z[16][2]; int o[16][8]; int s[16][2]; int prog[16][32]; int next; };
__device__ Flags g_fl;

#define TR(i)
#define TB(i)
struct Maps { CUtensorMap xn, y, hid, o, qkv, wk, wv, wq, w1, w2, wo; };

__device__ __forceinline__ uint32_t smem_u32(const void* p) { return (uint32_t)__cvta_generic_to_shared(p); }
__device__ __forceinline__ int otid() { int t; asm volatile("mov.u32 %0, %%tid.x;" : "=r"(t)); return t; }
__device__ __forceinline__ uint32_t mapa(uint32_t a, uint32_t r) { uint32_t o; asm volatile("mapa.shared::cluster.u32 %0, %1, %2;" : "=r"(o) : "r"(a), "r"(r)); return o; }
__device__ __forceinline__ void st_async_v4(uint32_t addr, float a, float b, float c, float d, uint32_t mbar) {
  asm volatile("st.async.weak.shared::cluster.mbarrier::complete_tx::bytes.v4.b32 [%0], {%1,%2,%3,%4}, [%5];" ::"r"(addr), "r"(__float_as_uint(a)), "r"(__float_as_uint(b)), "r"(__float_as_uint(c)), "r"(__float_as_uint(d)), "r"(mbar) : "memory"); }
__device__ __forceinline__ void mbar_init(uint32_t m, int c) { asm volatile("mbarrier.init.shared::cta.b64 [%0], %1;" ::"r"(m), "r"(c) : "memory"); }
__device__ __forceinline__ void mbar_expect(uint32_t m, int bytes) { asm volatile("mbarrier.arrive.expect_tx.shared::cta.b64 _, [%0], %1;" ::"r"(m), "r"(bytes) : "memory"); }
__device__ __forceinline__ void mbar_arrive(uint32_t m) { asm volatile("mbarrier.arrive.shared::cta.b64 _, [%0];" ::"r"(m) : "memory"); }
__device__ __forceinline__ void mbar_wait(uint32_t m, uint32_t parity) {
  uint32_t ok; int it = 0;
  do { asm volatile("{.reg .pred p; mbarrier.try_wait.parity.shared::cta.b64 p, [%1], %2; selp.u32 %0,1,0,p;}" : "=r"(ok) : "r"(m), "r"(parity) : "memory"); } while (!ok && ++it < SPIN_LIMIT); }
__device__ __forceinline__ void mbar_wait_cl(uint32_t m, uint32_t parity) {
  uint32_t ok; int it = 0;
  do { asm volatile("{.reg .pred p; mbarrier.try_wait.parity.acquire.cluster.shared::cta.b64 p, [%1], %2; selp.u32 %0,1,0,p;}" : "=r"(ok) : "r"(m), "r"(parity) : "memory"); } while (!ok && ++it < SPIN_LIMIT); }
__device__ __forceinline__ void bar_sync(int id, int n) { asm volatile("bar.sync %0, %1;" ::"r"(id), "r"(n) : "memory"); }
__device__ __forceinline__ void bar_arrive(int id, int n) { asm volatile("bar.arrive %0, %1;" ::"r"(id), "r"(n) : "memory"); }
__device__ __forceinline__ int ld_acq(const int* p) { int v; asm volatile("ld.acquire.gpu.global.s32 %0, [%1];" : "=r"(v) : "l"(p) : "memory"); return v; }
__device__ __forceinline__ void wait_flag(const int* p, int target) { int it = 0; while (ld_acq(p) < target && ++it < SPIN_LIMIT) { __nanosleep(40); } }
__device__ __forceinline__ void fence_async() { asm volatile("fence.proxy.async.global;" ::: "memory"); }
__device__ __forceinline__ uint4 lds128(uint32_t a) { uint4 v; asm volatile("ld.shared.v4.u32 {%0,%1,%2,%3}, [%4];" : "=r"(v.x), "=r"(v.y), "=r"(v.z), "=r"(v.w) : "r"(a) : "memory"); return v; }
__device__ __forceinline__ void sts128(uint32_t a, uint4 v) { asm volatile("st.shared.v4.u32 [%0], {%1,%2,%3,%4};" ::"r"(a), "r"(v.x), "r"(v.y), "r"(v.z), "r"(v.w) : "memory"); }
__device__ __forceinline__ void sts32(uint32_t a, uint32_t v) { asm volatile("st.shared.u32 [%0], %1;" ::"r"(a), "r"(v) : "memory"); }
__device__ __forceinline__ void sts16(uint32_t a, float f) { unsigned short h = __bfloat16_as_ushort(__float2bfloat16(f)); asm volatile("st.shared.u16 [%0], %1;" ::"r"(a), "h"(h) : "memory"); }
__device__ __forceinline__ void ldsm4(uint32_t* r, uint32_t a) { asm volatile("ldmatrix.sync.aligned.m8n8.x4.shared.b16 {%0,%1,%2,%3}, [%4];" : "=r"(r[0]), "=r"(r[1]), "=r"(r[2]), "=r"(r[3]) : "r"(a) : "memory"); }
__device__ __forceinline__ void ldsm4t(uint32_t* r, uint32_t a) { asm volatile("ldmatrix.sync.aligned.m8n8.x4.trans.shared.b16 {%0,%1,%2,%3}, [%4];" : "=r"(r[0]), "=r"(r[1]), "=r"(r[2]), "=r"(r[3]) : "r"(a) : "memory"); }
__device__ __forceinline__ void mma16(float* c, uint32_t a0, uint32_t a1, uint32_t a2, uint32_t a3, uint32_t b0, uint32_t b1) {
  asm volatile("mma.sync.aligned.m16n8k16.row.col.f32.bf16.bf16.f32 {%0,%1,%2,%3}, {%4,%5,%6,%7}, {%8,%9}, {%0,%1,%2,%3};" : "+f"(c[0]), "+f"(c[1]), "+f"(c[2]), "+f"(c[3]) : "r"(a0), "r"(a1), "r"(a2), "r"(a3), "r"(b0), "r"(b1)); }
__device__ __forceinline__ void mma8(float* c, uint32_t a0, uint32_t a1, uint32_t b0) {
  asm volatile("mma.sync.aligned.m16n8k8.row.col.f32.bf16.bf16.f32 {%0,%1,%2,%3}, {%4,%5}, {%6}, {%0,%1,%2,%3};" : "+f"(c[0]), "+f"(c[1]), "+f"(c[2]), "+f"(c[3]) : "r"(a0), "r"(a1), "r"(b0)); }
__device__ __forceinline__ uint32_t pack2(float a, float b) { __nv_bfloat162 h = __floats2bfloat162_rn(a, b); return *(uint32_t*)&h; }
__device__ __forceinline__ float rbf(float x) { uint32_t r; asm("cvt.rn.bf16x2.f32 %0, %1, %2;" : "=r"(r) : "f"(x), "f"(0.f)); return __uint_as_float(r); }
__device__ __forceinline__ void cp16(uint32_t d, const void* s) { asm volatile("cp.async.cg.shared.global [%0], [%1], 16;" ::"r"(d), "l"(s) : "memory"); }
__device__ __forceinline__ void tma2d(uint32_t dst, const CUtensorMap* m, int c0, int c1, uint32_t mbar) {
  asm volatile("cp.async.bulk.tensor.2d.shared::cluster.global.mbarrier::complete_tx::bytes [%0], [%1, {%2,%3}], [%4];" ::"r"(dst), "l"(m), "r"(c0), "r"(c1), "r"(mbar) : "memory"); }
__device__ __forceinline__ uint64_t mkdesc(uint32_t addr, uint32_t lbo, uint32_t sbo) {
  return (uint64_t)((addr & 0x3FFFF) >> 4) | ((uint64_t)(lbo >> 4) << 16) | ((uint64_t)(sbo >> 4) << 32) | (1ull << 62); }

#define R8(i) "+f"(d[i]), "+f"(d[i+1]), "+f"(d[i+2]), "+f"(d[i+3]), "+f"(d[i+4]), "+f"(d[i+5]), "+f"(d[i+6]), "+f"(d[i+7])
__device__ __forceinline__ void wgmma256(float* d, uint64_t da, uint64_t db, int acc) {
  asm volatile("{.reg .pred p; setp.ne.b32 p, %130, 0;\n"
    "wgmma.mma_async.sync.aligned.m64n256k16.f32.bf16.bf16 {"
    "%0,%1,%2,%3,%4,%5,%6,%7,%8,%9,%10,%11,%12,%13,%14,%15,%16,%17,%18,%19,%20,%21,%22,%23,%24,%25,%26,%27,%28,%29,%30,%31,"
    "%32,%33,%34,%35,%36,%37,%38,%39,%40,%41,%42,%43,%44,%45,%46,%47,%48,%49,%50,%51,%52,%53,%54,%55,%56,%57,%58,%59,%60,%61,%62,%63,"
    "%64,%65,%66,%67,%68,%69,%70,%71,%72,%73,%74,%75,%76,%77,%78,%79,%80,%81,%82,%83,%84,%85,%86,%87,%88,%89,%90,%91,%92,%93,%94,%95,"
    "%96,%97,%98,%99,%100,%101,%102,%103,%104,%105,%106,%107,%108,%109,%110,%111,%112,%113,%114,%115,%116,%117,%118,%119,%120,%121,%122,%123,%124,%125,%126,%127"
    "}, %128, %129, p, 1, 1, 0, 1;}"
    : R8(0), R8(8), R8(16), R8(24), R8(32), R8(40), R8(48), R8(56), R8(64), R8(72), R8(80), R8(88), R8(96), R8(104), R8(112), R8(120)
    : "l"(da), "l"(db), "r"(acc)); }

__global__ void __launch_bounds__(256) prologue_kernel(const bf16* __restrict__ x, const bf16* __restrict__ mem0) {
  int tid = threadIdx.x, lane = tid & 31, warp = tid >> 5;
  int row = blockIdx.x * 8 + warp;
  {
    const uint4* src = (const uint4*)(x + (size_t)row * DM);
    uint4 u[2] = { src[lane], src[lane + 32] };
    float v[16];
    #pragma unroll
    for (int i = 0; i < 2; i++) { const __nv_bfloat162* h = (const __nv_bfloat162*)&u[i];
      #pragma unroll
      for (int k = 0; k < 4; k++) { float2 f = __bfloat1622float2(h[k]); v[i * 8 + 2 * k] = f.x; v[i * 8 + 2 * k + 1] = f.y; } }
    #pragma unroll
    for (int pass = 0; pass < 2; pass++) {
      float s = 0;
      #pragma unroll
      for (int i = 0; i < 16; i++) s += v[i];
      #pragma unroll
      for (int o = 16; o; o >>= 1) s += __shfl_xor_sync(~0u, s, o);
      float mf = s * (1.f / DM);
      float q = 0;
      #pragma unroll
      for (int i = 0; i < 16; i++) { float dd = v[i] - mf; q += dd * dd; }
      #pragma unroll
      for (int o = 16; o; o >>= 1) q += __shfl_xor_sync(~0u, q, o);
      float m = rbf(mf), var = rbf(q * (1.f / DM));
      float den = rbf(sqrtf(rbf(var + 1e-5f)));
      #pragma unroll
      for (int i = 0; i < 16; i++) v[i] = rbf(rbf(v[i] - m) / den);
      uint4 o4[2];
      #pragma unroll
      for (int i = 0; i < 2; i++) { o4[i].x = pack2(v[i*8], v[i*8+1]); o4[i].y = pack2(v[i*8+2], v[i*8+3]); o4[i].z = pack2(v[i*8+4], v[i*8+5]); o4[i].w = pack2(v[i*8+6], v[i*8+7]); }
      uint4* dst = (uint4*)((pass ? g_y : g_xn) + (size_t)row * DM);
      dst[lane] = o4[0]; dst[lane + 32] = o4[1];
    }
  }
  int gt = blockIdx.x * 256 + tid;
  float4 z4 = make_float4(0, 0, 0, 0);
  #pragma unroll
  for (int i = 0; i < 4; i++) { ((float4*)g_z)[gt + i * 65536] = z4; ((float4*)g_s)[gt + i * 65536] = z4; }
  for (int i = gt; i < NSTEP * 1536; i += 65536) {
    float4 val = z4;
    if (i < 1536) {
      int j = i / 768, c = i % 768, ci = c >> 8, w = (c & 255) >> 5, l = c & 31, g = l >> 2, t = l & 3;
      float e3[3];
      #pragma unroll
      for (int k = 0; k < 3; k++) { int e = ci * 3 + k; int mt = e >> 2, cc = e & 3;
        e3[k] = e < 8 ? __bfloat162float(mem0[(2 * t + (cc & 1)) * DM + 256 * j + 32 * w + 16 * mt + g + 8 * (cc >> 1)]) : 0.f; }
      val = make_float4(e3[0], e3[1], e3[2], 32.f);
    }
    (&g_acc[0][0][0])[i] = val;
  }
  if (gt < (int)(sizeof(Flags) / 4)) ((int*)&g_fl)[gt] = 0;
}

constexpr int R_WO = 0, R_WR = 65536, R_KT = 131072, KT_SZ = 40 * 256, R_VT = R_KT + 2 * KT_SZ, VT_SZ = 48 * 272,
              R_MEM = R_VT + 2 * VT_SZ, R_Q = R_MEM + 8 * 512, R_O = R_Q + 8 * 256, R_S = R_O + 8 * 256,
              R_RQK = R_S + 8 * 56 * 4, R_RV = R_RQK + 8192, R_BAR = R_RV + 4096, R_END = R_BAR + 64;
__device__ __forceinline__ uint32_t swz(uint32_t r) { return ((r & 1) << 2) | ((r >> 1) & 3); }
__device__ __forceinline__ void stsm4t(uint32_t a, uint32_t r0, uint32_t r1, uint32_t r2, uint32_t r3) { asm volatile("stmatrix.sync.aligned.m8n8.x4.trans.shared.b16 [%0], {%1,%2,%3,%4};" ::"r"(a), "r"(r0), "r"(r1), "r"(r2), "r"(r3) : "memory"); }
__device__ __forceinline__ void stsm2(uint32_t a, uint32_t r0, uint32_t r1) { asm volatile("stmatrix.sync.aligned.m8n8.x2.shared.b16 [%0], {%1,%2};" ::"r"(a), "r"(r0), "r"(r1) : "memory"); }
__device__ __forceinline__ float ex2(float x) { float r; asm("ex2.approx.ftz.f32 %0, %1;" : "=f"(r) : "f"(x)); return r; }
#define REDV4(p, a, b, c) asm volatile("red.relaxed.gpu.global.add.v4.f32 [%0], {%1,%2,%3,%4};" ::"l"(p), "f"(a), "f"(b), "f"(c), "f"(1.0f) : "memory")
constexpr int SMEM_BYTES = 4 * 49152 + 8 * 2304 + 1024 + 256;
static_assert(R_END + 1024 <= SMEM_BYTES, "smem");

__device__ __forceinline__ void recurrence(uint32_t sb, const bf16* __restrict__ Wq, const bf16* __restrict__ Wk, const bf16* __restrict__ Wv, const bf16* __restrict__ Wo) {
  const int tid = threadIdx.x, warp = tid >> 5, lane = tid & 31, g = lane >> 2, t = lane & 3;
  const int h = blockIdx.x >> 1, j = blockIdx.x & 1;
  const uint32_t peer = j ^ 1;
  const uint32_t mQK = sb + R_BAR, mV = sb + R_BAR + 8;
  uint32_t A[2][16][4];
  const uint32_t stg = sb + R_WR;
  const int lm = lane >> 3, lr = lane & 7;
  for (int i = tid; i < 128 * 32; i += 384) { int r = i >> 5, c = i & 31; cp16(stg + r * 528 + c * 16, Wo + ((size_t)(h * 128 + r)) * DM + 256 * j + c * 8); }
  asm volatile("cp.async.wait_all;" ::: "memory"); __syncthreads();
  if (warp < 8) {
    #pragma unroll
    for (int mt = 0; mt < 2; mt++)
      #pragma unroll
      for (int ks = 0; ks < 8; ks++) {
        int k = 32 * (ks >> 1) + 8 * (lr >> 1) + (lr & 1) + 4 * (ks & 1) + 2 * (lm >> 1);
        uint32_t r[4]; ldsm4t(r, stg + k * 528 + (32 * warp + 16 * mt + 8 * (lm & 1)) * 2);
        sts128(sb + R_WO + ((warp * 16 + mt * 8 + ks) * 32 + lane) * 16, make_uint4(r[0], r[1], r[2], r[3]));
      }
  }
  __syncthreads();
  #pragma unroll 1
  for (int m = 0; m < 3; m++) {
    const bf16* W = m == 0 ? Wq : (m == 1 ? Wk : Wv);
    for (int i = tid; i < 256 * 16; i += 384) { int r = i >> 4, c = i & 15; cp16(stg + r * 272 + c * 16, W + ((size_t)(256 * j + r)) * 4096 + h * 128 + c * 8); }
    asm volatile("cp.async.wait_all;" ::: "memory"); __syncthreads();
    if ((warp >> 2) == m) {
      #pragma unroll
      for (int mt = 0; mt < 2; mt++)
        #pragma unroll
        for (int ks = 0; ks < 16; ks++) {
          int k = 32 * (ks >> 1) + 8 * (lr >> 1) + (lr & 1) + 4 * (ks & 1) + 2 * (lm >> 1);
          ldsm4t(A[mt][ks], stg + k * 272 + (32 * (warp & 3) + 16 * mt + 8 * (lm & 1)) * 2);
        }
    }
    __syncthreads();
  }
  if (warp >= 8) {
    #pragma unroll
    for (int i = 0; i < 32; i++) sts128(sb + R_WR + (((warp - 8) * 32 + i) * 32 + lane) * 16, make_uint4(A[i >> 4][i & 15][0], A[i >> 4][i & 15][1], A[i >> 4][i & 15][2], A[i >> 4][i & 15][3]));
  }
  for (int i = tid; i < 2 * 8 * 17; i += 384) { int b = i / 136, r = i % 136; sts128(sb + R_VT + b * VT_SZ + 40 * 272 + r * 16, make_uint4(0, 0, 0, 0)); }
  __syncthreads();
  if (warp >= 8) {
    auto prefetch = [&](int s) {
      const int vt = otid() - 256;
      if ((s & 3) == 0) { wait_flag(&g_fl.tile[s >> 2][h >> 1], 1); wait_flag(&g_fl.tile[s >> 2][16 + (h >> 1)], 1); }
      const int r = vt >> 4, c = vt & 15;
      const bf16* src = g_qkv + (size_t)(32 * s + r) * QW + h * 128 + c * 8;
      uint32_t kb = sb + R_KT + (s & 1) * KT_SZ + r * 256 + ((c ^ swz(r)) << 4), vb = sb + R_VT + (s & 1) * VT_SZ + r * 272 + c * 16;
      #pragma unroll
      for (int i = 0; i < 4; i++) { cp16(kb + i * 2048, src + (size_t)i * 8 * QW); cp16(vb + i * 2176, src + (size_t)i * 8 * QW + 4096); }
    };
    auto publish = [&](int s) {
      const int vt = otid() - 256;
      if (j == 0) { const int r = vt >> 4, c = vt & 15; uint4 v = lds128(sb + R_KT + (s & 1) * KT_SZ + (32 + r) * 256 + ((c ^ swz(r)) << 4));
        __stcg((uint4*)(g_km + ((size_t)(s * 32 + h)) * 1024) + vt, v); }
      else { uint32_t vb = sb + R_VT + (s & 1) * VT_SZ + 32 * 272 + vt * 2; uint32_t e[8];
        #pragma unroll
        for (int k = 0; k < 8; k++) { unsigned short x; asm volatile("ld.shared.u16 %0, [%1];" : "=h"(x) : "r"(vb + k * 272) : "memory"); e[k] = x; }
        __stcg((uint4*)(g_vmT + ((size_t)(s * 32 + h)) * 1024) + vt, make_uint4(e[0] | (e[1] << 16), e[2] | (e[3] << 16), e[4] | (e[5] << 16), e[6] | (e[7] << 16))); }
    };
    auto flag = [&](int s) { __syncwarp(); if ((otid() & 31) == 0) { __threadfence(); atomicAdd(&g_fl.prog[s >> 2][h], 1); } };
    prefetch(0); asm volatile("cp.async.wait_all;" ::: "memory"); bar_arrive(5, 384);
    #pragma unroll 1
    for (int s = 0; s < NSTEP; s++) {
      const int tid = otid(), lane = tid & 31, wv = (tid >> 5) - 8, g = lane >> 2, t = lane & 3;
      if (tid == 256) mbar_expect(mV, 4096);
      const uint32_t fo = (t ^ swz(g)) << 4;
      bar_sync(4, 384);
      float c[4][4];
      #pragma unroll
      for (int i = 0; i < 4; i++) { c[i][0] = c[i][1] = c[i][2] = c[i][3] = 0.f; }
      #pragma unroll
      for (int p = 0; p < 8; p++) {
        uint4 b = lds128(sb + R_MEM + g * 512 + (p >> 1) * 128 + (fo ^ ((p & 1) << 6)));
        mma16(c[0], A[0][2*p][0], A[0][2*p][1], A[0][2*p][2], A[0][2*p][3], b.x, b.y);
        mma16(c[1], A[1][2*p][0], A[1][2*p][1], A[1][2*p][2], A[1][2*p][3], b.x, b.y);
        mma16(c[2], A[0][2*p+1][0], A[0][2*p+1][1], A[0][2*p+1][2], A[0][2*p+1][3], b.z, b.w);
        mma16(c[3], A[1][2*p+1][0], A[1][2*p+1][1], A[1][2*p+1][2], A[1][2*p+1][3], b.z, b.w);
      }
      #pragma unroll
      for (int i = 0; i < 4; i++) { c[0][i] += c[2][i]; c[1][i] += c[3][i]; }
      const uint32_t rx = sb + R_RV + (wv * 64 + lane) * 16;
      { uint32_t ra = mapa(rx, peer), rm = mapa(mV, peer);
        st_async_v4(ra, c[0][0], c[0][1], c[0][2], c[0][3], rm);
        st_async_v4(ra + 512, c[1][0], c[1][1], c[1][2], c[1][3], rm); }
      const bool more = s < NSTEP - 1;
      const uint32_t wb = sb + (wv * 1024 + lane) * 16;
      if (more) {
        #pragma unroll
        for (int i = 0; i < 16; i++) { uint4 v = lds128(wb + R_WO + i * 512); A[0][i][0] = v.x; A[0][i][1] = v.y; A[0][i][2] = v.z; A[0][i][3] = v.w; }
      }
      mbar_wait(mV, s & 1);
      { uint4 r0 = lds128(rx), r1 = lds128(rx + 512);
        stsm4t(sb + R_VT + (s & 1) * VT_SZ + (32 + (lane & 7)) * 272 + (4 * wv + (lane >> 3)) * 16,
          pack2(c[0][0] + __uint_as_float(r0.x), c[0][1] + __uint_as_float(r0.y)), pack2(c[0][2] + __uint_as_float(r0.z), c[0][3] + __uint_as_float(r0.w)),
          pack2(c[1][0] + __uint_as_float(r1.x), c[1][1] + __uint_as_float(r1.y)), pack2(c[1][2] + __uint_as_float(r1.z), c[1][3] + __uint_as_float(r1.w))); }
      if (more) {
        bar_arrive(3, 384);
        #pragma unroll
        for (int i = 0; i < 16; i++) { uint4 v = lds128(wb + R_WO + 8192 + i * 512); A[1][i][0] = v.x; A[1][i][1] = v.y; A[1][i][2] = v.z; A[1][i][3] = v.w; }
      }
      bar_sync(7, 384);
      if (more) {
        #pragma unroll
        for (int i = 0; i < 4; i++) { c[i][0] = c[i][1] = c[i][2] = c[i][3] = 0.f; }
        #pragma unroll
        for (int p = 0; p < 4; p++) {
          uint4 b = lds128(sb + R_O + g * 256 + (p >> 1) * 128 + (fo ^ ((p & 1) << 6)));
          #pragma unroll
          for (int mt = 0; mt < 4; mt++) { const uint32_t* a = A[mt >> 1][(mt & 1) * 8 + 2 * p]; mma16(c[mt], a[0], a[1], a[2], a[3], b.x, b.y); }
          #pragma unroll
          for (int mt = 0; mt < 4; mt++) { const uint32_t* a = A[mt >> 1][(mt & 1) * 8 + 2 * p + 1]; mma16(c[mt], a[0], a[1], a[2], a[3], b.z, b.w); }
        }
        float4* dst = &g_acc[s + 1][j][wv * 64 + lane];
        REDV4(dst, c[0][0], c[0][1], c[0][2]); REDV4(dst + 256, c[0][3], c[1][0], c[1][1]); REDV4(dst + 512, c[1][2], c[1][3], 0.f);
        REDV4(dst + 32, c[2][0], c[2][1], c[2][2]); REDV4(dst + 288, c[2][3], c[3][0], c[3][1]); REDV4(dst + 544, c[3][2], c[3][3], 0.f);
        #pragma unroll
        for (int i = 0; i < 32; i++) { uint4 v = lds128(wb + R_WR + i * 512); A[i >> 4][i & 15][0] = v.x; A[i >> 4][i & 15][1] = v.y; A[i >> 4][i & 15][2] = v.z; A[i >> 4][i & 15][3] = v.w; }
        if (s < NSTEP - 2) prefetch(s + 1);
      }
      publish(s);
      if (s < NSTEP - 2) { asm volatile("cp.async.wait_all;" ::: "memory"); bar_arrive(5 + ((s + 1) & 1), 384); }
      flag(s);
    }
    return;
  }
  const float scale = 0.08838834764831845f, l2e = 1.4426950408889634f;
  #pragma unroll 1
  for (int s = 0; s < NSTEP; s++) {
    TR(0); TR(1);
    const int tid = otid(), lane = tid & 31, warp = tid >> 5, g = lane >> 2, t = lane & 3;
    const uint32_t fo = (t ^ swz(g)) << 4;
    {
      if (tid == 0) mbar_expect(mQK, 8192);
      const float4* src = &g_acc[s][j][tid];
      uint4 v0, v1, v2; int it = 0; bool ok;
      do {
        asm volatile("ld.relaxed.gpu.global.v4.u32 {%0,%1,%2,%3}, [%4];" : "=r"(v0.x), "=r"(v0.y), "=r"(v0.z), "=r"(v0.w) : "l"(src) : "memory");
        asm volatile("ld.relaxed.gpu.global.v4.u32 {%0,%1,%2,%3}, [%4];" : "=r"(v1.x), "=r"(v1.y), "=r"(v1.z), "=r"(v1.w) : "l"(src + 256) : "memory");
        asm volatile("ld.relaxed.gpu.global.v4.u32 {%0,%1,%2,%3}, [%4];" : "=r"(v2.x), "=r"(v2.y), "=r"(v2.z), "=r"(v2.w) : "l"(src + 512) : "memory");
        ok = (v0.w == 0x42000000u) && (v1.w == 0x42000000u) && (v2.w == 0x42000000u);
      } while (!ok && ++it < SPIN_LIMIT);
      __syncwarp();
      stsm4t(sb + R_MEM + (lane & 7) * 512 + (((4 * warp + (lane >> 3)) ^ swz(lane & 7)) << 4),
        pack2(__uint_as_float(v0.x), __uint_as_float(v0.y)), pack2(__uint_as_float(v0.z), __uint_as_float(v1.x)),
        pack2(__uint_as_float(v1.y), __uint_as_float(v1.z)), pack2(__uint_as_float(v2.x), __uint_as_float(v2.y)));
    }
    TR(2);
    bar_sync(1, 256);
    TR(3);
    float c[4][4];
    #pragma unroll
    for (int i = 0; i < 4; i++) { c[i][0] = c[i][1] = c[i][2] = c[i][3] = 0.f; }
    #pragma unroll
    for (int p = 0; p < 8; p++) {
      uint4 b = lds128(sb + R_MEM + g * 512 + (p >> 1) * 128 + (fo ^ ((p & 1) << 6)));
      mma16(c[0], A[0][2*p][0], A[0][2*p][1], A[0][2*p][2], A[0][2*p][3], b.x, b.y);
      mma16(c[1], A[1][2*p][0], A[1][2*p][1], A[1][2*p][2], A[1][2*p][3], b.x, b.y);
      mma16(c[2], A[0][2*p+1][0], A[0][2*p+1][1], A[0][2*p+1][2], A[0][2*p+1][3], b.z, b.w);
      mma16(c[3], A[1][2*p+1][0], A[1][2*p+1][1], A[1][2*p+1][2], A[1][2*p+1][3], b.z, b.w);
    }
    bar_arrive(4, 384);
    #pragma unroll
    for (int i = 0; i < 4; i++) { c[0][i] += c[2][i]; c[1][i] += c[3][i]; }
    const uint32_t kb = sb + R_KT + (s & 1) * KT_SZ;
    {
      const uint32_t rx = sb + R_RQK + (warp * 64 + lane) * 16;
      { uint32_t ra = mapa(rx, peer), rm = mapa(mQK, peer);
        st_async_v4(ra, c[0][0], c[0][1], c[0][2], c[0][3], rm);
        st_async_v4(ra + 512, c[1][0], c[1][1], c[1][2], c[1][3], rm); }
      TR(4);
      const uint32_t dst = (warp < 4 ? sb + R_Q : kb + 32 * 256) + (lane & 7) * 256 + (((4 * (warp & 3) + (lane >> 3)) ^ swz(lane & 7)) << 4);
      mbar_wait(mQK, s & 1);
      TR(5);
      uint4 r0 = lds128(rx), r1 = lds128(rx + 512);
      stsm4t(dst, pack2(c[0][0] + __uint_as_float(r0.x), c[0][1] + __uint_as_float(r0.y)), pack2(c[0][2] + __uint_as_float(r0.z), c[0][3] + __uint_as_float(r0.w)),
        pack2(c[1][0] + __uint_as_float(r1.x), c[1][1] + __uint_as_float(r1.y)), pack2(c[1][2] + __uint_as_float(r1.z), c[1][3] + __uint_as_float(r1.w)));
    }
    if (s == NSTEP - 1) { bar_arrive(7, 384); break; }
    TR(8);
    bar_sync(5 + (s & 1), 384);
    TR(9);
    if (warp < 5) {
      #pragma unroll
      for (int i = 0; i < 4; i++) { c[i][0] = c[i][1] = c[i][2] = c[i][3] = 0.f; }
      #pragma unroll
      for (int p = 0; p < 4; p++) {
        const uint32_t o = g * 256 + (p >> 1) * 128 + (fo ^ ((p & 1) << 6));
        uint4 qa = lds128(sb + R_Q + o), kq = lds128(kb + warp * 2048 + o);
        mma16(c[(p & 1) * 2], qa.x, 0, qa.y, 0, kq.x, kq.y); mma16(c[(p & 1) * 2 + 1], qa.z, 0, qa.w, 0, kq.z, kq.w);
      }
      float a = rbf(rbf((c[0][0] + c[1][0]) + (c[2][0] + c[3][0])) * scale) * l2e, b = rbf(rbf((c[0][1] + c[1][1]) + (c[2][1] + c[3][1])) * scale) * l2e;
      asm volatile("st.shared.v2.f32 [%0], {%1,%2};" ::"r"(sb + R_S + g * 224 + (8 * warp + 2 * t) * 4), "f"(a), "f"(b) : "memory");
    }
    TR(10);
    bar_sync(2, 256);
    TR(11);
    float sv[10];
    #pragma unroll
    for (int i = 0; i < 5; i++) asm volatile("ld.shared.v2.f32 {%0,%1}, [%2];" : "=f"(sv[2*i]), "=f"(sv[2*i+1]) : "r"(sb + R_S + g * 224 + (8 * i + 2 * t) * 4) : "memory");
    const uint32_t vb = sb + R_VT + (s & 1) * VT_SZ + (lane & 15) * 272 + (16 * warp + 8 * (lane >> 4)) * 2;
    uint32_t r0[4], r1[4], r2[4]; ldsm4t(r0, vb); ldsm4t(r1, vb + 16 * 272);
    float mx = fmaxf(fmaxf(fmaxf(sv[0], sv[1]), fmaxf(sv[2], sv[3])), fmaxf(fmaxf(sv[4], sv[5]), fmaxf(sv[6], sv[7])));
    mx = fmaxf(mx, fmaxf(sv[8], sv[9]));
    mx = fmaxf(mx, __shfl_xor_sync(~0u, mx, 1)); mx = fmaxf(mx, __shfl_xor_sync(~0u, mx, 2));
    #pragma unroll
    for (int i = 0; i < 10; i++) sv[i] = ex2(sv[i] - mx);
    float sum = (((sv[0] + sv[1]) + (sv[2] + sv[3])) + ((sv[4] + sv[5]) + (sv[6] + sv[7]))) + (sv[8] + sv[9]);
    sum += __shfl_xor_sync(~0u, sum, 1); sum += __shfl_xor_sync(~0u, sum, 2);
    float inv; asm("rcp.approx.ftz.f32 %0, %1;" : "=f"(inv) : "f"(sum));
    uint32_t P[5];
    #pragma unroll
    for (int i = 0; i < 5; i++) P[i] = pack2(sv[2*i] * inv, sv[2*i+1] * inv);
    TR(6);
    #pragma unroll
    for (int i = 0; i < 4; i++) { c[i][0] = c[i][1] = c[i][2] = c[i][3] = 0.f; }
    bar_sync(3, 384);
    ldsm4t(r2, vb + 32 * 272);
    mma16(c[0], P[0], 0, P[1], 0, r0[0], r0[1]); mma16(c[1], P[0], 0, P[1], 0, r0[2], r0[3]);
    mma16(c[2], P[2], 0, P[3], 0, r1[0], r1[1]); mma16(c[3], P[2], 0, P[3], 0, r1[2], r1[3]);
    mma16(c[0], P[4], 0, 0, 0, r2[0], r2[1]); mma16(c[1], P[4], 0, 0, 0, r2[2], r2[3]);
    stsm2(sb + R_O + (lane & 7) * 256 + (((2 * warp + ((lane >> 3) & 1)) ^ swz(lane & 7)) << 4), pack2(c[0][0] + c[2][0], c[0][1] + c[2][1]), pack2(c[1][0] + c[3][0], c[1][1] + c[3][1]));
    bar_arrive(7, 384);
    TR(7);
  }
}

constexpr int I_M1 = 512, I_Q = 624, I_M2 = 880, I_AT = 1008, I_G = I_AT + 32, GSZ = 56, I_END = I_G + 15 * GSZ + 24;
constexpr int B_STG = 4 * 49152, B_BAR = B_STG + 8 * 2304;
struct Item { int type, rb, nt, ks; };
__device__ __forceinline__ Item decode(int it) {
  Item r; r.ks = 0;
  if (it < I_M1) { r.type = 0; r.rb = it >> 5; r.nt = it & 31; }
  else if (it < I_Q) { int i = it - I_M1; r.type = 1; r.rb = i / 7; r.nt = i % 7; }
  else if (it < I_M2) { int i = it - I_Q; r.type = 0; r.rb = i >> 4; r.nt = 32 + (i & 15); }
  else if (it < I_AT) { int i = it - I_M2; r.type = 2; r.rb = i >> 3; r.nt = (i >> 2) & 1; r.ks = i & 3; }
  else if (it < I_G) { r.type = 3; r.rb = 0; r.nt = it - I_AT; }
  else {
    int i = it - I_G, gi = i / GSZ, q = i % GSZ; if (gi == 15) q += 32;
    if (q < 32) { r.type = 3; r.rb = gi + 1; r.nt = q; }
    else if (q < 48) { r.type = 4; r.rb = gi; r.nt = (q - 32) >> 3; r.ks = (q - 32) & 7; }
    else { r.type = 5; r.rb = gi; r.nt = q - 48; } }
  return r;
}
__device__ __forceinline__ float gelu_t(float x) { float u = 0.7978845608028654f * (x + 0.044715f * x * x * x); float th; asm("tanh.approx.f32 %0, %1;" : "=f"(th) : "f"(u)); float hx = 0.5f * x; return fmaf(hx, th, hx); }

__device__ __forceinline__ void bulk(uint32_t sb, const Maps& mp, const bf16* __restrict__ x, const bf16* __restrict__ b1, const bf16* __restrict__ b2, bf16* __restrict__ out) {
  const int tid = threadIdx.x, warp = tid >> 5, lane = tid & 31, g = lane >> 2, t = lane & 3;
  const int bid = blockIdx.x - NREC;
  const uint32_t full = sb + B_BAR, empty = sb + B_BAR + 32, ifull = sb + B_BAR + 64, iempty = sb + B_BAR + 80;
  volatile int* ring = (volatile int*)(__cvta_shared_to_generic(sb + B_BAR + 96));
  if (warp >= 8) {
    asm volatile("setmaxnreg.dec.sync.aligned.u32 40;");
    if (tid == 256) {
      uint32_t st = 0, ph = 0;
      for (int n = 0;; n++) {
        int it = n == 0 ? bid : NBULK + atomicAdd(&g_fl.next, 1);
        Item I = decode(it);
        if (it < I_END) {
          if (I.type == 5) { wait_flag(&g_fl.s[I.rb][0], 16); wait_flag(&g_fl.z[I.rb][0], 8); }
          else if (I.type == 3) { wait_flag(&g_fl.prog[I.rb][I.nt], 32); wait_flag(&g_fl.tile[I.rb][I.nt >> 1], 1); wait_flag(&g_fl.tile[I.rb][16 + (I.nt >> 1)], 1); wait_flag(&g_fl.tile[I.rb][32 + (I.nt >> 1)], 1); fence_async(); }
          else if (I.type == 2) { wait_flag(&g_fl.hid[I.rb], 7); fence_async(); }
          else if (I.type == 4) { wait_flag(&g_fl.o[I.rb][I.ks], 4); fence_async(); }
        }
        mbar_wait(iempty + (n & 1) * 8, ((n >> 1) & 1) ^ 1);
        ring[n & 1] = it; mbar_arrive(ifull + (n & 1) * 8);
        if (it >= I_END) break;
        if (I.type == 5) continue;
        if (I.type == 3) {
          for (int m = 0; m < 3; m++) {
            mbar_wait(empty + st * 8, ph ^ 1);
            mbar_expect(full + st * 8, 32768);
            int col = (m == 0 ? 8192 : (m == 1 ? 0 : 4096)) + I.nt * 128;
            tma2d(sb + st * 49152, &mp.qkv, col, I.rb * 128, full + st * 8);
            tma2d(sb + st * 49152 + 16384, &mp.qkv, col + 64, I.rb * 128, full + st * 8);
            if (++st == 4) { st = 0; ph ^= 1; }
          }
          continue;
        }
        const CUtensorMap *ma, *mb; int nkb = 8, kb0 = 0, n0;
        if (I.type == 0) { ma = &mp.xn; mb = I.nt < 16 ? &mp.wk : (I.nt < 32 ? &mp.wv : &mp.wq); n0 = (I.nt & 15) * 256; }
        else if (I.type == 1) { ma = &mp.y; mb = &mp.w1; n0 = I.nt * 256; }
        else if (I.type == 2) { ma = &mp.hid; mb = &mp.w2; n0 = I.nt * 256; nkb = 7; kb0 = I.ks * 7; }
        else { ma = &mp.o; mb = &mp.wo; n0 = I.nt * 256; kb0 = I.ks * 8; }
        for (int kb = kb0; kb < kb0 + nkb; kb++) {
          mbar_wait(empty + st * 8, ph ^ 1);
          mbar_expect(full + st * 8, 49152);
          uint32_t sa = sb + st * 49152;
          tma2d(sa, ma, kb * 64, I.rb * 128, full + st * 8);
          #pragma unroll
          for (int q = 0; q < 4; q++) tma2d(sa + 16384 + q * 8192, mb, n0 + q * 64, kb * 64, full + st * 8);
          if (++st == 4) { st = 0; ph ^= 1; }
        }
      }
    } else if (warp == 9) {
      for (int n = 0;; n++) {
        mbar_wait(ifull + (n & 1) * 8, (n >> 1) & 1);
        int it = ring[n & 1];
        if (it >= I_END) break;
        Item I = decode(it);
        bar_sync(6 + (n & 1), 288);
        if (lane == 0) {
          if (I.type != 5) {
            fence_async(); __threadfence();
            int* f = I.type == 0 ? &g_fl.tile[I.rb][I.nt] : I.type == 1 ? &g_fl.hid[I.rb] : I.type == 2 ? &g_fl.z[I.rb][0] : I.type == 3 ? &g_fl.o[I.rb][I.nt >> 2] : &g_fl.s[I.rb][0];
            atomicAdd(f, 1);
          }
          mbar_arrive(iempty + (n & 1) * 8);
        }
      }
    }
    return;
  }
  asm volatile("setmaxnreg.inc.sync.aligned.u32 232;");
  const int wg = warp >> 2;
  const uint32_t stg = sb + B_STG + warp * 2304;
  const int lm = lane >> 3, lr = lane & 7;
  uint32_t st = 0, ph = 0;
  float d[128];
  #pragma unroll 1
  for (int n = 0;; n++) {
    mbar_wait(ifull + (n & 1) * 8, (n >> 1) & 1);
    const int it = ring[n & 1];
    __syncwarp(); if (lane == 0) mbar_arrive(iempty + (n & 1) * 8);
    if (it >= I_END) break;
    Item I = decode(it);
    const int row0 = I.rb * 128 + warp * 16;
    TB(0);
    if (I.type == 5) {
      #pragma unroll
      for (int i = 0; i < 4; i++) {
        size_t off = (size_t)(I.rb * 128 + I.nt * 16 + warp * 2 + (i >> 1)) * DM + (i & 1) * 256 + lane * 8;
        float4 s0 = __ldcg((const float4*)(g_s + off)), s1 = __ldcg((const float4*)(g_s + off + 4));
        float4 z0 = __ldcg((const float4*)(g_z + off)), z1 = __ldcg((const float4*)(g_z + off + 4));
        uint4 xv = *(const uint4*)(x + off), bv = *(const uint4*)(b2 + (i & 1) * 256 + lane * 8);
        float sa[8] = {s0.x, s0.y, s0.z, s0.w, s1.x, s1.y, s1.z, s1.w}, za[8] = {z0.x, z0.y, z0.z, z0.w, z1.x, z1.y, z1.z, z1.w}, r[8];
        #pragma unroll
        for (int e = 0; e < 8; e++) { float xx = __bfloat162float(((const bf16*)&xv)[e]), bb = __bfloat162float(((const bf16*)&bv)[e]);
          float u = rbf(rbf(za[e]) + bb); float gg = rbf(__fdividef(u, 1.f + __expf(-u))); r[e] = xx + rbf(rbf(sa[e]) * gg); }
        *(uint4*)(out + off) = make_uint4(pack2(r[0], r[1]), pack2(r[2], r[3]), pack2(r[4], r[5]), pack2(r[6], r[7]));
      }
      bar_arrive(6 + (n & 1), 288);
      continue;
    }
    if (I.type == 3) {
      const int h = I.nt, seg = warp >> 1, half = warp & 1, step = I.rb * 4 + seg;
      uint32_t kmr[16], vmr[16];
      { const uint32_t* km = (const uint32_t*)(g_km + ((size_t)(step * 32 + h)) * 1024) + g * 64 + t;
        const uint32_t* vm = (const uint32_t*)(g_vmT + ((size_t)(step * 32 + h)) * 1024) + g * 4 + t;
        #pragma unroll
        for (int i = 0; i < 16; i++) { kmr[i] = __ldcg(km + i * 4); vmr[i] = __ldcg(vm + i * 32); } }
      uint32_t sQ = sb + st * 49152; mbar_wait(full + st * 8, ph); uint32_t eQ = empty + st * 8; if (++st == 4) { st = 0; ph ^= 1; }
      uint32_t sK = sb + st * 49152; mbar_wait(full + st * 8, ph); uint32_t eK = empty + st * 8; if (++st == 4) { st = 0; ph ^= 1; }
      float sc[5][4];
      #pragma unroll
      for (int i = 0; i < 5; i++) { sc[i][0] = sc[i][1] = sc[i][2] = sc[i][3] = 0.f; }
      #pragma unroll
      for (int ks = 0; ks < 8; ks++) {
        uint32_t a[4]; { int r = warp * 16 + 8 * (lm & 1) + lr, c8 = 2 * ks + (lm >> 1); ldsm4(a, sQ + (c8 >> 3) * 16384 + r * 128 + (((c8 & 7) ^ (r & 7)) << 4)); }
        #pragma unroll
        for (int np = 0; np < 2; np++) {
          if (np == 1 && half == 0) continue;
          uint32_t b[4]; int r = seg * 32 + 16 * np + 8 * (lm >> 1) + lr, c8 = 2 * ks + (lm & 1);
          ldsm4(b, sK + (c8 >> 3) * 16384 + r * 128 + (((c8 & 7) ^ (r & 7)) << 4));
          mma16(sc[2*np], a[0], a[1], a[2], a[3], b[0], b[1]); mma16(sc[2*np+1], a[0], a[1], a[2], a[3], b[2], b[3]);
        }
        mma16(sc[4], a[0], a[1], a[2], a[3], kmr[2*ks], kmr[2*ks+1]);
      }
      __syncwarp(); if (lane == 0) { mbar_arrive(eQ); mbar_arrive(eK); }
      const float scale = 0.08838834764831845f;
      uint32_t P[5][2];
      #pragma unroll
      for (int rr = 0; rr < 2; rr++) {
        const int qi = 16 * half + g + 8 * rr;
        float mx = -3.0e38f;
        #pragma unroll
        for (int i = 0; i < 5; i++)
          #pragma unroll
          for (int e = 0; e < 2; e++) { float v = rbf(rbf(sc[i][2*rr+e]) * scale); if (i < 4 && 8 * i + 2 * t + e > qi) v = -1.0e9f; sc[i][2*rr+e] = v; mx = fmaxf(mx, v); }
        mx = fmaxf(mx, __shfl_xor_sync(~0u, mx, 1)); mx = fmaxf(mx, __shfl_xor_sync(~0u, mx, 2));
        float sum = 0;
        #pragma unroll
        for (int i = 0; i < 5; i++)
          #pragma unroll
          for (int e = 0; e < 2; e++) { float v = __expf(sc[i][2*rr+e] - mx); sc[i][2*rr+e] = v; sum += v; }
        sum += __shfl_xor_sync(~0u, sum, 1); sum += __shfl_xor_sync(~0u, sum, 2);
        float inv = __fdividef(1.f, sum);
        #pragma unroll
        for (int i = 0; i < 5; i++) P[i][rr] = pack2(sc[i][2*rr] * inv, sc[i][2*rr+1] * inv);
      }
      uint32_t sV = sb + st * 49152; mbar_wait(full + st * 8, ph); uint32_t eV = empty + st * 8; if (++st == 4) { st = 0; ph ^= 1; }
      #pragma unroll
      for (int i = 0; i < 64; i++) d[i] = 0.f;
      #pragma unroll
      for (int n2 = 0; n2 < 8; n2++) {
        #pragma unroll
        for (int kk = 0; kk < 2; kk++) {
          if (kk == 1 && half == 0) continue;
          uint32_t b[4]; int r = seg * 32 + 16 * kk + 8 * (lm & 1) + lr, c8 = 2 * n2 + (lm >> 1);
          ldsm4t(b, sV + (c8 >> 3) * 16384 + r * 128 + (((c8 & 7) ^ (r & 7)) << 4));
          mma16(d + 8 * n2, P[2*kk][0], P[2*kk][1], P[2*kk+1][0], P[2*kk+1][1], b[0], b[1]);
          mma16(d + 8 * n2 + 4, P[2*kk][0], P[2*kk][1], P[2*kk+1][0], P[2*kk+1][1], b[2], b[3]);
        }
        mma8(d + 8 * n2, P[4][0], P[4][1], vmr[2*n2]); mma8(d + 8 * n2 + 4, P[4][0], P[4][1], vmr[2*n2+1]);
      }
      __syncwarp(); if (lane == 0) mbar_arrive(eV);
      #pragma unroll
      for (int ch = 0; ch < 2; ch++) {
        #pragma unroll
        for (int i = 0; i < 8; i++) { const float* a = d + ch * 32 + i * 4;
          sts32(stg + g * 144 + i * 16 + t * 4, pack2(a[0], a[1])); sts32(stg + (g + 8) * 144 + i * 16 + t * 4, pack2(a[2], a[3])); }
        __syncwarp();
        #pragma unroll
        for (int i = 0; i < 4; i++) { int r = i * 4 + lm; uint4 v = lds128(stg + r * 144 + lr * 16);
          *(uint4*)(g_o + (size_t)(row0 + r) * 4096 + h * 128 + ch * 64 + lr * 8) = v; }
        __syncwarp();
      }
      bar_arrive(6 + (n & 1), 288);
      continue;
    }
    const int nkb = I.type == 2 ? 7 : 8;
    uint32_t prev = 0;
    for (int kb = 0; kb < nkb; kb++) {
      mbar_wait(full + st * 8, ph);
      uint32_t sa = sb + st * 49152;
      asm volatile("wgmma.fence.sync.aligned;" ::: "memory");
      #pragma unroll
      for (int k = 0; k < 4; k++)
        wgmma256(d, mkdesc(sa + wg * 8192 + k * 32, 16, 1024), mkdesc(sa + 16384 + k * 2048, 8192, 1024), (kb | k) != 0);
      asm volatile("wgmma.commit_group.sync.aligned;" ::: "memory");
      if (kb > 0) { asm volatile("wgmma.wait_group.sync.aligned 1;" ::: "memory"); if (lane == 0) mbar_arrive(prev); }
      prev = empty + st * 8;
      if (++st == 4) { st = 0; ph ^= 1; }
    }
    asm volatile("wgmma.wait_group.sync.aligned 0;" ::: "memory");
    if (lane == 0) mbar_arrive(prev);
    TB(1);
    if (I.type <= 1) {
      bf16* dst; int ld;
      if (I.type == 0) { dst = g_qkv + (size_t)row0 * QW + I.nt * 256; ld = QW; } else { dst = g_hid + (size_t)row0 * FF + I.nt * 256; ld = FF; }
      #pragma unroll
      for (int ch = 0; ch < 4; ch++) {
        #pragma unroll
        for (int i = 0; i < 8; i++) { float* a = d + ch * 32 + i * 4;
          if (I.type == 1) { float2 bb = __bfloat1622float2(*(const __nv_bfloat162*)(b1 + I.nt * 256 + ch * 64 + i * 8 + 2 * t));
            a[0] = gelu_t(rbf(rbf(a[0]) + bb.x)); a[1] = gelu_t(rbf(rbf(a[1]) + bb.y)); a[2] = gelu_t(rbf(rbf(a[2]) + bb.x)); a[3] = gelu_t(rbf(rbf(a[3]) + bb.y)); }
          sts32(stg + g * 144 + i * 16 + t * 4, pack2(a[0], a[1])); sts32(stg + (g + 8) * 144 + i * 16 + t * 4, pack2(a[2], a[3])); }
        __syncwarp();
        #pragma unroll
        for (int i = 0; i < 4; i++) { int r = i * 4 + lm; uint4 v = lds128(stg + r * 144 + lr * 16); *(uint4*)(dst + (size_t)r * ld + ch * 64 + lr * 8) = v; }
        __syncwarp();
      }
    } else {
      float* dst = (I.type == 2 ? g_z : g_s) + (size_t)(row0 + g) * DM + I.nt * 256 + 2 * t;
      #pragma unroll
      for (int i = 0; i < 32; i++) {
        asm volatile("red.relaxed.gpu.global.add.v2.f32 [%0], {%1,%2};" ::"l"(dst + i * 8), "f"(d[4*i]), "f"(d[4*i+1]) : "memory");
        asm volatile("red.relaxed.gpu.global.add.v2.f32 [%0], {%1,%2};" ::"l"(dst + 8 * DM + i * 8), "f"(d[4*i+2]), "f"(d[4*i+3]) : "memory");
      }
    }
    bar_arrive(6 + (n & 1), 288);
  }
}

__global__ void __cluster_dims__(2, 1, 1) __launch_bounds__(384, 1)
main_kernel(const __grid_constant__ Maps mp, const bf16* x, const bf16* Wq, const bf16* Wk, const bf16* Wv, const bf16* Wo, const bf16* b1, const bf16* b2, bf16* out) {
  extern __shared__ __align__(1024) uint8_t smem_raw[];
  const uint32_t sb = smem_u32(smem_raw);
  if (sb & 1023) __trap();
  if (threadIdx.x == 0) {
    if (blockIdx.x < NREC) { mbar_init(sb + R_BAR, 1); mbar_init(sb + R_BAR + 8, 1); }
    else { for (int i = 0; i < 4; i++) { mbar_init(sb + B_BAR + i * 8, 1); mbar_init(sb + B_BAR + 32 + i * 8, 8); }
      for (int i = 0; i < 2; i++) { mbar_init(sb + B_BAR + 64 + i * 8, 1); mbar_init(sb + B_BAR + 80 + i * 8, 9); } }
    asm volatile("fence.mbarrier_init.release.cluster;" ::: "memory");
  }
  asm volatile("barrier.cluster.arrive.release.aligned; barrier.cluster.wait.acquire.aligned;" ::: "memory");
  if (blockIdx.x < NREC) recurrence(sb, Wq, Wk, Wv, Wo);
  else bulk(sb, mp, x, b1, b2, out);
}

typedef CUresult (*EncFn)(CUtensorMap*, CUtensorMapDataType, cuuint32_t, void*, const cuuint64_t*, const cuuint64_t*, const cuuint32_t*, const cuuint32_t*, CUtensorMapInterleave, CUtensorMapSwizzle, CUtensorMapL2promotion, CUtensorMapFloatOOBfill);
static void mk(EncFn f, CUtensorMap* m, const void* p, uint64_t rows, uint64_t cols, uint32_t boxr) {
  cuuint64_t dims[2] = {cols, rows}, str[1] = {cols * 2}; cuuint32_t box[2] = {64, boxr}, es[2] = {1, 1};
  f(m, CU_TENSOR_MAP_DATA_TYPE_BFLOAT16, 2, (void*)p, dims, str, box, es, CU_TENSOR_MAP_INTERLEAVE_NONE, CU_TENSOR_MAP_SWIZZLE_128B, CU_TENSOR_MAP_L2_PROMOTION_L2_256B, CU_TENSOR_MAP_FLOAT_OOB_FILL_NONE);
}
extern "C" void kernel_launch(void* const* d_in, const int* in_sizes, int n_in, void* d_out, int out_size) {
  const bf16 *x = (const bf16*)d_in[0], *mem0 = (const bf16*)d_in[1], *Wq = (const bf16*)d_in[2], *Wk = (const bf16*)d_in[3], *Wv = (const bf16*)d_in[4], *Wo = (const bf16*)d_in[5];
  const bf16 *w1 = (const bf16*)d_in[8], *b1 = (const bf16*)d_in[9], *w2 = (const bf16*)d_in[10], *b2 = (const bf16*)d_in[11];
  void* fn = nullptr; cudaDriverEntryPointQueryResult qr;
  cudaGetDriverEntryPoint("cuTensorMapEncodeTiled", &fn, cudaEnableDefault, &qr);
  EncFn f = (EncFn)fn;
  void *pxn, *py, *ph, *po, *pq;
  cudaGetSymbolAddress(&pxn, g_xn); cudaGetSymbolAddress(&py, g_y); cudaGetSymbolAddress(&ph, g_hid); cudaGetSymbolAddress(&po, g_o); cudaGetSymbolAddress(&pq, g_qkv);
  Maps mp;
  mk(f, &mp.xn, pxn, SEQ, DM, 128); mk(f, &mp.y, py, SEQ, DM, 128); mk(f, &mp.hid, ph, SEQ, FF, 128); mk(f, &mp.o, po, SEQ, 4096, 128); mk(f, &mp.qkv, pq, SEQ, QW, 128);
  mk(f, &mp.wk, Wk, DM, 4096, 64); mk(f, &mp.wv, Wv, DM, 4096, 64); mk(f, &mp.wq, Wq, DM, 4096, 64);
  mk(f, &mp.w1, w1, DM, FF, 64); mk(f, &mp.w2, w2, FF, DM, 64); mk(f, &mp.wo, Wo, 4096, DM, 64);
  cudaFuncSetAttribute(main_kernel, cudaFuncAttributeMaxDynamicSharedMemorySize, SMEM_BYTES);
  prologue_kernel<<<256, 256, 0, cudaStreamPerThread>>>(x, mem0);
  main_kernel<<<NCTA, 384, SMEM_BYTES, cudaStreamPerThread>>>(mp, x, Wq, Wk, Wv, Wo, b1, b2, (bf16*)d_out);
}
```

```cpp
#include <cuda_runtime.h>
#include <cuda_bf16.h>
#include <cuda.h>
#include <stdint.h>

typedef __nv_bfloat16 bf16;
constexpr int SEQ = 2048, DM = 512, FF = 1792, QW = 12288, NSTEP = 64;
constexpr int NREC = 64, NBULK = 68, NCTA = 132;
constexpr int SPIN_LIMIT = 1 << 22;
#define THR 2
#define PDELAY 500

__device__ bf16 g_xn[SEQ * DM];
__device__ bf16 g_y[SEQ * DM];
__device__ bf16 g_qkv[(size_t)SEQ * QW];
__device__ bf16 g_hid[SEQ * FF];
__device__ bf16 g_o[(size_t)SEQ * 4096];
__device__ float g_z[SEQ * DM];
__device__ float g_s[SEQ * DM];
__device__ float4 g_acc[NSTEP][2][768];
__device__ bf16 g_km[NSTEP * 32 * 8 * 128];
__device__ bf16 g_vmT[NSTEP * 32 * 128 * 8];
struct Flags { int tile[16][48]; int hid[16]; int z[16][2]; int o[16][8]; int s[16][2]; int prog[16][32]; int next; };
__device__ Flags g_fl;

#define TR(i)
#define TB(i)
struct Maps { CUtensorMap xn, y, hid, o, qkv, wk, wv, wq, w1, w2, wo; };

extern __shared__ __align__(1024) uint8_t smem_raw[];
__device__ __forceinline__ uint4 ldc(uint32_t off) { return *(const uint4*)(smem_raw + off); }
__device__ __forceinline__ uint32_t smem_u32(const void* p) { return (uint32_t)__cvta_generic_to_shared(p); }
__device__ __forceinline__ int otid() { int t; asm volatile("mov.u32 %0, %%tid.x;" : "=r"(t)); return t; }
__device__ __forceinline__ uint32_t mapa(uint32_t a, uint32_t r) { uint32_t o; asm volatile("mapa.shared::cluster.u32 %0, %1, %2;" : "=r"(o) : "r"(a), "r"(r)); return o; }
__device__ __forceinline__ void st_async_v4(uint32_t addr, float a, float b, float c, float d, uint32_t mbar) {
  asm volatile("st.async.weak.shared::cluster.mbarrier::complete_tx::bytes.v4.b32 [%0], {%1,%2,%3,%4}, [%5];" ::"r"(addr), "r"(__float_as_uint(a)), "r"(__float_as_uint(b)), "r"(__float_as_uint(c)), "r"(__float_as_uint(d)), "r"(mbar) : "memory"); }
__device__ __forceinline__ void mbar_init(uint32_t m, int c) { asm volatile("mbarrier.init.shared::cta.b64 [%0], %1;" ::"r"(m), "r"(c) : "memory"); }
__device__ __forceinline__ void mbar_expect(uint32_t m, int bytes) { asm volatile("mbarrier.arrive.expect_tx.shared::cta.b64 _, [%0], %1;" ::"r"(m), "r"(bytes) : "memory"); }
__device__ __forceinline__ void mbar_arrive(uint32_t m) { asm volatile("mbarrier.arrive.shared::cta.b64 _, [%0];" ::"r"(m) : "memory"); }
__device__ __forceinline__ void mbar_wait(uint32_t m, uint32_t parity) {
  uint32_t ok; int it = 0;
  do { asm volatile("{.reg .pred p; mbarrier.try_wait.parity.shared::cta.b64 p, [%1], %2; selp.u32 %0,1,0,p;}" : "=r"(ok) : "r"(m), "r"(parity) : "memory"); } while (!ok && ++it < SPIN_LIMIT); }
__device__ __forceinline__ void mbar_spin(uint32_t m, uint32_t parity) {
  uint32_t ok; int it = 0;
  do { asm volatile("{.reg .pred p; mbarrier.test_wait.parity.shared::cta.b64 p, [%1], %2; selp.u32 %0,1,0,p;}" : "=r"(ok) : "r"(m), "r"(parity) : "memory"); } while (!ok && ++it < SPIN_LIMIT); }
__device__ __forceinline__ void bar_sync(int id, int n) { asm volatile("bar.sync %0, %1;" ::"r"(id), "r"(n) : "memory"); }
__device__ __forceinline__ void bar_arrive(int id, int n) { asm volatile("bar.arrive %0, %1;" ::"r"(id), "r"(n) : "memory"); }
__device__ __forceinline__ int ld_acq(const int* p) { int v; asm volatile("ld.acquire.gpu.global.s32 %0, [%1];" : "=r"(v) : "l"(p) : "memory"); return v; }
__device__ __forceinline__ void wait_flag(const int* p, int target) { int it = 0; while (ld_acq(p) < target && ++it < SPIN_LIMIT) { __nanosleep(40); } }
__device__ __forceinline__ void fence_async() { asm volatile("fence.proxy.async.global;" ::: "memory"); }
__device__ __forceinline__ uint4 lds128(uint32_t a) { uint4 v; asm volatile("ld.shared.v4.u32 {%0,%1,%2,%3}, [%4];" : "=r"(v.x), "=r"(v.y), "=r"(v.z), "=r"(v.w) : "r"(a) : "memory"); return v; }
__device__ __forceinline__ void sts128(uint32_t a, uint4 v) { asm volatile("st.shared.v4.u32 [%0], {%1,%2,%3,%4};" ::"r"(a), "r"(v.x), "r"(v.y), "r"(v.z), "r"(v.w) : "memory"); }
__device__ __forceinline__ void sts32(uint32_t a, uint32_t v) { asm volatile("st.shared.u32 [%0], %1;" ::"r"(a), "r"(v) : "memory"); }
__device__ __forceinline__ void sts16(uint32_t a, float f) { unsigned short h = __bfloat16_as_ushort(__float2bfloat16(f)); asm volatile("st.shared.u16 [%0], %1;" ::"r"(a), "h"(h) : "memory"); }
__device__ __forceinline__ void ldsm4(uint32_t* r, uint32_t a) { asm volatile("ldmatrix.sync.aligned.m8n8.x4.shared.b16 {%0,%1,%2,%3}, [%4];" : "=r"(r[0]), "=r"(r[1]), "=r"(r[2]), "=r"(r[3]) : "r"(a) : "memory"); }
__device__ __forceinline__ void ldsm4t(uint32_t* r, uint32_t a) { asm volatile("ldmatrix.sync.aligned.m8n8.x4.trans.shared.b16 {%0,%1,%2,%3}, [%4];" : "=r"(r[0]), "=r"(r[1]), "=r"(r[2]), "=r"(r[3]) : "r"(a) : "memory"); }
__device__ __forceinline__ void mma16(float* c, uint32_t a0, uint32_t a1, uint32_t a2, uint32_t a3, uint32_t b0, uint32_t b1) {
  asm("mma.sync.aligned.m16n8k16.row.col.f32.bf16.bf16.f32 {%0,%1,%2,%3}, {%4,%5,%6,%7}, {%8,%9}, {%0,%1,%2,%3};" : "+f"(c[0]), "+f"(c[1]), "+f"(c[2]), "+f"(c[3]) : "r"(a0), "r"(a1), "r"(a2), "r"(a3), "r"(b0), "r"(b1)); }
__device__ __forceinline__ void mma8(float* c, uint32_t a0, uint32_t a1, uint32_t b0) {
  asm("mma.sync.aligned.m16n8k8.row.col.f32.bf16.bf16.f32 {%0,%1,%2,%3}, {%4,%5}, {%6}, {%0,%1,%2,%3};" : "+f"(c[0]), "+f"(c[1]), "+f"(c[2]), "+f"(c[3]) : "r"(a0), "r"(a1), "r"(b0)); }
__device__ __forceinline__ uint32_t pack2(float a, float b) { __nv_bfloat162 h = __floats2bfloat162_rn(a, b); return *(uint32_t*)&h; }
__device__ __forceinline__ float rbf(float x) { uint32_t r; asm("cvt.rn.bf16x2.f32 %0, %1, %2;" : "=r"(r) : "f"(x), "f"(0.f)); return __uint_as_float(r); }
__device__ __forceinline__ void cp16(uint32_t d, const void* s) { asm volatile("cp.async.cg.shared.global [%0], [%1], 16;" ::"r"(d), "l"(s) : "memory"); }
__device__ __forceinline__ void tma2d(uint32_t dst, const CUtensorMap* m, int c0, int c1, uint32_t mbar) {
  asm volatile("cp.async.bulk.tensor.2d.shared::cluster.global.mbarrier::complete_tx::bytes [%0], [%1, {%2,%3}], [%4];" ::"r"(dst), "l"(m), "r"(c0), "r"(c1), "r"(mbar) : "memory"); }
__device__ __forceinline__ uint64_t mkdesc(uint32_t addr, uint32_t lbo, uint32_t sbo) {
  return (uint64_t)((addr & 0x3FFFF) >> 4) | ((uint64_t)(lbo >> 4) << 16) | ((uint64_t)(sbo >> 4) << 32) | (1ull << 62); }

#define R8(i) "+f"(d[i]), "+f"(d[i+1]), "+f"(d[i+2]), "+f"(d[i+3]), "+f"(d[i+4]), "+f"(d[i+5]), "+f"(d[i+6]), "+f"(d[i+7])
__device__ __forceinline__ void wgmma256(float* d, uint64_t da, uint64_t db, int acc) {
  asm volatile("{.reg .pred p; setp.ne.b32 p, %130, 0;\n"
    "wgmma.mma_async.sync.aligned.m64n256k16.f32.bf16.bf16 {"
    "%0,%1,%2,%3,%4,%5,%6,%7,%8,%9,%10,%11,%12,%13,%14,%15,%16,%17,%18,%19,%20,%21,%22,%23,%24,%25,%26,%27,%28,%29,%30,%31,"
    "%32,%33,%34,%35,%36,%37,%38,%39,%40,%41,%42,%43,%44,%45,%46,%47,%48,%49,%50,%51,%52,%53,%54,%55,%56,%57,%58,%59,%60,%61,%62,%63,"
    "%64,%65,%66,%67,%68,%69,%70,%71,%72,%73,%74,%75,%76,%77,%78,%79,%80,%81,%82,%83,%84,%85,%86,%87,%88,%89,%90,%91,%92,%93,%94,%95,"
    "%96,%97,%98,%99,%100,%101,%102,%103,%104,%105,%106,%107,%108,%109,%110,%111,%112,%113,%114,%115,%116,%117,%118,%119,%120,%121,%122,%123,%124,%125,%126,%127"
    "}, %128, %129, p, 1, 1, 0, 1;}"
    : R8(0), R8(8), R8(16), R8(24), R8(32), R8(40), R8(48), R8(56), R8(64), R8(72), R8(80), R8(88), R8(96), R8(104), R8(112), R8(120)
    : "l"(da), "l"(db), "r"(acc)); }

__global__ void __launch_bounds__(256) prologue_kernel(const bf16* __restrict__ x, const bf16* __restrict__ mem0) {
  int tid = threadIdx.x, lane = tid & 31, warp = tid >> 5;
  int row = blockIdx.x * 8 + warp;
  {
    const uint4* src = (const uint4*)(x + (size_t)row * DM);
    uint4 u[2] = { src[lane], src[lane + 32] };
    float v[16];
    #pragma unroll
    for (int i = 0; i < 2; i++) { const __nv_bfloat162* h = (const __nv_bfloat162*)&u[i];
      #pragma unroll
      for (int k = 0; k < 4; k++) { float2 f = __bfloat1622float2(h[k]); v[i * 8 + 2 * k] = f.x; v[i * 8 + 2 * k + 1] = f.y; } }
    #pragma unroll
    for (int pass = 0; pass < 2; pass++) {
      float s = 0;
      #pragma unroll
      for (int i = 0; i < 16; i++) s += v[i];
      #pragma unroll
      for (int o = 16; o; o >>= 1) s += __shfl_xor_sync(~0u, s, o);
      float mf = s * (1.f / DM);
      float q = 0;
      #pragma unroll
      for (int i = 0; i < 16; i++) { float dd = v[i] - mf; q += dd * dd; }
      #pragma unroll
      for (int o = 16; o; o >>= 1) q += __shfl_xor_sync(~0u, q, o);
      float m = rbf(mf), var = rbf(q * (1.f / DM));
      float den = rbf(sqrtf(rbf(var + 1e-5f)));
      #pragma unroll
      for (int i = 0; i < 16; i++) v[i] = rbf(rbf(v[i] - m) / den);
      uint4 o4[2];
      #pragma unroll
      for (int i = 0; i < 2; i++) { o4[i].x = pack2(v[i*8], v[i*8+1]); o4[i].y = pack2(v[i*8+2], v[i*8+3]); o4[i].z = pack2(v[i*8+4], v[i*8+5]); o4[i].w = pack2(v[i*8+6], v[i*8+7]); }
      uint4* dst = (uint4*)((pass ? g_y : g_xn) + (size_t)row * DM);
      dst[lane] = o4[0]; dst[lane + 32] = o4[1];
    }
  }
  int gt = blockIdx.x * 256 + tid;
  float4 z4 = make_float4(0, 0, 0, 0);
  #pragma unroll
  for (int i = 0; i < 4; i++) { ((float4*)g_z)[gt + i * 65536] = z4; ((float4*)g_s)[gt + i * 65536] = z4; }
  for (int i = gt; i < NSTEP * 1536; i += 65536) {
    float4 val = z4;
    if (i < 1536) {
      int j = i / 768, c = i % 768, ci = c >> 8, w = (c & 255) >> 5, l = c & 31, g = l >> 2, t = l & 3;
      float e3[3];
      #pragma unroll
      for (int k = 0; k < 3; k++) { int e = ci * 3 + k; int mt = e >> 2, cc = e & 3;
        e3[k] = e < 8 ? __bfloat162float(mem0[(2 * t + (cc & 1)) * DM + 256 * j + 32 * w + 16 * mt + g + 8 * (cc >> 1)]) : 0.f; }
      val = make_float4(e3[0], e3[1], e3[2], 32.f);
    }
    (&g_acc[0][0][0])[i] = val;
  }
  if (gt < (int)(sizeof(Flags) / 4)) ((int*)&g_fl)[gt] = 0;
}

constexpr int R_WO = 0, R_WR = 65536, R_KT = 131072, KT_SZ = 40 * 256, R_VT = R_KT + 2 * KT_SZ, VT_SZ = 40 * 272,
              R_MEM = R_VT + 2 * VT_SZ, R_Q = R_MEM + 8 * 512, R_O = R_Q + 8 * 256, R_S = R_O + 8 * 256,
              R_SM = R_S + 8 * 40 * 4, R_RQK = R_SM + 1024, R_RV = R_RQK + 8192, R_WQ = R_RV + 4096, R_BAR = R_WQ + 32768, R_END = R_BAR + 64;
__device__ __forceinline__ uint32_t swz(uint32_t r) { return ((r & 1) << 2) | ((r >> 1) & 3); }
__device__ __forceinline__ void stsm4t(uint32_t a, uint32_t r0, uint32_t r1, uint32_t r2, uint32_t r3) { asm volatile("stmatrix.sync.aligned.m8n8.x4.trans.shared.b16 [%0], {%1,%2,%3,%4};" ::"r"(a), "r"(r0), "r"(r1), "r"(r2), "r"(r3) : "memory"); }
__device__ __forceinline__ void stsm2(uint32_t a, uint32_t r0, uint32_t r1) { asm volatile("stmatrix.sync.aligned.m8n8.x2.shared.b16 [%0], {%1,%2};" ::"r"(a), "r"(r0), "r"(r1) : "memory"); }
__device__ __forceinline__ float ex2(float x) { float r; asm("ex2.approx.ftz.f32 %0, %1;" : "=f"(r) : "f"(x)); return r; }
#define REDV4(p, a, b, c) asm volatile("red.relaxed.gpu.global.add.v4.f32 [%0], {%1,%2,%3,%4};" ::"l"(p), "f"(a), "f"(b), "f"(c), "f"(1.0f) : "memory")
constexpr int SMEM_BYTES = 232448;
static_assert(R_END <= SMEM_BYTES, "smem");

__device__ __forceinline__ void recurrence(uint32_t sb, const bf16* __restrict__ Wq, const bf16* __restrict__ Wk, const bf16* __restrict__ Wv, const bf16* __restrict__ Wo) {
  const int tid = threadIdx.x, warp = tid >> 5, lane = tid & 31, g = lane >> 2, t = lane & 3;
  const int h = blockIdx.x >> 1, j = blockIdx.x & 1;
  const uint32_t peer = j ^ 1;
  const uint32_t mQK = sb + R_BAR, mV = sb + R_BAR + 8;
  uint32_t A[2][16][4];
  const uint32_t stg = sb + R_WR;
  const int lm = lane >> 3, lr = lane & 7;
  for (int i = tid; i < 128 * 32; i += 384) { int r = i >> 5, c = i & 31; cp16(stg + r * 528 + c * 16, Wo + ((size_t)(h * 128 + r)) * DM + 256 * j + c * 8); }
  asm volatile("cp.async.wait_all;" ::: "memory"); __syncthreads();
  if (warp < 8) {
    #pragma unroll
    for (int mt = 0; mt < 2; mt++)
      #pragma unroll
      for (int ks = 0; ks < 8; ks++) {
        int k = 32 * (ks >> 1) + 8 * (lr >> 1) + (lr & 1) + 4 * (ks & 1) + 2 * (lm >> 1);
        uint32_t r[4]; ldsm4t(r, stg + k * 528 + (32 * warp + 16 * mt + 8 * (lm & 1)) * 2);
        sts128(sb + R_WO + ((warp * 16 + mt * 8 + ks) * 32 + lane) * 16, make_uint4(r[0], r[1], r[2], r[3]));
      }
  }
  __syncthreads();
  #pragma unroll 1
  for (int m = 0; m < 3; m++) {
    const bf16* W = m == 0 ? Wq : (m == 1 ? Wk : Wv);
    for (int i = tid; i < 256 * 16; i += 384) { int r = i >> 4, c = i & 15; cp16(stg + r * 272 + c * 16, W + ((size_t)(256 * j + r)) * 4096 + h * 128 + c * 8); }
    asm volatile("cp.async.wait_all;" ::: "memory"); __syncthreads();
    if ((warp >> 2) == m) {
      #pragma unroll
      for (int mt = 0; mt < 2; mt++)
        #pragma unroll
        for (int ks = 0; ks < 16; ks++) {
          int k = 32 * (ks >> 1) + 8 * (lr >> 1) + (lr & 1) + 4 * (ks & 1) + 2 * (lm >> 1);
          ldsm4t(A[mt][ks], stg + k * 272 + (32 * (warp & 3) + 16 * mt + 8 * (lm & 1)) * 2);
        }
    }
    __syncthreads();
  }
  if (warp >= 8) {
    #pragma unroll
    for (int i = 0; i < 32; i++) sts128(sb + R_WR + (((warp - 8) * 32 + i) * 32 + lane) * 16, make_uint4(A[i >> 4][i & 15][0], A[i >> 4][i & 15][1], A[i >> 4][i & 15][2], A[i >> 4][i & 15][3]));
  }
  if (warp < 4) {
    #pragma unroll
    for (int i = 0; i < 16; i++) sts128(sb + R_WQ + ((warp * 16 + i) * 32 + lane) * 16, make_uint4(A[1][i][0], A[1][i][1], A[1][i][2], A[1][i][3]));
  }
  __syncthreads();
  if (warp >= 8) {
    const uint32_t zero = blockIdx.y;
    #pragma unroll 1
    for (int s = 0; s < NSTEP; s++) {
      const int tid = otid(), lane = tid & 31, wv = (tid >> 5) - 8, g = lane >> 2, t = lane & 3;
      if (tid == 256) mbar_expect(mV, 4096);
      const uint32_t fo = (t ^ swz(g)) << 4;
      TR(1);
      bar_sync(4, 384);
      float c[4][4];
      #pragma unroll
      for (int i = 0; i < 4; i++) { c[i][0] = c[i][1] = c[i][2] = c[i][3] = 0.f; }
      #pragma unroll
      for (int p = 0; p < 8; p++) {
        uint4 b = ldc(R_MEM + g * 512 + (p >> 1) * 128 + (fo ^ ((p & 1) << 6)));
        mma16(c[0], A[0][2*p][0], A[0][2*p][1], A[0][2*p][2], A[0][2*p][3], b.x, b.y);
        mma16(c[1], A[1][2*p][0], A[1][2*p][1], A[1][2*p][2], A[1][2*p][3], b.x, b.y);
        mma16(c[2], A[0][2*p+1][0], A[0][2*p+1][1], A[0][2*p+1][2], A[0][2*p+1][3], b.z, b.w);
        mma16(c[3], A[1][2*p+1][0], A[1][2*p+1][1], A[1][2*p+1][2], A[1][2*p+1][3], b.z, b.w);
      }
      #pragma unroll
      for (int i = 0; i < 4; i++) { c[0][i] += c[2][i]; c[1][i] += c[3][i]; }
      const uint32_t rx = sb + R_RV + (wv * 64 + lane) * 16;
      { uint32_t ra = mapa(rx, peer), rm = mapa(mV, peer);
        st_async_v4(ra, c[0][0], c[0][1], c[0][2], c[0][3], rm);
        st_async_v4(ra + 512, c[1][0], c[1][1], c[1][2], c[1][3], rm); }
      TR(4);
      const bool more = s < NSTEP - 1;
      uint32_t wb = sb + (wv * 1024 + lane) * 16;
      if (more) {
        #pragma unroll
        for (int i = 0; i < 16; i++) { uint4 v = lds128(wb + R_WO + i * 512); A[0][i][0] = v.x; A[0][i][1] = v.y; A[0][i][2] = v.z; A[0][i][3] = v.w;
          if ((i % THR) == THR - 1) wb += v.x & zero; }
      }
      TR(3);
      mbar_wait(mV, s & 1);
      TR(5);
      { uint4 r0 = lds128(rx), r1 = lds128(rx + 512);
        stsm4t(sb + R_VT + (s & 1) * VT_SZ + (32 + (lane & 7)) * 272 + (4 * wv + (lane >> 3)) * 16,
          pack2(c[0][0] + __uint_as_float(r0.x), c[0][1] + __uint_as_float(r0.y)), pack2(c[0][2] + __uint_as_float(r0.z), c[0][3] + __uint_as_float(r0.w)),
          pack2(c[1][0] + __uint_as_float(r1.x), c[1][1] + __uint_as_float(r1.y)), pack2(c[1][2] + __uint_as_float(r1.z), c[1][3] + __uint_as_float(r1.w))); }
      if (more) {
        bar_arrive(3, 256);
        #pragma unroll
        for (int i = 0; i < 16; i++) { uint4 v = lds128(wb + R_WO + 8192 + i * 512); A[1][i][0] = v.x; A[1][i][1] = v.y; A[1][i][2] = v.z; A[1][i][3] = v.w;
          if ((i % THR) == THR - 1) wb += v.x & zero; }
      }
      if (!more) bar_arrive(6, 384);
      TR(8);
      if (more) {
        bar_sync(7, 256);
        #pragma unroll
        for (int i = 0; i < 4; i++) { c[i][0] = c[i][1] = c[i][2] = c[i][3] = 0.f; }
        #pragma unroll
        for (int p = 0; p < 4; p++) {
          uint4 b = ldc(R_O + g * 256 + (p >> 1) * 128 + (fo ^ ((p & 1) << 6)));
          #pragma unroll
          for (int mt = 0; mt < 4; mt++) { const uint32_t* a = A[mt >> 1][(mt & 1) * 8 + 2 * p]; mma16(c[mt], a[0], a[1], a[2], a[3], b.x, b.y); }
          #pragma unroll
          for (int mt = 0; mt < 4; mt++) { const uint32_t* a = A[mt >> 1][(mt & 1) * 8 + 2 * p + 1]; mma16(c[mt], a[0], a[1], a[2], a[3], b.z, b.w); }
        }
        TR(6);
        float4* dst = &g_acc[s + 1][j][wv * 64 + lane];
        REDV4(dst, c[0][0], c[0][1], c[0][2]); REDV4(dst + 256, c[0][3], c[1][0], c[1][1]); REDV4(dst + 512, c[1][2], c[1][3], 0.f);
        REDV4(dst + 32, c[2][0], c[2][1], c[2][2]); REDV4(dst + 288, c[2][3], c[3][0], c[3][1]); REDV4(dst + 544, c[3][2], c[3][3], 0.f);
        bar_arrive(8, 384);
        TR(7);
        #pragma unroll
        for (int i = 0; i < 32; i++) { uint4 v = lds128(wb + R_WR + i * 512); A[i >> 4][i & 15][0] = v.x; A[i >> 4][i & 15][1] = v.y; A[i >> 4][i & 15][2] = v.z; A[i >> 4][i & 15][3] = v.w; }
      }
    }
    return;
  }
  const float scale = 0.08838834764831845f, l2e = 1.4426950408889634f;
  auto prefetch = [&](int s) {
    const int vt = otid() - 160;
    if ((s & 3) == 0) { wait_flag(&g_fl.tile[s >> 2][h >> 1], 1); wait_flag(&g_fl.tile[s >> 2][16 + (h >> 1)], 1); }
    const int r = vt >> 4, c = vt & 15;
    const bf16* src = g_qkv + (size_t)(32 * s + r) * QW + h * 128 + c * 8;
    uint32_t kb = sb + R_KT + (s & 1) * KT_SZ + r * 256, vb = sb + R_VT + (s & 1) * VT_SZ + r * 272 + c * 16;
    #pragma unroll
    for (int i = 0; i < 8; i++) { cp16(kb + i * 1024 + ((c ^ swz(r + 4 * i)) << 4), src + (size_t)i * 4 * QW); cp16(vb + i * 1088, src + (size_t)i * 4 * QW + 4096); }
  };
  auto publish = [&](int s) {
    const int l = otid() & 31;
    #pragma unroll
    for (int i = 0; i < 4; i++) {
      const int vt = l + 32 * i;
      if (j == 0) { const int r = vt >> 4, c = vt & 15; uint4 v = lds128(sb + R_KT + (s & 1) * KT_SZ + (32 + r) * 256 + ((c ^ swz(r)) << 4));
        __stcg((uint4*)(g_km + ((size_t)(s * 32 + h)) * 1024) + vt, v); }
      else { uint32_t vb = sb + R_VT + (s & 1) * VT_SZ + 32 * 272 + vt * 2; uint32_t e[8];
        #pragma unroll
        for (int k = 0; k < 8; k++) { unsigned short x; asm volatile("ld.shared.u16 %0, [%1];" : "=h"(x) : "r"(vb + k * 272) : "memory"); e[k] = x; }
        __stcg((uint4*)(g_vmT + ((size_t)(s * 32 + h)) * 1024) + vt, make_uint4(e[0] | (e[1] << 16), e[2] | (e[3] << 16), e[4] | (e[5] << 16), e[6] | (e[7] << 16))); }
    }
  };
  auto flag = [&](int s) { __syncwarp(); if ((otid() & 31) == 0) { __threadfence(); atomicAdd(&g_fl.prog[s >> 2][h], 1); } __syncwarp(); };
  if (warp >= 4) {
  if (warp == 5 || warp == 6) prefetch(0);
  #pragma unroll 1
  for (int s = 0; s < NSTEP; s++) {
    TR(0); TR(1);
    const int tid = otid(), lane = tid & 31, warp = tid >> 5, g = lane >> 2, t = lane & 3;
    const uint32_t fo = (t ^ swz(g)) << 4;
    {
      if (tid == 0) mbar_expect(mQK, 8192);
      const float4* src = &g_acc[s][j][tid];
      uint4 v0, v1, v2; int it = 0; bool ok;
      do {
        asm volatile("ld.relaxed.gpu.global.v4.u32 {%0,%1,%2,%3}, [%4];" : "=r"(v0.x), "=r"(v0.y), "=r"(v0.z), "=r"(v0.w) : "l"(src) : "memory");
        asm volatile("ld.relaxed.gpu.global.v4.u32 {%0,%1,%2,%3}, [%4];" : "=r"(v1.x), "=r"(v1.y), "=r"(v1.z), "=r"(v1.w) : "l"(src + 256) : "memory");
        asm volatile("ld.relaxed.gpu.global.v4.u32 {%0,%1,%2,%3}, [%4];" : "=r"(v2.x), "=r"(v2.y), "=r"(v2.z), "=r"(v2.w) : "l"(src + 512) : "memory");
        ok = (v0.w == 0x42000000u) && (v1.w == 0x42000000u) && (v2.w == 0x42000000u);
      } while (!ok && ++it < SPIN_LIMIT);
      __syncwarp();
      stsm4t(sb + R_MEM + (lane & 7) * 512 + (((4 * warp + (lane >> 3)) ^ swz(lane & 7)) << 4),
        pack2(__uint_as_float(v0.x), __uint_as_float(v0.y)), pack2(__uint_as_float(v0.z), __uint_as_float(v1.x)),
        pack2(__uint_as_float(v1.y), __uint_as_float(v1.z)), pack2(__uint_as_float(v2.x), __uint_as_float(v2.y)));
    }
    TR(2);
    asm volatile("cp.async.wait_all;" ::: "memory");
    bar_sync(1, 256);
    TR(3);
    float c[4][4];
    #pragma unroll
    for (int i = 0; i < 4; i++) { c[i][0] = c[i][1] = c[i][2] = c[i][3] = 0.f; }
    #pragma unroll
    for (int p = 0; p < 8; p++) {
      uint4 b = ldc(R_MEM + g * 512 + (p >> 1) * 128 + (fo ^ ((p & 1) << 6)));
      mma16(c[0], A[0][2*p][0], A[0][2*p][1], A[0][2*p][2], A[0][2*p][3], b.x, b.y);
      mma16(c[1], A[1][2*p][0], A[1][2*p][1], A[1][2*p][2], A[1][2*p][3], b.x, b.y);
      mma16(c[2], A[0][2*p+1][0], A[0][2*p+1][1], A[0][2*p+1][2], A[0][2*p+1][3], b.z, b.w);
      mma16(c[3], A[1][2*p+1][0], A[1][2*p+1][1], A[1][2*p+1][2], A[1][2*p+1][3], b.z, b.w);
    }
    #pragma unroll
    for (int i = 0; i < 4; i++) { c[0][i] += c[2][i]; c[1][i] += c[3][i]; }
    const uint32_t rx = sb + R_RQK + (warp * 64 + lane) * 16;
    { uint32_t ra = mapa(rx, peer), rm = mapa(mQK, peer);
      st_async_v4(ra, c[0][0], c[0][1], c[0][2], c[0][3], rm);
      st_async_v4(ra + 512, c[1][0], c[1][1], c[1][2], c[1][3], rm); }
    bar_arrive(4, 384);
    TR(4);
    const uint32_t so = (lane & 7) * 256 + (((4 * (warp & 3) + (lane >> 3)) ^ swz(lane & 7)) << 4);
    mbar_wait(mQK, s & 1);
    TR(5);
    uint32_t m0, m1, m2, m3;
    { uint4 r0 = lds128(rx), r1 = lds128(rx + 512);
      m0 = pack2(c[0][0] + __uint_as_float(r0.x), c[0][1] + __uint_as_float(r0.y)); m1 = pack2(c[0][2] + __uint_as_float(r0.z), c[0][3] + __uint_as_float(r0.w));
      m2 = pack2(c[1][0] + __uint_as_float(r1.x), c[1][1] + __uint_as_float(r1.y)); m3 = pack2(c[1][2] + __uint_as_float(r1.z), c[1][3] + __uint_as_float(r1.w)); }
    stsm4t(sb + R_KT + (s & 1) * KT_SZ + 32 * 256 + so, m0, m1, m2, m3);
    if (s == NSTEP - 1) { bar_sync(6, 384); if (warp == 7) { publish(s - 1); flag(s - 2); flag(s - 1); } if (warp == 6) { publish(s); flag(s); } break; }
    asm("movmatrix.sync.aligned.m8n8.trans.b16 %0, %0;" : "+r"(m0)); asm("movmatrix.sync.aligned.m8n8.trans.b16 %0, %0;" : "+r"(m1));
    asm("movmatrix.sync.aligned.m8n8.trans.b16 %0, %0;" : "+r"(m2)); asm("movmatrix.sync.aligned.m8n8.trans.b16 %0, %0;" : "+r"(m3));
    TR(8);
    bar_sync(5, 256);
    TR(9);
    { uint32_t qa[4]; ldsm4(qa, sb + R_Q + so);
      #pragma unroll
      for (int i = 0; i < 2; i++) { c[i][0] = c[i][1] = c[i][2] = c[i][3] = 0.f; }
      mma16(c[0], qa[0], 0, qa[1], 0, m0, m1); mma16(c[1], qa[2], 0, qa[3], 0, m2, m3);
      asm volatile("st.shared.v2.f32 [%0], {%1,%2};" ::"r"(sb + R_SM + (warp - 4) * 256 + lane * 8), "f"(c[0][0] + c[1][0]), "f"(c[0][1] + c[1][1]) : "memory"); }
    bar_arrive(2, 256);
    TR(10);
    if (warp == 7) { if (s > 1) flag(s - 2); if (s > 0) publish(s - 1); } else if (warp >= 5 && s < NSTEP - 2) prefetch(s + 1);
    TR(7);
    bar_sync(8, 384);
    { long long t0 = clock64(); while (clock64() - t0 < PDELAY); }
  }
  return;
  }
  #pragma unroll 1
  for (int s = 0; s < NSTEP; s++) {
    TR(0); TR(1);
    const int tid = otid(), lane = tid & 31, warp = tid >> 5, g = lane >> 2, t = lane & 3;
    const uint32_t fo = (t ^ swz(g)) << 4;
    {
      if (tid == 0) mbar_expect(mQK, 8192);
      const float4* src = &g_acc[s][j][tid];
      uint4 v0, v1, v2; int it = 0; bool ok;
      do {
        asm volatile("ld.relaxed.gpu.global.v4.u32 {%0,%1,%2,%3}, [%4];" : "=r"(v0.x), "=r"(v0.y), "=r"(v0.z), "=r"(v0.w) : "l"(src) : "memory");
        asm volatile("ld.relaxed.gpu.global.v4.u32 {%0,%1,%2,%3}, [%4];" : "=r"(v1.x), "=r"(v1.y), "=r"(v1.z), "=r"(v1.w) : "l"(src + 256) : "memory");
        asm volatile("ld.relaxed.gpu.global.v4.u32 {%0,%1,%2,%3}, [%4];" : "=r"(v2.x), "=r"(v2.y), "=r"(v2.z), "=r"(v2.w) : "l"(src + 512) : "memory");
        ok = (v0.w == 0x42000000u) && (v1.w == 0x42000000u) && (v2.w == 0x42000000u);
      } while (!ok && ++it < SPIN_LIMIT);
      __syncwarp();
      stsm4t(sb + R_MEM + (lane & 7) * 512 + (((4 * warp + (lane >> 3)) ^ swz(lane & 7)) << 4),
        pack2(__uint_as_float(v0.x), __uint_as_float(v0.y)), pack2(__uint_as_float(v0.z), __uint_as_float(v1.x)),
        pack2(__uint_as_float(v1.y), __uint_as_float(v1.z)), pack2(__uint_as_float(v2.x), __uint_as_float(v2.y)));
    }
    TR(2);

    bar_sync(1, 256);
    TR(3);
    float c[4][4];
    #pragma unroll
    for (int i = 0; i < 4; i++) { c[i][0] = c[i][1] = c[i][2] = c[i][3] = 0.f; }
    #pragma unroll
    for (int p = 0; p < 8; p++) {
      uint4 b = ldc(R_MEM + g * 512 + (p >> 1) * 128 + (fo ^ ((p & 1) << 6)));
      mma16(c[0], A[0][2*p][0], A[0][2*p][1], A[0][2*p][2], A[0][2*p][3], b.x, b.y);
      mma16(c[1], A[1][2*p][0], A[1][2*p][1], A[1][2*p][2], A[1][2*p][3], b.x, b.y);
      mma16(c[2], A[0][2*p+1][0], A[0][2*p+1][1], A[0][2*p+1][2], A[0][2*p+1][3], b.z, b.w);
      mma16(c[3], A[1][2*p+1][0], A[1][2*p+1][1], A[1][2*p+1][2], A[1][2*p+1][3], b.z, b.w);
    }
    #pragma unroll
    for (int i = 0; i < 4; i++) { c[0][i] += c[2][i]; c[1][i] += c[3][i]; }
    const uint32_t rx = sb + R_RQK + (warp * 64 + lane) * 16;
    { uint32_t ra = mapa(rx, peer), rm = mapa(mQK, peer);
      st_async_v4(ra, c[0][0], c[0][1], c[0][2], c[0][3], rm);
      st_async_v4(ra + 512, c[1][0], c[1][1], c[1][2], c[1][3], rm); }
    bar_arrive(4, 384);
    TR(4);
    const uint32_t so = (lane & 7) * 256 + (((4 * (warp & 3) + (lane >> 3)) ^ swz(lane & 7)) << 4);
    if (s == NSTEP - 1) { mbar_wait(mQK, s & 1); bar_arrive(6, 384); break; }
    uint4 kf[4]; uint32_t vf[4][4];
    const uint32_t vb = sb + R_VT + (s & 1) * VT_SZ + (lane & 15) * 272 + (32 * warp + 8 * (lane >> 4)) * 2;
    #pragma unroll
    for (int p = 0; p < 4; p++) kf[p] = lds128(sb + R_KT + (s & 1) * KT_SZ + warp * 2048 + g * 256 + (p >> 1) * 128 + (fo ^ ((p & 1) << 6)));
    #pragma unroll
    for (int i = 0; i < 4; i++) ldsm4t(vf[i], vb + (i >> 1) * 16 * 272 + (i & 1) * 32);
    mbar_wait(mQK, s & 1);
    TR(5);
    uint32_t m0, m1, m2, m3;
    { uint4 r0 = lds128(rx), r1 = lds128(rx + 512);
      m0 = pack2(c[0][0] + __uint_as_float(r0.x), c[0][1] + __uint_as_float(r0.y)); m1 = pack2(c[0][2] + __uint_as_float(r0.z), c[0][3] + __uint_as_float(r0.w));
      m2 = pack2(c[1][0] + __uint_as_float(r1.x), c[1][1] + __uint_as_float(r1.y)); m3 = pack2(c[1][2] + __uint_as_float(r1.z), c[1][3] + __uint_as_float(r1.w)); }
    stsm4t(sb + R_Q + so, m0, m1, m2, m3);
    TR(8);
    bar_sync(5, 256);
    TR(9);
    {
      uint4 qa[4];
      #pragma unroll
      for (int p = 0; p < 4; p++) qa[p] = lds128(sb + R_Q + g * 256 + (p >> 1) * 128 + (fo ^ ((p & 1) << 6)));
      #pragma unroll
      for (int i = 0; i < 4; i++) { c[i][0] = c[i][1] = c[i][2] = c[i][3] = 0.f; }
      #pragma unroll
      for (int p = 0; p < 4; p++) { mma16(c[(p & 1) * 2], qa[p].x, 0, qa[p].y, 0, kf[p].x, kf[p].y); mma16(c[(p & 1) * 2 + 1], qa[p].z, 0, qa[p].w, 0, kf[p].z, kf[p].w); }
      float a = rbf(rbf((c[0][0] + c[1][0]) + (c[2][0] + c[3][0])) * scale) * l2e, b = rbf(rbf((c[0][1] + c[1][1]) + (c[2][1] + c[3][1])) * scale) * l2e;
      asm volatile("st.shared.v2.f32 [%0], {%1,%2};" ::"r"(sb + R_S + g * 160 + (8 * warp + 2 * t) * 4), "f"(a), "f"(b) : "memory");
    }
    TR(10);
    bar_sync(2, 256);
    TR(11);
    float sv[10], pm[8];
    #pragma unroll
    for (int i = 0; i < 4; i++) asm volatile("ld.shared.v2.f32 {%0,%1}, [%2];" : "=f"(pm[2*i]), "=f"(pm[2*i+1]) : "r"(sb + R_SM + i * 256 + lane * 8) : "memory");
    #pragma unroll
    for (int i = 0; i < 4; i++) asm volatile("ld.shared.v2.f32 {%0,%1}, [%2];" : "=f"(sv[2*i]), "=f"(sv[2*i+1]) : "r"(sb + R_S + g * 160 + (8 * i + 2 * t) * 4) : "memory");
    sv[8] = rbf(rbf((pm[0] + pm[2]) + (pm[4] + pm[6])) * scale) * l2e; sv[9] = rbf(rbf((pm[1] + pm[3]) + (pm[5] + pm[7])) * scale) * l2e;
    float mx = fmaxf(fmaxf(fmaxf(sv[0], sv[1]), fmaxf(sv[2], sv[3])), fmaxf(fmaxf(sv[4], sv[5]), fmaxf(sv[6], sv[7])));
    mx = fmaxf(mx, fmaxf(sv[8], sv[9]));
    mx = fmaxf(mx, __shfl_xor_sync(~0u, mx, 1)); mx = fmaxf(mx, __shfl_xor_sync(~0u, mx, 2));
    uint32_t P[5];
    #pragma unroll
    for (int i = 0; i < 5; i++) P[i] = pack2(ex2(sv[2*i] - mx), ex2(sv[2*i+1] - mx));
    TR(6);
    #pragma unroll
    for (int i = 0; i < 4; i++) { c[i][0] = c[i][1] = c[i][2] = c[i][3] = 0.f; }
    #pragma unroll
    for (int kk = 0; kk < 2; kk++) {
      mma16(c[0], P[2*kk], 0, P[2*kk+1], 0, vf[2*kk][0], vf[2*kk][1]); mma16(c[1], P[2*kk], 0, P[2*kk+1], 0, vf[2*kk][2], vf[2*kk][3]);
      mma16(c[2], P[2*kk], 0, P[2*kk+1], 0, vf[2*kk+1][0], vf[2*kk+1][1]); mma16(c[3], P[2*kk], 0, P[2*kk+1], 0, vf[2*kk+1][2], vf[2*kk+1][3]);
    }
    float sum = 0.f;
    #pragma unroll
    for (int i = 0; i < 5; i++) sum += __uint_as_float(P[i] << 16) + __uint_as_float(P[i] & 0xffff0000u);
    sum += __shfl_xor_sync(~0u, sum, 1); sum += __shfl_xor_sync(~0u, sum, 2);
    float inv; asm("rcp.approx.ftz.f32 %0, %1;" : "=f"(inv) : "f"(sum));
    bar_sync(3, 256);
    { uint32_t r[4]; ldsm4t(r, sb + R_VT + (s & 1) * VT_SZ + (32 + (lane & 7)) * 272 + (4 * warp + (lane >> 3)) * 16);
      #pragma unroll
      for (int i = 0; i < 4; i++) mma8(c[i], P[4], 0, r[i]); }
    asm volatile("stmatrix.sync.aligned.m8n8.x4.shared.b16 [%0], {%1,%2,%3,%4};" ::"r"(sb + R_O + so),
      "r"(pack2(c[0][0] * inv, c[0][1] * inv)), "r"(pack2(c[1][0] * inv, c[1][1] * inv)), "r"(pack2(c[2][0] * inv, c[2][1] * inv)), "r"(pack2(c[3][0] * inv, c[3][1] * inv)) : "memory");
    bar_arrive(7, 256);
    TR(7);
    bar_sync(8, 384);
    long long t0 = clock64();
    #pragma unroll
    for (int i = 0; i < 16; i++) { uint4 v = lds128(sb + R_WQ + ((warp * 16 + i) * 32 + lane) * 16); A[1][i][0] = v.x; A[1][i][1] = v.y; A[1][i][2] = v.z; A[1][i][3] = v.w; }
    while (clock64() - t0 < PDELAY);
  }
}

constexpr int I_M1 = 512, I_Q = 624, I_M2 = 880, I_AT = 1008, I_G = I_AT + 32, GSZ = 56, I_END = I_G + 15 * GSZ + 24;
constexpr int B_STG = 4 * 49152, B_BAR = B_STG + 8 * 2304;
struct Item { int type, rb, nt, ks; };
__device__ __forceinline__ Item decode(int it) {
  Item r; r.ks = 0;
  if (it < I_M1) { r.type = 0; r.rb = it >> 5; r.nt = it & 31; }
  else if (it < I_Q) { int i = it - I_M1; r.type = 1; r.rb = i / 7; r.nt = i % 7; }
  else if (it < I_M2) { int i = it - I_Q; r.type = 0; r.rb = i >> 4; r.nt = 32 + (i & 15); }
  else if (it < I_AT) { int i = it - I_M2; r.type = 2; r.rb = i >> 3; r.nt = (i >> 2) & 1; r.ks = i & 3; }
  else if (it < I_G) { r.type = 3; r.rb = 0; r.nt = it - I_AT; }
  else {
    int i = it - I_G, gi = i / GSZ, q = i % GSZ; if (gi == 15) q += 32;
    if (q < 32) { r.type = 3; r.rb = gi + 1; r.nt = q; }
    else if (q < 48) { r.type = 4; r.rb = gi; r.nt = (q - 32) >> 3; r.ks = (q - 32) & 7; }
    else { r.type = 5; r.rb = gi; r.nt = q - 48; } }
  return r;
}
__device__ __forceinline__ float gelu_t(float x) { float u = 0.7978845608028654f * (x + 0.044715f * x * x * x); float th; asm("tanh.approx.f32 %0, %1;" : "=f"(th) : "f"(u)); float hx = 0.5f * x; return fmaf(hx, th, hx); }

__device__ __forceinline__ void bulk(uint32_t sb, const Maps& mp, const bf16* __restrict__ x, const bf16* __restrict__ b1, const bf16* __restrict__ b2, bf16* __restrict__ out) {
  const int tid = threadIdx.x, warp = tid >> 5, lane = tid & 31, g = lane >> 2, t = lane & 3;
  const int bid = blockIdx.x - NREC;
  const uint32_t full = sb + B_BAR, empty = sb + B_BAR + 32, ifull = sb + B_BAR + 64, iempty = sb + B_BAR + 80;
  volatile int* ring = (volatile int*)(__cvta_shared_to_generic(sb + B_BAR + 96));
  if (warp >= 8) {
    asm volatile("setmaxnreg.dec.sync.aligned.u32 40;");
    if (tid == 256) {
      uint32_t st = 0, ph = 0;
      for (int n = 0;; n++) {
        int it = n == 0 ? bid : NBULK + atomicAdd(&g_fl.next, 1);
        Item I = decode(it);
        if (it < I_END) {
          if (I.type == 5) { wait_flag(&g_fl.s[I.rb][0], 16); wait_flag(&g_fl.z[I.rb][0], 8); }
          else if (I.type == 3) { wait_flag(&g_fl.prog[I.rb][I.nt], 8); wait_flag(&g_fl.tile[I.rb][I.nt >> 1], 1); wait_flag(&g_fl.tile[I.rb][16 + (I.nt >> 1)], 1); wait_flag(&g_fl.tile[I.rb][32 + (I.nt >> 1)], 1); fence_async(); }
          else if (I.type == 2) { wait_flag(&g_fl.hid[I.rb], 7); fence_async(); }
          else if (I.type == 4) { wait_flag(&g_fl.o[I.rb][I.ks], 4); fence_async(); }
        }
        mbar_wait(iempty + (n & 1) * 8, ((n >> 1) & 1) ^ 1);
        ring[n & 1] = it; mbar_arrive(ifull + (n & 1) * 8);
        if (it >= I_END) break;
        if (I.type == 5) continue;
        if (I.type == 3) {
          for (int m = 0; m < 3; m++) {
            mbar_wait(empty + st * 8, ph ^ 1);
            mbar_expect(full + st * 8, 32768);
            int col = (m == 0 ? 8192 : (m == 1 ? 0 : 4096)) + I.nt * 128;
            tma2d(sb + st * 49152, &mp.qkv, col, I.rb * 128, full + st * 8);
            tma2d(sb + st * 49152 + 16384, &mp.qkv, col + 64, I.rb * 128, full + st * 8);
            if (++st == 4) { st = 0; ph ^= 1; }
          }
          continue;
        }
        const CUtensorMap *ma, *mb; int nkb = 8, kb0 = 0, n0;
        if (I.type == 0) { ma = &mp.xn; mb = I.nt < 16 ? &mp.wk : (I.nt < 32 ? &mp.wv : &mp.wq); n0 = (I.nt & 15) * 256; }
        else if (I.type == 1) { ma = &mp.y; mb = &mp.w1; n0 = I.nt * 256; }
        else if (I.type == 2) { ma = &mp.hid; mb = &mp.w2; n0 = I.nt * 256; nkb = 7; kb0 = I.ks * 7; }
        else { ma = &mp.o; mb = &mp.wo; n0 = I.nt * 256; kb0 = I.ks * 8; }
        for (int kb = kb0; kb < kb0 + nkb; kb++) {
          mbar_wait(empty + st * 8, ph ^ 1);
          mbar_expect(full + st * 8, 49152);
          uint32_t sa = sb + st * 49152;
          tma2d(sa, ma, kb * 64, I.rb * 128, full + st * 8);
          #pragma unroll
          for (int q = 0; q < 4; q++) tma2d(sa + 16384 + q * 8192, mb, n0 + q * 64, kb * 64, full + st * 8);
          if (++st == 4) { st = 0; ph ^= 1; }
        }
      }
    } else if (warp == 9) {
      for (int n = 0;; n++) {
        mbar_wait(ifull + (n & 1) * 8, (n >> 1) & 1);
        int it = ring[n & 1];
        if (it >= I_END) break;
        Item I = decode(it);
        bar_sync(6 + (n & 1), 288);
        if (lane == 0) {
          if (I.type != 5) {
            fence_async(); __threadfence();
            int* f = I.type == 0 ? &g_fl.tile[I.rb][I.nt] : I.type == 1 ? &g_fl.hid[I.rb] : I.type == 2 ? &g_fl.z[I.rb][0] : I.type == 3 ? &g_fl.o[I.rb][I.nt >> 2] : &g_fl.s[I.rb][0];
            atomicAdd(f, 1);
          }
          mbar_arrive(iempty + (n & 1) * 8);
        }
      }
    }
    return;
  }
  asm volatile("setmaxnreg.inc.sync.aligned.u32 232;");
  const int wg = warp >> 2;
  const uint32_t stg = sb + B_STG + warp * 2304;
  const int lm = lane >> 3, lr = lane & 7;
  uint32_t st = 0, ph = 0;
  float d[128];
  #pragma unroll 1
  for (int n = 0;; n++) {
    mbar_wait(ifull + (n & 1) * 8, (n >> 1) & 1);
    const int it = ring[n & 1];
    __syncwarp(); if (lane == 0) mbar_arrive(iempty + (n & 1) * 8);
    if (it >= I_END) break;
    Item I = decode(it);
    const int row0 = I.rb * 128 + warp * 16;
    TB(0);
    if (I.type == 5) {
      #pragma unroll
      for (int i = 0; i < 4; i++) {
        size_t off = (size_t)(I.rb * 128 + I.nt * 16 + warp * 2 + (i >> 1)) * DM + (i & 1) * 256 + lane * 8;
        float4 s0 = __ldcg((const float4*)(g_s + off)), s1 = __ldcg((const float4*)(g_s + off + 4));
        float4 z0 = __ldcg((const float4*)(g_z + off)), z1 = __ldcg((const float4*)(g_z + off + 4));
        uint4 xv = *(const uint4*)(x + off), bv = *(const uint4*)(b2 + (i & 1) * 256 + lane * 8);
        float sa[8] = {s0.x, s0.y, s0.z, s0.w, s1.x, s1.y, s1.z, s1.w}, za[8] = {z0.x, z0.y, z0.z, z0.w, z1.x, z1.y, z1.z, z1.w}, r[8];
        #pragma unroll
        for (int e = 0; e < 8; e++) { float xx = __bfloat162float(((const bf16*)&xv)[e]), bb = __bfloat162float(((const bf16*)&bv)[e]);
          float u = rbf(rbf(za[e]) + bb); float gg = rbf(__fdividef(u, 1.f + __expf(-u))); r[e] = xx + rbf(rbf(sa[e]) * gg); }
        *(uint4*)(out + off) = make_uint4(pack2(r[0], r[1]), pack2(r[2], r[3]), pack2(r[4], r[5]), pack2(r[6], r[7]));
      }
      bar_arrive(6 + (n & 1), 288);
      continue;
    }
    if (I.type == 3) {
      const int h = I.nt, seg = warp >> 1, half = warp & 1, step = I.rb * 4 + seg;
      uint32_t kmr[16], vmr[16];
      { const uint32_t* km = (const uint32_t*)(g_km + ((size_t)(step * 32 + h)) * 1024) + g * 64 + t;
        const uint32_t* vm = (const uint32_t*)(g_vmT + ((size_t)(step * 32 + h)) * 1024) + g * 4 + t;
        #pragma unroll
        for (int i = 0; i < 16; i++) { kmr[i] = __ldcg(km + i * 4); vmr[i] = __ldcg(vm + i * 32); } }
      uint32_t sQ = sb + st * 49152; mbar_wait(full + st * 8, ph); uint32_t eQ = empty + st * 8; if (++st == 4) { st = 0; ph ^= 1; }
      uint32_t sK = sb + st * 49152; mbar_wait(full + st * 8, ph); uint32_t eK = empty + st * 8; if (++st == 4) { st = 0; ph ^= 1; }
      float sc[5][4];
      #pragma unroll
      for (int i = 0; i < 5; i++) { sc[i][0] = sc[i][1] = sc[i][2] = sc[i][3] = 0.f; }
      #pragma unroll
      for (int ks = 0; ks < 8; ks++) {
        uint32_t a[4]; { int r = warp * 16 + 8 * (lm & 1) + lr, c8 = 2 * ks + (lm >> 1); ldsm4(a, sQ + (c8 >> 3) * 16384 + r * 128 + (((c8 & 7) ^ (r & 7)) << 4)); }
        #pragma unroll
        for (int np = 0; np < 2; np++) {
          if (np == 1 && half == 0) continue;
          uint32_t b[4]; int r = seg * 32 + 16 * np + 8 * (lm >> 1) + lr, c8 = 2 * ks + (lm & 1);
          ldsm4(b, sK + (c8 >> 3) * 16384 + r * 128 + (((c8 & 7) ^ (r & 7)) << 4));
          mma16(sc[2*np], a[0], a[1], a[2], a[3], b[0], b[1]); mma16(sc[2*np+1], a[0], a[1], a[2], a[3], b[2], b[3]);
        }
        mma16(sc[4], a[0], a[1], a[2], a[3], kmr[2*ks], kmr[2*ks+1]);
      }
      __syncwarp(); if (lane == 0) { mbar_arrive(eQ); mbar_arrive(eK); }
      const float scale = 0.08838834764831845f;
      uint32_t P[5][2];
      #pragma unroll
      for (int rr = 0; rr < 2; rr++) {
        const int qi = 16 * half + g + 8 * rr;
        float mx = -3.0e38f;
        #pragma unroll
        for (int i = 0; i < 5; i++)
          #pragma unroll
          for (int e = 0; e < 2; e++) { float v = rbf(rbf(sc[i][2*rr+e]) * scale); if (i < 4 && 8 * i + 2 * t + e > qi) v = -1.0e9f; sc[i][2*rr+e] = v; mx = fmaxf(mx, v); }
        mx = fmaxf(mx, __shfl_xor_sync(~0u, mx, 1)); mx = fmaxf(mx, __shfl_xor_sync(~0u, mx, 2));
        float sum = 0;
        #pragma unroll
        for (int i = 0; i < 5; i++)
          #pragma unroll
          for (int e = 0; e < 2; e++) { float v = __expf(sc[i][2*rr+e] - mx); sc[i][2*rr+e] = v; sum += v; }
        sum += __shfl_xor_sync(~0u, sum, 1); sum += __shfl_xor_sync(~0u, sum, 2);
        float inv = __fdividef(1.f, sum);
        #pragma unroll
        for (int i = 0; i < 5; i++) P[i][rr] = pack2(sc[i][2*rr] * inv, sc[i][2*rr+1] * inv);
      }
      uint32_t sV = sb + st * 49152; mbar_wait(full + st * 8, ph); uint32_t eV = empty + st * 8; if (++st == 4) { st = 0; ph ^= 1; }
      #pragma unroll
      for (int i = 0; i < 64; i++) d[i] = 0.f;
      #pragma unroll
      for (int n2 = 0; n2 < 8; n2++) {
        #pragma unroll
        for (int kk = 0; kk < 2; kk++) {
          if (kk == 1 && half == 0) continue;
          uint32_t b[4]; int r = seg * 32 + 16 * kk + 8 * (lm & 1) + lr, c8 = 2 * n2 + (lm >> 1);
          ldsm4t(b, sV + (c8 >> 3) * 16384 + r * 128 + (((c8 & 7) ^ (r & 7)) << 4));
          mma16(d + 8 * n2, P[2*kk][0], P[2*kk][1], P[2*kk+1][0], P[2*kk+1][1], b[0], b[1]);
          mma16(d + 8 * n2 + 4, P[2*kk][0], P[2*kk][1], P[2*kk+1][0], P[2*kk+1][1], b[2], b[3]);
        }
        mma8(d + 8 * n2, P[4][0], P[4][1], vmr[2*n2]); mma8(d + 8 * n2 + 4, P[4][0], P[4][1], vmr[2*n2+1]);
      }
      __syncwarp(); if (lane == 0) mbar_arrive(eV);
      #pragma unroll
      for (int ch = 0; ch < 2; ch++) {
        #pragma unroll
        for (int i = 0; i < 8; i++) { const float* a = d + ch * 32 + i * 4;
          sts32(stg + g * 144 + i * 16 + t * 4, pack2(a[0], a[1])); sts32(stg + (g + 8) * 144 + i * 16 + t * 4, pack2(a[2], a[3])); }
        __syncwarp();
        #pragma unroll
        for (int i = 0; i < 4; i++) { int r = i * 4 + lm; uint4 v = lds128(stg + r * 144 + lr * 16);
          *(uint4*)(g_o + (size_t)(row0 + r) * 4096 + h * 128 + ch * 64 + lr * 8) = v; }
        __syncwarp();
      }
      bar_arrive(6 + (n & 1), 288);
      continue;
    }
    const int nkb = I.type == 2 ? 7 : 8;
    uint32_t prev = 0;
    for (int kb = 0; kb < nkb; kb++) {
      mbar_wait(full + st * 8, ph);
      uint32_t sa = sb + st * 49152;
      asm volatile("wgmma.fence.sync.aligned;" ::: "memory");
      #pragma unroll
      for (int k = 0; k < 4; k++)
        wgmma256(d, mkdesc(sa + wg * 8192 + k * 32, 16, 1024), mkdesc(sa + 16384 + k * 2048, 8192, 1024), (kb | k) != 0);
      asm volatile("wgmma.commit_group.sync.aligned;" ::: "memory");
      if (kb > 0) { asm volatile("wgmma.wait_group.sync.aligned 1;" ::: "memory"); if (lane == 0) mbar_arrive(prev); }
      prev = empty + st * 8;
      if (++st == 4) { st = 0; ph ^= 1; }
    }
    asm volatile("wgmma.wait_group.sync.aligned 0;" ::: "memory");
    if (lane == 0) mbar_arrive(prev);
    TB(1);
    if (I.type <= 1) {
      bf16* dst; int ld;
      if (I.type == 0) { dst = g_qkv + (size_t)row0 * QW + I.nt * 256; ld = QW; } else { dst = g_hid + (size_t)row0 * FF + I.nt * 256; ld = FF; }
      #pragma unroll
      for (int ch = 0; ch < 4; ch++) {
        #pragma unroll
        for (int i = 0; i < 8; i++) { float* a = d + ch * 32 + i * 4;
          if (I.type == 1) { float2 bb = __bfloat1622float2(*(const __nv_bfloat162*)(b1 + I.nt * 256 + ch * 64 + i * 8 + 2 * t));
            a[0] = gelu_t(rbf(rbf(a[0]) + bb.x)); a[1] = gelu_t(rbf(rbf(a[1]) + bb.y)); a[2] = gelu_t(rbf(rbf(a[2]) + bb.x)); a[3] = gelu_t(rbf(rbf(a[3]) + bb.y)); }
          sts32(stg + g * 144 + i * 16 + t * 4, pack2(a[0], a[1])); sts32(stg + (g + 8) * 144 + i * 16 + t * 4, pack2(a[2], a[3])); }
        __syncwarp();
        #pragma unroll
        for (int i = 0; i < 4; i++) { int r = i * 4 + lm; uint4 v = lds128(stg + r * 144 + lr * 16); *(uint4*)(dst + (size_t)r * ld + ch * 64 + lr * 8) = v; }
        __syncwarp();
      }
    } else {
      float* dst = (I.type == 2 ? g_z : g_s) + (size_t)(row0 + g) * DM + I.nt * 256 + 2 * t;
      #pragma unroll
      for (int i = 0; i < 32; i++) {
        asm volatile("red.relaxed.gpu.global.add.v2.f32 [%0], {%1,%2};" ::"l"(dst + i * 8), "f"(d[4*i]), "f"(d[4*i+1]) : "memory");
        asm volatile("red.relaxed.gpu.global.add.v2.f32 [%0], {%1,%2};" ::"l"(dst + 8 * DM + i * 8), "f"(d[4*i+2]), "f"(d[4*i+3]) : "memory");
      }
    }
    bar_arrive(6 + (n & 1), 288);
  }
}

__global__ void __cluster_dims__(2, 1, 1) __launch_bounds__(384, 1)
main_kernel(const __grid_constant__ Maps mp, const bf16* x, const bf16* Wq, const bf16* Wk, const bf16* Wv, const bf16* Wo, const bf16* b1, const bf16* b2, bf16* out) {
  const uint32_t sb = smem_u32(smem_raw);
  if (sb & 1023) __trap();
  if (threadIdx.x == 0) {
    if (blockIdx.x < NREC) { mbar_init(sb + R_BAR, 1); mbar_init(sb + R_BAR + 8, 1); }
    else { for (int i = 0; i < 4; i++) { mbar_init(sb + B_BAR + i * 8, 1); mbar_init(sb + B_BAR + 32 + i * 8, 8); }
      for (int i = 0; i < 2; i++) { mbar_init(sb + B_BAR + 64 + i * 8, 1); mbar_init(sb + B_BAR + 80 + i * 8, 9); } }
    asm volatile("fence.mbarrier_init.release.cluster;" ::: "memory");
  }
  asm volatile("barrier.cluster.arrive.release.aligned; barrier.cluster.wait.acquire.aligned;" ::: "memory");
  if (blockIdx.x < NREC) recurrence(sb, Wq, Wk, Wv, Wo);
  else bulk(sb, mp, x, b1, b2, out);
}

typedef CUresult (*EncFn)(CUtensorMap*, CUtensorMapDataType, cuuint32_t, void*, const cuuint64_t*, const cuuint64_t*, const cuuint32_t*, const cuuint32_t*, CUtensorMapInterleave, CUtensorMapSwizzle, CUtensorMapL2promotion, CUtensorMapFloatOOBfill);
static void mk(EncFn f, CUtensorMap* m, const void* p, uint64_t rows, uint64_t cols, uint32_t boxr) {
  cuuint64_t dims[2] = {cols, rows}, str[1] = {cols * 2}; cuuint32_t box[2] = {64, boxr}, es[2] = {1, 1};
  f(m, CU_TENSOR_MAP_DATA_TYPE_BFLOAT16, 2, (void*)p, dims, str, box, es, CU_TENSOR_MAP_INTERLEAVE_NONE, CU_TENSOR_MAP_SWIZZLE_128B, CU_TENSOR_MAP_L2_PROMOTION_L2_256B, CU_TENSOR_MAP_FLOAT_OOB_FILL_NONE);
}
extern "C" void kernel_launch(void* const* d_in, const int* in_sizes, int n_in, void* d_out, int out_size) {
  const bf16 *x = (const bf16*)d_in[0], *mem0 = (const bf16*)d_in[1], *Wq = (const bf16*)d_in[2], *Wk = (const bf16*)d_in[3], *Wv = (const bf16*)d_in[4], *Wo = (const bf16*)d_in[5];
  const bf16 *w1 = (const bf16*)d_in[8], *b1 = (const bf16*)d_in[9], *w2 = (const bf16*)d_in[10], *b2 = (const bf16*)d_in[11];
  void* fn = nullptr; cudaDriverEntryPointQueryResult qr;
  cudaGetDriverEntryPoint("cuTensorMapEncodeTiled", &fn, cudaEnableDefault, &qr);
  EncFn f = (EncFn)fn;
  void *pxn, *py, *ph, *po, *pq;
  cudaGetSymbolAddress(&pxn, g_xn); cudaGetSymbolAddress(&py, g_y); cudaGetSymbolAddress(&ph, g_hid); cudaGetSymbolAddress(&po, g_o); cudaGetSymbolAddress(&pq, g_qkv);
  Maps mp;
  mk(f, &mp.xn, pxn, SEQ, DM, 128); mk(f, &mp.y, py, SEQ, DM, 128); mk(f, &mp.hid, ph, SEQ, FF, 128); mk(f, &mp.o, po, SEQ, 4096, 128); mk(f, &mp.qkv, pq, SEQ, QW, 128);
  mk(f, &mp.wk, Wk, DM, 4096, 64); mk(f, &mp.wv, Wv, DM, 4096, 64); mk(f, &mp.wq, Wq, DM, 4096, 64);
  mk(f, &mp.w1, w1, DM, FF, 64); mk(f, &mp.w2, w2, FF, DM, 64); mk(f, &mp.wo, Wo, 4096, DM, 64);
  cudaFuncSetAttribute(main_kernel, cudaFuncAttributeMaxDynamicSharedMemorySize, SMEM_BYTES);
  prologue_kernel<<<256, 256, 0, cudaStreamPerThread>>>(x, mem0);
  main_kernel<<<NCTA, 384, SMEM_BYTES, cudaStreamPerThread>>>(mp, x, Wq, Wk, Wv, Wo, b1, b2, (bf16*)d_out);
}
```

```cpp
#include <cuda_runtime.h>
#include <cuda_bf16.h>
#include <cuda.h>
#include <stdint.h>

typedef __nv_bfloat16 bf16;
constexpr int SEQ = 2048, DM = 512, FF = 1792, QW = 12288, NSTEP = 64;
constexpr int NREC = 64, NBULK = 68, NCTA = 132;
constexpr int SPIN_LIMIT = 1 << 22;
#define THR 2
#define PDELAY 500

__device__ bf16 g_xn[SEQ * DM];
__device__ bf16 g_y[SEQ * DM];
__device__ bf16 g_qkv[(size_t)SEQ * QW];
__device__ bf16 g_hid[SEQ * FF];
__device__ bf16 g_o[(size_t)SEQ * 4096];
__device__ float g_z[SEQ * DM];
__device__ float g_s[SEQ * DM];
__device__ float4 g_acc[NSTEP][2][768];
__device__ bf16 g_km[NSTEP * 32 * 8 * 128];
__device__ bf16 g_vmT[NSTEP * 32 * 128 * 8];
struct Flags { int tile[16][48]; int hid[16]; int z[16][2]; int o[16][8]; int s[16][2]; int prog[16][32]; int next; };
__device__ Flags g_fl;

#define TR(i)
#define TB(i)
struct Maps { CUtensorMap xn, y, hid, o, qkv, wk, wv, wq, w1, w2, wo; };

extern __shared__ __align__(1024) uint8_t smem_raw[];
__device__ __forceinline__ uint4 ldc(uint32_t off) { return *(const uint4*)(smem_raw + off); }
__device__ __forceinline__ uint32_t smem_u32(const void* p) { return (uint32_t)__cvta_generic_to_shared(p); }
__device__ __forceinline__ int otid() { int t; asm volatile("mov.u32 %0, %%tid.x;" : "=r"(t)); return t; }
__device__ __forceinline__ uint32_t mapa(uint32_t a, uint32_t r) { uint32_t o; asm volatile("mapa.shared::cluster.u32 %0, %1, %2;" : "=r"(o) : "r"(a), "r"(r)); return o; }
__device__ __forceinline__ void st_async_v4(uint32_t addr, float a, float b, float c, float d, uint32_t mbar) {
  asm volatile("st.async.weak.shared::cluster.mbarrier::complete_tx::bytes.v4.b32 [%0], {%1,%2,%3,%4}, [%5];" ::"r"(addr), "r"(__float_as_uint(a)), "r"(__float_as_uint(b)), "r"(__float_as_uint(c)), "r"(__float_as_uint(d)), "r"(mbar) : "memory"); }
__device__ __forceinline__ void mbar_init(uint32_t m, int c) { asm volatile("mbarrier.init.shared::cta.b64 [%0], %1;" ::"r"(m), "r"(c) : "memory"); }
__device__ __forceinline__ void mbar_expect(uint32_t m, int bytes) { asm volatile("mbarrier.arrive.expect_tx.shared::cta.b64 _, [%0], %1;" ::"r"(m), "r"(bytes) : "memory"); }
__device__ __forceinline__ void mbar_arrive(uint32_t m) { asm volatile("mbarrier.arrive.shared::cta.b64 _, [%0];" ::"r"(m) : "memory"); }
__device__ __forceinline__ void mbar_wait(uint32_t m, uint32_t parity) {
  uint32_t ok; int it = 0;
  do { asm volatile("{.reg .pred p; mbarrier.try_wait.parity.shared::cta.b64 p, [%1], %2; selp.u32 %0,1,0,p;}" : "=r"(ok) : "r"(m), "r"(parity) : "memory"); } while (!ok && ++it < SPIN_LIMIT); }
__device__ __forceinline__ void mbar_spin(uint32_t m, uint32_t parity) {
  uint32_t ok; int it = 0;
  do { asm volatile("{.reg .pred p; mbarrier.test_wait.parity.shared::cta.b64 p, [%1], %2; selp.u32 %0,1,0,p;}" : "=r"(ok) : "r"(m), "r"(parity) : "memory"); } while (!ok && ++it < SPIN_LIMIT); }
__device__ __forceinline__ void bar_sync(int id, int n) { asm volatile("bar.sync %0, %1;" ::"r"(id), "r"(n) : "memory"); }
__device__ __forceinline__ void bar_arrive(int id, int n) { asm volatile("bar.arrive %0, %1;" ::"r"(id), "r"(n) : "memory"); }
__device__ __forceinline__ int ld_acq(const int* p) { int v; asm volatile("ld.acquire.gpu.global.s32 %0, [%1];" : "=r"(v) : "l"(p) : "memory"); return v; }
__device__ __forceinline__ void wait_flag(const int* p, int target) { int it = 0; while (ld_acq(p) < target && ++it < SPIN_LIMIT) { __nanosleep(40); } }
__device__ __forceinline__ void fence_async() { asm volatile("fence.proxy.async.global;" ::: "memory"); }
__device__ __forceinline__ uint4 lds128(uint32_t a) { uint4 v; asm volatile("ld.shared.v4.u32 {%0,%1,%2,%3}, [%4];" : "=r"(v.x), "=r"(v.y), "=r"(v.z), "=r"(v.w) : "r"(a) : "memory"); return v; }
__device__ __forceinline__ void sts128(uint32_t a, uint4 v) { asm volatile("st.shared.v4.u32 [%0], {%1,%2,%3,%4};" ::"r"(a), "r"(v.x), "r"(v.y), "r"(v.z), "r"(v.w) : "memory"); }
__device__ __forceinline__ void sts32(uint32_t a, uint32_t v) { asm volatile("st.shared.u32 [%0], %1;" ::"r"(a), "r"(v) : "memory"); }
__device__ __forceinline__ void sts16(uint32_t a, float f) { unsigned short h = __bfloat16_as_ushort(__float2bfloat16(f)); asm volatile("st.shared.u16 [%0], %1;" ::"r"(a), "h"(h) : "memory"); }
__device__ __forceinline__ void ldsm4(uint32_t* r, uint32_t a) { asm volatile("ldmatrix.sync.aligned.m8n8.x4.shared.b16 {%0,%1,%2,%3}, [%4];" : "=r"(r[0]), "=r"(r[1]), "=r"(r[2]), "=r"(r[3]) : "r"(a) : "memory"); }
__device__ __forceinline__ void ldsm4t(uint32_t* r, uint32_t a) { asm volatile("ldmatrix.sync.aligned.m8n8.x4.trans.shared.b16 {%0,%1,%2,%3}, [%4];" : "=r"(r[0]), "=r"(r[1]), "=r"(r[2]), "=r"(r[3]) : "r"(a) : "memory"); }
__device__ __forceinline__ void mma16(float* c, uint32_t a0, uint32_t a1, uint32_t a2, uint32_t a3, uint32_t b0, uint32_t b1) {
  asm("mma.sync.aligned.m16n8k16.row.col.f32.bf16.bf16.f32 {%0,%1,%2,%3}, {%4,%5,%6,%7}, {%8,%9}, {%0,%1,%2,%3};" : "+f"(c[0]), "+f"(c[1]), "+f"(c[2]), "+f"(c[3]) : "r"(a0), "r"(a1), "r"(a2), "r"(a3), "r"(b0), "r"(b1)); }
__device__ __forceinline__ void mma8(float* c, uint32_t a0, uint32_t a1, uint32_t b0) {
  asm("mma.sync.aligned.m16n8k8.row.col.f32.bf16.bf16.f32 {%0,%1,%2,%3}, {%4,%5}, {%6}, {%0,%1,%2,%3};" : "+f"(c[0]), "+f"(c[1]), "+f"(c[2]), "+f"(c[3]) : "r"(a0), "r"(a1), "r"(b0)); }
__device__ __forceinline__ uint32_t pack2(float a, float b) { __nv_bfloat162 h = __floats2bfloat162_rn(a, b); return *(uint32_t*)&h; }
__device__ __forceinline__ float rbf(float x) { uint32_t r; asm("cvt.rn.bf16x2.f32 %0, %1, %2;" : "=r"(r) : "f"(x), "f"(0.f)); return __uint_as_float(r); }
__device__ __forceinline__ void cp16(uint32_t d, const void* s) { asm volatile("cp.async.cg.shared.global [%0], [%1], 16;" ::"r"(d), "l"(s) : "memory"); }
__device__ __forceinline__ void tma2d(uint32_t dst, const CUtensorMap* m, int c0, int c1, uint32_t mbar) {
  asm volatile("cp.async.bulk.tensor.2d.shared::cluster.global.mbarrier::complete_tx::bytes [%0], [%1, {%2,%3}], [%4];" ::"r"(dst), "l"(m), "r"(c0), "r"(c1), "r"(mbar) : "memory"); }
__device__ __forceinline__ uint64_t mkdesc(uint32_t addr, uint32_t lbo, uint32_t sbo) {
  return (uint64_t)((addr & 0x3FFFF) >> 4) | ((uint64_t)(lbo >> 4) << 16) | ((uint64_t)(sbo >> 4) << 32) | (1ull << 62); }

#define R8(i) "+f"(d[i]), "+f"(d[i+1]), "+f"(d[i+2]), "+f"(d[i+3]), "+f"(d[i+4]), "+f"(d[i+5]), "+f"(d[i+6]), "+f"(d[i+7])
__device__ __forceinline__ void wgmma256(float* d, uint64_t da, uint64_t db, int acc) {
  asm volatile("{.reg .pred p; setp.ne.b32 p, %130, 0;\n"
    "wgmma.mma_async.sync.aligned.m64n256k16.f32.bf16.bf16 {"
    "%0,%1,%2,%3,%4,%5,%6,%7,%8,%9,%10,%11,%12,%13,%14,%15,%16,%17,%18,%19,%20,%21,%22,%23,%24,%25,%26,%27,%28,%29,%30,%31,"
    "%32,%33,%34,%35,%36,%37,%38,%39,%40,%41,%42,%43,%44,%45,%46,%47,%48,%49,%50,%51,%52,%53,%54,%55,%56,%57,%58,%59,%60,%61,%62,%63,"
    "%64,%65,%66,%67,%68,%69,%70,%71,%72,%73,%74,%75,%76,%77,%78,%79,%80,%81,%82,%83,%84,%85,%86,%87,%88,%89,%90,%91,%92,%93,%94,%95,"
    "%96,%97,%98,%99,%100,%101,%102,%103,%104,%105,%106,%107,%108,%109,%110,%111,%112,%113,%114,%115,%116,%117,%118,%119,%120,%121,%122,%123,%124,%125,%126,%127"
    "}, %128, %129, p, 1, 1, 0, 1;}"
    : R8(0), R8(8), R8(16), R8(24), R8(32), R8(40), R8(48), R8(56), R8(64), R8(72), R8(80), R8(88), R8(96), R8(104), R8(112), R8(120)
    : "l"(da), "l"(db), "r"(acc)); }

__global__ void __launch_bounds__(256) prologue_kernel(const bf16* __restrict__ x, const bf16* __restrict__ mem0) {
  int tid = threadIdx.x, lane = tid & 31, warp = tid >> 5;
  int row = blockIdx.x * 8 + warp;
  {
    const uint4* src = (const uint4*)(x + (size_t)row * DM);
    uint4 u[2] = { src[lane], src[lane + 32] };
    float v[16];
    #pragma unroll
    for (int i = 0; i < 2; i++) { const __nv_bfloat162* h = (const __nv_bfloat162*)&u[i];
      #pragma unroll
      for (int k = 0; k < 4; k++) { float2 f = __bfloat1622float2(h[k]); v[i * 8 + 2 * k] = f.x; v[i * 8 + 2 * k + 1] = f.y; } }
    #pragma unroll
    for (int pass = 0; pass < 2; pass++) {
      float s = 0;
      #pragma unroll
      for (int i = 0; i < 16; i++) s += v[i];
      #pragma unroll
      for (int o = 16; o; o >>= 1) s += __shfl_xor_sync(~0u, s, o);
      float mf = s * (1.f / DM);
      float q = 0;
      #pragma unroll
      for (int i = 0; i < 16; i++) { float dd = v[i] - mf; q += dd * dd; }
      #pragma unroll
      for (int o = 16; o; o >>= 1) q += __shfl_xor_sync(~0u, q, o);
      float m = rbf(mf), var = rbf(q * (1.f / DM));
      float den = rbf(sqrtf(rbf(var + 1e-5f)));
      #pragma unroll
      for (int i = 0; i < 16; i++) v[i] = rbf(rbf(v[i] - m) / den);
      uint4 o4[2];
      #pragma unroll
      for (int i = 0; i < 2; i++) { o4[i].x = pack2(v[i*8], v[i*8+1]); o4[i].y = pack2(v[i*8+2], v[i*8+3]); o4[i].z = pack2(v[i*8+4], v[i*8+5]); o4[i].w = pack2(v[i*8+6], v[i*8+7]); }
      uint4* dst = (uint4*)((pass ? g_y : g_xn) + (size_t)row * DM);
      dst[lane] = o4[0]; dst[lane + 32] = o4[1];
    }
  }
  int gt = blockIdx.x * 256 + tid;
  float4 z4 = make_float4(0, 0, 0, 0);
  #pragma unroll
  for (int i = 0; i < 4; i++) { ((float4*)g_z)[gt + i * 65536] = z4; ((float4*)g_s)[gt + i * 65536] = z4; }
  for (int i = gt; i < NSTEP * 1536; i += 65536) {
    float4 val = z4;
    if (i < 1536) {
      int j = i / 768, c = i % 768, ci = c >> 8, w = (c & 255) >> 5, l = c & 31, g = l >> 2, t = l & 3;
      float e3[3];
      #pragma unroll
      for (int k = 0; k < 3; k++) { int e = ci * 3 + k; int mt = e >> 2, cc = e & 3;
        e3[k] = e < 8 ? __bfloat162float(mem0[(2 * t + (cc & 1)) * DM + 256 * j + 32 * w + 16 * mt + g + 8 * (cc >> 1)]) : 0.f; }
      val = make_float4(e3[0], e3[1], e3[2], 32.f);
    }
    (&g_acc[0][0][0])[i] = val;
  }
  if (gt < (int)(sizeof(Flags) / 4)) ((int*)&g_fl)[gt] = 0;
}

constexpr int R_WR = 0, R_KT = 65536, KT_SZ = 40 * 256, R_VT = R_KT + 2 * KT_SZ, VT_SZ = 40 * 272,
              R_MEM = R_VT + 2 * VT_SZ, R_Q = R_MEM + 32 * 160, R_O = R_Q + 8 * 256, R_S = R_O + 8 * 256,
              R_SM = R_S + 8 * 40 * 4, R_RQK = R_SM + 1024, R_RV = R_RQK + 8192, R_WQ = R_RV + 4096, R_BAR = 232448 - 64, R_END = R_BAR + 64;
#define KD 150
#define VP 4
__device__ __forceinline__ void wgmma8(float* d, uint64_t da, uint64_t db, int acc) {
  asm volatile("{.reg .pred p; setp.ne.b32 p, %6, 0;\n wgmma.mma_async.sync.aligned.m64n8k16.f32.bf16.bf16 {%0,%1,%2,%3}, %4, %5, p, 1, 1, 0, 0;}"
    : "+f"(d[0]), "+f"(d[1]), "+f"(d[2]), "+f"(d[3]) : "l"(da), "l"(db), "r"(acc)); }
__device__ __forceinline__ void stsm4(uint32_t a, uint32_t r0, uint32_t r1, uint32_t r2, uint32_t r3) { asm volatile("stmatrix.sync.aligned.m8n8.x4.shared.b16 [%0], {%1,%2,%3,%4};" ::"r"(a), "r"(r0), "r"(r1), "r"(r2), "r"(r3) : "memory"); }
__device__ __forceinline__ uint32_t swz(uint32_t r) { return ((r & 1) << 2) | ((r >> 1) & 3); }
__device__ __forceinline__ void stsm4t(uint32_t a, uint32_t r0, uint32_t r1, uint32_t r2, uint32_t r3) { asm volatile("stmatrix.sync.aligned.m8n8.x4.trans.shared.b16 [%0], {%1,%2,%3,%4};" ::"r"(a), "r"(r0), "r"(r1), "r"(r2), "r"(r3) : "memory"); }
__device__ __forceinline__ void stsm2(uint32_t a, uint32_t r0, uint32_t r1) { asm volatile("stmatrix.sync.aligned.m8n8.x2.shared.b16 [%0], {%1,%2};" ::"r"(a), "r"(r0), "r"(r1) : "memory"); }
__device__ __forceinline__ float ex2(float x) { float r; asm("ex2.approx.ftz.f32 %0, %1;" : "=f"(r) : "f"(x)); return r; }
#define REDV4(p, a, b, c) asm volatile("red.relaxed.gpu.global.add.v4.f32 [%0], {%1,%2,%3,%4};" ::"l"(p), "f"(a), "f"(b), "f"(c), "f"(1.0f) : "memory")
constexpr int SMEM_BYTES = 232448;
static_assert(R_END <= SMEM_BYTES, "smem");

__device__ __forceinline__ void recurrence(uint32_t sb, const bf16* __restrict__ Wq, const bf16* __restrict__ Wk, const bf16* __restrict__ Wv, const bf16* __restrict__ Wo) {
  const int tid = threadIdx.x, warp = tid >> 5, lane = tid & 31, g = lane >> 2, t = lane & 3;
  const int h = blockIdx.x >> 1, j = blockIdx.x & 1;
  const uint32_t peer = j ^ 1;
  const uint32_t mQ = sb + R_BAR, mV = sb + R_BAR + 8, mK = sb + R_BAR + 16;
  uint32_t A[2][16][4];
  const uint32_t stA = sb + 65536, stB = stA + 69632;
  const int lm = lane >> 3, lr = lane & 7;
  for (int i = tid; i < 256 * 16; i += 384) { int r = i >> 4, c = i & 15; size_t o = ((size_t)(256 * j + r)) * 4096 + h * 128 + c * 8;
    cp16(stA + r * 272 + c * 16, Wv + o); cp16(stB + r * 272 + c * 16, Wq + o); }
  asm volatile("cp.async.wait_all;" ::: "memory"); __syncthreads();
  if (warp < 4) {
    #pragma unroll
    for (int mt = 0; mt < 2; mt++)
      #pragma unroll
      for (int ks = 0; ks < 16; ks++) {
        int k = 32 * (ks >> 1) + 8 * (lr >> 1) + (lr & 1) + 4 * (ks & 1) + 2 * (lm >> 1);
        ldsm4t(A[mt][ks], stB + k * 272 + (32 * warp + 16 * mt + 8 * (lm & 1)) * 2);
      }
  } else {
    #pragma unroll 4
    for (int i = 0; i < 16; i++) { int idx = (warp - 4) * 16 + i, c = idx >> 2, dg = 4 * (idx & 3) + lm; uint32_t r[4];
      ldsm4t(r, stA + (8 * c + lr) * 272 + dg * 16);
      stsm4(sb + R_WR + (dg >> 3) * 32768 + c * 1024 + (dg & 7) * 128 + lr * 16, r[0], r[1], r[2], r[3]); }
    asm volatile("fence.proxy.async.shared::cta;" ::: "memory");
  }
  __syncthreads();
  for (int i = tid; i < 256 * 16; i += 384) { int r = i >> 4, c = i & 15; cp16(stA + r * 272 + c * 16, Wk + ((size_t)(256 * j + r)) * 4096 + h * 128 + c * 8);
    r = i >> 5; c = i & 31; cp16(stB + r * 528 + c * 16, Wo + ((size_t)(h * 128 + r)) * DM + 256 * j + c * 8); }
  asm volatile("cp.async.wait_all;" ::: "memory"); __syncthreads();
  if (warp >= 4) {
    #pragma unroll
    for (int mt = 0; mt < 2; mt++)
      #pragma unroll
      for (int ks = 0; ks < 16; ks++) {
        int k = 32 * (ks >> 1) + 8 * (lr >> 1) + (lr & 1) + 4 * (ks & 1) + 2 * (lm >> 1);
        ldsm4t(A[mt][ks], warp < 8 ? stA + k * 272 + (32 * (warp & 3) + 16 * mt + 8 * (lm & 1)) * 2
                                   : stB + (k & 127) * 528 + (64 * (warp & 3) + 32 * mt + 16 * (ks >> 3) + 8 * (lm & 1)) * 2);
      }
  }
  __syncthreads();
  if (warp < 4) {
    #pragma unroll
    for (int i = 0; i < 16; i++) sts128(sb + R_WQ + ((warp * 16 + i) * 32 + lane) * 16, make_uint4(A[1][i][0], A[1][i][1], A[1][i][2], A[1][i][3]));
  }
  __syncthreads();
  if (warp >= 8) {
    #pragma unroll 1
    for (int s = 0; s < NSTEP; s++) {
      const int tid = otid(), lane = tid & 31, wv = (tid >> 5) - 8, g = lane >> 2, t = lane & 3;
      if (tid == 256) mbar_expect(mV, 4096);
      const uint32_t fo = (t ^ swz(g)) << 4;
      const uint64_t da = (uint64_t)(((sb + R_WR) & 0x3FFFF) >> 4) | (64ull << 16) | (8ull << 32), db = (uint64_t)(((sb + R_MEM) & 0x3FFFF) >> 4) | (10ull << 16) | (8ull << 32);
      TR(1);
      bar_sync(4, 384);
      TR(2);
      float c[4][4];
      asm volatile("wgmma.fence.sync.aligned;" ::: "memory");
      #pragma unroll
      for (int i = 0; i < 16; i++) { wgmma8(c[i & 1], da + i * 128, db + i * 20, i >= 2); wgmma8(c[2 + (i & 1)], da + 2048 + i * 128, db + i * 20, i >= 2); }
      asm volatile("wgmma.commit_group.sync.aligned;" ::: "memory");
      asm volatile("wgmma.wait_group.sync.aligned 0;" ::: "memory");
      #pragma unroll
      for (int i = 0; i < 4; i++) asm volatile("" : "+f"(c[i][0]), "+f"(c[i][1]), "+f"(c[i][2]), "+f"(c[i][3]) :: "memory");
      TR(3);
      #pragma unroll
      for (int i = 0; i < 4; i++) { c[0][i] += c[1][i]; c[1][i] = c[2][i] + c[3][i]; }
      const uint32_t rx = sb + R_RV + (wv * 64 + lane) * 16;
      { uint32_t ra = mapa(rx, peer), rm = mapa(mV, peer);
        st_async_v4(ra, c[0][0], c[0][1], c[0][2], c[0][3], rm);
        st_async_v4(ra + 512, c[1][0], c[1][1], c[1][2], c[1][3], rm); }
      TR(4);
      const bool more = s < NSTEP - 1;
      mbar_wait(mV, s & 1);
      TR(5);
      { uint4 r0 = lds128(rx), r1 = lds128(rx + 512);
        stsm4t(sb + R_VT + (s & 1) * VT_SZ + (32 + (lane & 7)) * 272 + (8 * (lane >> 4) + 2 * wv + ((lane >> 3) & 1)) * 16,
          pack2(c[0][0] + __uint_as_float(r0.x), c[0][1] + __uint_as_float(r0.y)), pack2(c[0][2] + __uint_as_float(r0.z), c[0][3] + __uint_as_float(r0.w)),
          pack2(c[1][0] + __uint_as_float(r1.x), c[1][1] + __uint_as_float(r1.y)), pack2(c[1][2] + __uint_as_float(r1.z), c[1][3] + __uint_as_float(r1.w))); }
      if (!more) { bar_arrive(6, 384); break; }
      bar_arrive(3, 256);
      TR(8);
      bar_sync(7, 256);
      TR(9);
      #pragma unroll
      for (int i = 0; i < 4; i++) { c[i][0] = c[i][1] = c[i][2] = c[i][3] = 0.f; }
      #pragma unroll
      for (int p = 0; p < 4; p++) {
        uint4 b = ldc(R_O + g * 256 + (p >> 1) * 128 + (fo ^ ((p & 1) << 6)));
        #pragma unroll
        for (int mt = 0; mt < 4; mt++) { const uint32_t* a = A[mt >> 1][(mt & 1) * 8 + 2 * p]; mma16(c[mt], a[0], a[1], a[2], a[3], b.x, b.y); }
        #pragma unroll
        for (int mt = 0; mt < 4; mt++) { const uint32_t* a = A[mt >> 1][(mt & 1) * 8 + 2 * p + 1]; mma16(c[mt], a[0], a[1], a[2], a[3], b.z, b.w); }
      }
      TR(6);
      float4* dst = &g_acc[s + 1][j][wv * 64 + lane];
      REDV4(dst, c[0][0], c[0][1], c[0][2]); REDV4(dst + 256, c[0][3], c[1][0], c[1][1]); REDV4(dst + 512, c[1][2], c[1][3], 0.f);
      REDV4(dst + 32, c[2][0], c[2][1], c[2][2]); REDV4(dst + 288, c[2][3], c[3][0], c[3][1]); REDV4(dst + 544, c[3][2], c[3][3], 0.f);
      bar_arrive(8, 384);
      TR(7);
    }
    return;
  }
  const float scale = 0.08838834764831845f, l2e = 1.4426950408889634f;
  auto prefetch = [&](int s) {
    const int vt = otid() - 160;
    if ((s & 3) == 0) { wait_flag(&g_fl.tile[s >> 2][h >> 1], 1); wait_flag(&g_fl.tile[s >> 2][16 + (h >> 1)], 1); }
    const int r = vt >> 4, c = vt & 15;
    const bf16* src = g_qkv + (size_t)(32 * s + r) * QW + h * 128 + c * 8;
    uint32_t kb = sb + R_KT + (s & 1) * KT_SZ + r * 256, vb = sb + R_VT + (s & 1) * VT_SZ + r * 272 + c * 16;
    #pragma unroll
    for (int i = 0; i < 8; i++) { cp16(kb + i * 1024 + ((c ^ swz(r + 4 * i)) << 4), src + (size_t)i * 4 * QW); cp16(vb + i * 1088, src + (size_t)i * 4 * QW + 4096); }
  };
  auto publish = [&](int s) {
    const int l = otid() & 31;
    #pragma unroll
    for (int i = 0; i < 4; i++) {
      const int vt = l + 32 * i;
      if (j == 0) { const int r = vt >> 4, c = vt & 15; uint4 v = lds128(sb + R_KT + (s & 1) * KT_SZ + (32 + r) * 256 + ((c ^ swz(r)) << 4));
        __stcg((uint4*)(g_km + ((size_t)(s * 32 + h)) * 1024) + vt, v); }
      else { uint32_t vb = sb + R_VT + (s & 1) * VT_SZ + 32 * 272 + vt * 2; uint32_t e[8];
        #pragma unroll
        for (int k = 0; k < 8; k++) { unsigned short x; asm volatile("ld.shared.u16 %0, [%1];" : "=h"(x) : "r"(vb + k * 272) : "memory"); e[k] = x; }
        __stcg((uint4*)(g_vmT + ((size_t)(s * 32 + h)) * 1024) + vt, make_uint4(e[0] | (e[1] << 16), e[2] | (e[3] << 16), e[4] | (e[5] << 16), e[6] | (e[7] << 16))); }
    }
  };
  auto flag = [&](int s) { __syncwarp(); if ((otid() & 31) == 0) { __threadfence(); atomicAdd(&g_fl.prog[s >> 2][h], 1); } __syncwarp(); };
  if (warp >= 4) {
  if (warp == 5 || warp == 6) prefetch(0);
  #pragma unroll 1
  for (int s = 0; s < NSTEP; s++) {
    TR(0); TR(1);
    const int tid = otid(), lane = tid & 31, warp = tid >> 5, g = lane >> 2, t = lane & 3;
    const uint32_t fo = (t ^ swz(g)) << 4;
    {
      if (tid == 0) mbar_expect(mQ, 4096);
      if (tid == 128) mbar_expect(mK, 4096);
      const float4* src = &g_acc[s][j][tid];
      uint4 v0, v1, v2; int it = 0; bool ok;
      do {
        asm volatile("ld.relaxed.gpu.global.v4.u32 {%0,%1,%2,%3}, [%4];" : "=r"(v0.x), "=r"(v0.y), "=r"(v0.z), "=r"(v0.w) : "l"(src) : "memory");
        asm volatile("ld.relaxed.gpu.global.v4.u32 {%0,%1,%2,%3}, [%4];" : "=r"(v1.x), "=r"(v1.y), "=r"(v1.z), "=r"(v1.w) : "l"(src + 256) : "memory");
        asm volatile("ld.relaxed.gpu.global.v4.u32 {%0,%1,%2,%3}, [%4];" : "=r"(v2.x), "=r"(v2.y), "=r"(v2.z), "=r"(v2.w) : "l"(src + 512) : "memory");
        ok = (v0.w == 0x42000000u) && (v1.w == 0x42000000u) && (v2.w == 0x42000000u);
      } while (!ok && ++it < SPIN_LIMIT);
      __syncwarp();
      stsm4t(sb + R_MEM + (lane & 7) * 16 + (4 * warp + (lane >> 3)) * 160,
        pack2(__uint_as_float(v0.x), __uint_as_float(v0.y)), pack2(__uint_as_float(v0.z), __uint_as_float(v1.x)),
        pack2(__uint_as_float(v1.y), __uint_as_float(v1.z)), pack2(__uint_as_float(v2.x), __uint_as_float(v2.y)));
      asm volatile("fence.proxy.async.shared::cta;" ::: "memory");
    }
    TR(2);
    asm volatile("cp.async.wait_all;" ::: "memory");
    bar_sync(1, 256);
    { long long t0 = clock64(); while (clock64() - t0 < KD); }
    if (VP < 0) bar_arrive(4, 384);
    TR(3);
    float c[4][4];
    #pragma unroll
    for (int i = 0; i < 4; i++) { c[i][0] = c[i][1] = c[i][2] = c[i][3] = 0.f; }
    #pragma unroll
    for (int p = 0; p < 8; p++) {
      uint4 b = ldc(R_MEM + g * 16 + t * 160 + p * 640);
      mma16(c[0], A[0][2*p][0], A[0][2*p][1], A[0][2*p][2], A[0][2*p][3], b.x, b.y);
      mma16(c[1], A[1][2*p][0], A[1][2*p][1], A[1][2*p][2], A[1][2*p][3], b.x, b.y);
      mma16(c[2], A[0][2*p+1][0], A[0][2*p+1][1], A[0][2*p+1][2], A[0][2*p+1][3], b.z, b.w);
      mma16(c[3], A[1][2*p+1][0], A[1][2*p+1][1], A[1][2*p+1][2], A[1][2*p+1][3], b.z, b.w);
      if (p == VP) asm volatile("bar.arrive 4, 384;");
    }
    #pragma unroll
    for (int i = 0; i < 4; i++) { c[0][i] += c[2][i]; c[1][i] += c[3][i]; }
    const uint32_t rx = sb + R_RQK + (warp * 64 + lane) * 16;
    { uint32_t ra = mapa(rx, peer), rm = mapa(mK, peer);
      st_async_v4(ra, c[0][0], c[0][1], c[0][2], c[0][3], rm);
      st_async_v4(ra + 512, c[1][0], c[1][1], c[1][2], c[1][3], rm); }
    if (VP > 7) bar_arrive(4, 384);
    TR(4);
    const uint32_t so = (lane & 7) * 256 + (((4 * (warp & 3) + (lane >> 3)) ^ swz(lane & 7)) << 4);
    mbar_wait(mK, s & 1);
    TR(5);
    uint32_t m0, m1, m2, m3;
    { uint4 r0 = lds128(rx), r1 = lds128(rx + 512);
      m0 = pack2(c[0][0] + __uint_as_float(r0.x), c[0][1] + __uint_as_float(r0.y)); m1 = pack2(c[0][2] + __uint_as_float(r0.z), c[0][3] + __uint_as_float(r0.w));
      m2 = pack2(c[1][0] + __uint_as_float(r1.x), c[1][1] + __uint_as_float(r1.y)); m3 = pack2(c[1][2] + __uint_as_float(r1.z), c[1][3] + __uint_as_float(r1.w)); }
    stsm4t(sb + R_KT + (s & 1) * KT_SZ + 32 * 256 + so, m0, m1, m2, m3);
    if (s == NSTEP - 1) { bar_sync(6, 384); if (warp == 7) { publish(s - 1); flag(s - 2); flag(s - 1); } if (warp == 6) { publish(s); flag(s); } break; }
    asm("movmatrix.sync.aligned.m8n8.trans.b16 %0, %0;" : "+r"(m0)); asm("movmatrix.sync.aligned.m8n8.trans.b16 %0, %0;" : "+r"(m1));
    asm("movmatrix.sync.aligned.m8n8.trans.b16 %0, %0;" : "+r"(m2)); asm("movmatrix.sync.aligned.m8n8.trans.b16 %0, %0;" : "+r"(m3));
    TR(8);
    bar_sync(9, 256);
    TR(9);
    { uint32_t qa[4]; ldsm4(qa, sb + R_Q + so);
      #pragma unroll
      for (int i = 0; i < 2; i++) { c[i][0] = c[i][1] = c[i][2] = c[i][3] = 0.f; }
      mma16(c[0], qa[0], 0, qa[1], 0, m0, m1); mma16(c[1], qa[2], 0, qa[3], 0, m2, m3);
      asm volatile("st.shared.v2.f32 [%0], {%1,%2};" ::"r"(sb + R_SM + (warp - 4) * 256 + lane * 8), "f"(c[0][0] + c[1][0]), "f"(c[0][1] + c[1][1]) : "memory"); }
    bar_arrive(2, 256);
    TR(10);
    if (warp == 7) { if (s > 1) flag(s - 2); if (s > 0) publish(s - 1); } else if (warp >= 5 && s < NSTEP - 2) prefetch(s + 1);
    TR(7);
    bar_sync(8, 384);
    { long long t0 = clock64(); while (clock64() - t0 < PDELAY); }
  }
  return;
  }
  #pragma unroll 1
  for (int s = 0; s < NSTEP; s++) {
    TR(0); TR(1);
    const int tid = otid(), lane = tid & 31, warp = tid >> 5, g = lane >> 2, t = lane & 3;
    const uint32_t fo = (t ^ swz(g)) << 4;
    {
      if (tid == 0) mbar_expect(mQ, 4096);
      if (tid == 128) mbar_expect(mK, 4096);
      const float4* src = &g_acc[s][j][tid];
      uint4 v0, v1, v2; int it = 0; bool ok;
      do {
        asm volatile("ld.relaxed.gpu.global.v4.u32 {%0,%1,%2,%3}, [%4];" : "=r"(v0.x), "=r"(v0.y), "=r"(v0.z), "=r"(v0.w) : "l"(src) : "memory");
        asm volatile("ld.relaxed.gpu.global.v4.u32 {%0,%1,%2,%3}, [%4];" : "=r"(v1.x), "=r"(v1.y), "=r"(v1.z), "=r"(v1.w) : "l"(src + 256) : "memory");
        asm volatile("ld.relaxed.gpu.global.v4.u32 {%0,%1,%2,%3}, [%4];" : "=r"(v2.x), "=r"(v2.y), "=r"(v2.z), "=r"(v2.w) : "l"(src + 512) : "memory");
        ok = (v0.w == 0x42000000u) && (v1.w == 0x42000000u) && (v2.w == 0x42000000u);
      } while (!ok && ++it < SPIN_LIMIT);
      __syncwarp();
      stsm4t(sb + R_MEM + (lane & 7) * 16 + (4 * warp + (lane >> 3)) * 160,
        pack2(__uint_as_float(v0.x), __uint_as_float(v0.y)), pack2(__uint_as_float(v0.z), __uint_as_float(v1.x)),
        pack2(__uint_as_float(v1.y), __uint_as_float(v1.z)), pack2(__uint_as_float(v2.x), __uint_as_float(v2.y)));
      asm volatile("fence.proxy.async.shared::cta;" ::: "memory");
    }
    TR(2);

    bar_sync(1, 256);
    bar_arrive(4, 384);
    TR(3);
    float c[4][4];
    #pragma unroll
    for (int i = 0; i < 4; i++) { c[i][0] = c[i][1] = c[i][2] = c[i][3] = 0.f; }
    #pragma unroll
    for (int p = 0; p < 8; p++) {
      uint4 b = ldc(R_MEM + g * 16 + t * 160 + p * 640);
      mma16(c[0], A[0][2*p][0], A[0][2*p][1], A[0][2*p][2], A[0][2*p][3], b.x, b.y);
      mma16(c[1], A[1][2*p][0], A[1][2*p][1], A[1][2*p][2], A[1][2*p][3], b.x, b.y);
      mma16(c[2], A[0][2*p+1][0], A[0][2*p+1][1], A[0][2*p+1][2], A[0][2*p+1][3], b.z, b.w);
      mma16(c[3], A[1][2*p+1][0], A[1][2*p+1][1], A[1][2*p+1][2], A[1][2*p+1][3], b.z, b.w);
    }
    #pragma unroll
    for (int i = 0; i < 4; i++) { c[0][i] += c[2][i]; c[1][i] += c[3][i]; }
    const uint32_t rx = sb + R_RQK + (warp * 64 + lane) * 16;
    { uint32_t ra = mapa(rx, peer), rm = mapa(mQ, peer);
      st_async_v4(ra, c[0][0], c[0][1], c[0][2], c[0][3], rm);
      st_async_v4(ra + 512, c[1][0], c[1][1], c[1][2], c[1][3], rm); }
    TR(4);
    const uint32_t so = (lane & 7) * 256 + (((4 * (warp & 3) + (lane >> 3)) ^ swz(lane & 7)) << 4);
    if (s == NSTEP - 1) { mbar_wait(mQ, s & 1); bar_arrive(6, 384); break; }
    uint4 kf[4]; uint32_t vf[4][4];
    const uint32_t vb = sb + R_VT + (s & 1) * VT_SZ + (lane & 15) * 272 + (32 * warp + 8 * (lane >> 4)) * 2;
    #pragma unroll
    for (int p = 0; p < 4; p++) kf[p] = lds128(sb + R_KT + (s & 1) * KT_SZ + warp * 2048 + g * 256 + (p >> 1) * 128 + (fo ^ ((p & 1) << 6)));
    #pragma unroll
    for (int i = 0; i < 4; i++) ldsm4t(vf[i], vb + (i >> 1) * 16 * 272 + (i & 1) * 32);
    mbar_wait(mQ, s & 1);
    TR(5);
    uint32_t m0, m1, m2, m3;
    { uint4 r0 = lds128(rx), r1 = lds128(rx + 512);
      m0 = pack2(c[0][0] + __uint_as_float(r0.x), c[0][1] + __uint_as_float(r0.y)); m1 = pack2(c[0][2] + __uint_as_float(r0.z), c[0][3] + __uint_as_float(r0.w));
      m2 = pack2(c[1][0] + __uint_as_float(r1.x), c[1][1] + __uint_as_float(r1.y)); m3 = pack2(c[1][2] + __uint_as_float(r1.z), c[1][3] + __uint_as_float(r1.w)); }
    stsm4t(sb + R_Q + so, m0, m1, m2, m3);
    TR(8);
    bar_arrive(9, 256); bar_sync(5, 128);
    TR(9);
    {
      uint4 qa[4];
      #pragma unroll
      for (int p = 0; p < 4; p++) qa[p] = lds128(sb + R_Q + g * 256 + (p >> 1) * 128 + (fo ^ ((p & 1) << 6)));
      #pragma unroll
      for (int i = 0; i < 4; i++) { c[i][0] = c[i][1] = c[i][2] = c[i][3] = 0.f; }
      #pragma unroll
      for (int p = 0; p < 4; p++) { mma16(c[(p & 1) * 2], qa[p].x, 0, qa[p].y, 0, kf[p].x, kf[p].y); mma16(c[(p & 1) * 2 + 1], qa[p].z, 0, qa[p].w, 0, kf[p].z, kf[p].w); }
      float a = rbf(rbf((c[0][0] + c[1][0]) + (c[2][0] + c[3][0])) * scale) * l2e, b = rbf(rbf((c[0][1] + c[1][1]) + (c[2][1] + c[3][1])) * scale) * l2e;
      asm volatile("st.shared.v2.f32 [%0], {%1,%2};" ::"r"(sb + R_S + g * 160 + (8 * warp + 2 * t) * 4), "f"(a), "f"(b) : "memory");
    }
    TR(10);
    bar_sync(10, 128);
    float sv[8], pm[8];
    #pragma unroll
    for (int i = 0; i < 4; i++) asm volatile("ld.shared.v2.f32 {%0,%1}, [%2];" : "=f"(sv[2*i]), "=f"(sv[2*i+1]) : "r"(sb + R_S + g * 160 + (8 * i + 2 * t) * 4) : "memory");
    float mx = fmaxf(fmaxf(fmaxf(sv[0], sv[1]), fmaxf(sv[2], sv[3])), fmaxf(fmaxf(sv[4], sv[5]), fmaxf(sv[6], sv[7])));
    mx = fmaxf(mx, __shfl_xor_sync(~0u, mx, 1)); mx = fmaxf(mx, __shfl_xor_sync(~0u, mx, 2));
    uint32_t P[5];
    #pragma unroll
    for (int i = 0; i < 4; i++) P[i] = pack2(ex2(sv[2*i] - mx), ex2(sv[2*i+1] - mx));
    #pragma unroll
    for (int i = 0; i < 4; i++) { c[i][0] = c[i][1] = c[i][2] = c[i][3] = 0.f; }
    #pragma unroll
    for (int kk = 0; kk < 2; kk++) {
      mma16(c[0], P[2*kk], 0, P[2*kk+1], 0, vf[2*kk][0], vf[2*kk][1]); mma16(c[1], P[2*kk], 0, P[2*kk+1], 0, vf[2*kk][2], vf[2*kk][3]);
      mma16(c[2], P[2*kk], 0, P[2*kk+1], 0, vf[2*kk+1][0], vf[2*kk+1][1]); mma16(c[3], P[2*kk], 0, P[2*kk+1], 0, vf[2*kk+1][2], vf[2*kk+1][3]);
    }
    float sum = 0.f;
    #pragma unroll
    for (int i = 0; i < 4; i++) sum += __uint_as_float(P[i] << 16) + __uint_as_float(P[i] & 0xffff0000u);
    TR(11);
    bar_sync(2, 256);
    #pragma unroll
    for (int i = 0; i < 4; i++) asm volatile("ld.shared.v2.f32 {%0,%1}, [%2];" : "=f"(pm[2*i]), "=f"(pm[2*i+1]) : "r"(sb + R_SM + i * 256 + lane * 8) : "memory");
    const float s8 = rbf(rbf((pm[0] + pm[2]) + (pm[4] + pm[6])) * scale) * l2e, s9 = rbf(rbf((pm[1] + pm[3]) + (pm[5] + pm[7])) * scale) * l2e;
    float mg = fmaxf(mx, fmaxf(s8, s9));
    mg = fmaxf(mg, __shfl_xor_sync(~0u, mg, 1)); mg = fmaxf(mg, __shfl_xor_sync(~0u, mg, 2));
    const float fs = ex2(mx - mg);
    P[4] = pack2(ex2(s8 - mg), ex2(s9 - mg));
    #pragma unroll
    for (int i = 0; i < 4; i++) { c[i][0] *= fs; c[i][1] *= fs; }
    sum = fmaf(sum, fs, __uint_as_float(P[4] << 16) + __uint_as_float(P[4] & 0xffff0000u));
    sum += __shfl_xor_sync(~0u, sum, 1); sum += __shfl_xor_sync(~0u, sum, 2);
    float inv; asm("rcp.approx.ftz.f32 %0, %1;" : "=f"(inv) : "f"(sum));
    TR(6);
    bar_sync(3, 256);
    { uint32_t r[4]; ldsm4t(r, sb + R_VT + (s & 1) * VT_SZ + (32 + (lane & 7)) * 272 + (4 * warp + (lane >> 3)) * 16);
      #pragma unroll
      for (int i = 0; i < 4; i++) mma8(c[i], P[4], 0, r[i]); }
    asm volatile("stmatrix.sync.aligned.m8n8.x4.shared.b16 [%0], {%1,%2,%3,%4};" ::"r"(sb + R_O + so),
      "r"(pack2(c[0][0] * inv, c[0][1] * inv)), "r"(pack2(c[1][0] * inv, c[1][1] * inv)), "r"(pack2(c[2][0] * inv, c[2][1] * inv)), "r"(pack2(c[3][0] * inv, c[3][1] * inv)) : "memory");
    bar_arrive(7, 256);
    TR(7);
    bar_sync(8, 384);
    long long t0 = clock64();
    #pragma unroll
    for (int i = 0; i < 16; i++) { uint4 v = lds128(sb + R_WQ + ((warp * 16 + i) * 32 + lane) * 16); A[1][i][0] = v.x; A[1][i][1] = v.y; A[1][i][2] = v.z; A[1][i][3] = v.w; }
    while (clock64() - t0 < PDELAY);
  }
}

constexpr int I_M1 = 512, I_Q = 624, I_M2 = 880, I_AT = 1008, I_G = I_AT + 32, GSZ = 56, I_END = I_G + 15 * GSZ + 24;
constexpr int B_STG = 4 * 49152, B_BAR = B_STG + 8 * 2304;
struct Item { int type, rb, nt, ks; };
__device__ __forceinline__ Item decode(int it) {
  Item r; r.ks = 0;
  if (it < I_M1) { r.type = 0; r.rb = it >> 5; r.nt = it & 31; }
  else if (it < I_Q) { int i = it - I_M1; r.type = 1; r.rb = i / 7; r.nt = i % 7; }
  else if (it < I_M2) { int i = it - I_Q; r.type = 0; r.rb = i >> 4; r.nt = 32 + (i & 15); }
  else if (it < I_AT) { int i = it - I_M2; r.type = 2; r.rb = i >> 3; r.nt = (i >> 2) & 1; r.ks = i & 3; }
  else if (it < I_G) { r.type = 3; r.rb = 0; r.nt = it - I_AT; }
  else {
    int i = it - I_G, gi = i / GSZ, q = i % GSZ; if (gi == 15) q += 32;
    if (q < 32) { r.type = 3; r.rb = gi + 1; r.nt = q; }
    else if (q < 48) { r.type = 4; r.rb = gi; r.nt = (q - 32) >> 3; r.ks = (q - 32) & 7; }
    else { r.type = 5; r.rb = gi; r.nt = q - 48; } }
  return r;
}
__device__ __forceinline__ float gelu_t(float x) { float u = 0.7978845608028654f * (x + 0.044715f * x * x * x); float th; asm("tanh.approx.f32 %0, %1;" : "=f"(th) : "f"(u)); float hx = 0.5f * x; return fmaf(hx, th, hx); }

__device__ __forceinline__ void bulk(uint32_t sb, const Maps& mp, const bf16* __restrict__ x, const bf16* __restrict__ b1, const bf16* __restrict__ b2, bf16* __restrict__ out) {
  const int tid = threadIdx.x, warp = tid >> 5, lane = tid & 31, g = lane >> 2, t = lane & 3;
  const int bid = blockIdx.x - NREC;
  const uint32_t full = sb + B_BAR, empty = sb + B_BAR + 32, ifull = sb + B_BAR + 64, iempty = sb + B_BAR + 80;
  volatile int* ring = (volatile int*)(__cvta_shared_to_generic(sb + B_BAR + 96));
  if (warp >= 8) {
    asm volatile("setmaxnreg.dec.sync.aligned.u32 40;");
    if (tid == 256) {
      uint32_t st = 0, ph = 0;
      for (int n = 0;; n++) {
        int it = n == 0 ? bid : NBULK + atomicAdd(&g_fl.next, 1);
        Item I = decode(it);
        if (it < I_END) {
          if (I.type == 5) { wait_flag(&g_fl.s[I.rb][0], 16); wait_flag(&g_fl.z[I.rb][0], 8); }
          else if (I.type == 3) { wait_flag(&g_fl.prog[I.rb][I.nt], 8); wait_flag(&g_fl.tile[I.rb][I.nt >> 1], 1); wait_flag(&g_fl.tile[I.rb][16 + (I.nt >> 1)], 1); wait_flag(&g_fl.tile[I.rb][32 + (I.nt >> 1)], 1); fence_async(); }
          else if (I.type == 2) { wait_flag(&g_fl.hid[I.rb], 7); fence_async(); }
          else if (I.type == 4) { wait_flag(&g_fl.o[I.rb][I.ks], 4); fence_async(); }
        }
        mbar_wait(iempty + (n & 1) * 8, ((n >> 1) & 1) ^ 1);
        ring[n & 1] = it; mbar_arrive(ifull + (n & 1) * 8);
        if (it >= I_END) break;
        if (I.type == 5) continue;
        if (I.type == 3) {
          for (int m = 0; m < 3; m++) {
            mbar_wait(empty + st * 8, ph ^ 1);
            mbar_expect(full + st * 8, 32768);
            int col = (m == 0 ? 8192 : (m == 1 ? 0 : 4096)) + I.nt * 128;
            tma2d(sb + st * 49152, &mp.qkv, col, I.rb * 128, full + st * 8);
            tma2d(sb + st * 49152 + 16384, &mp.qkv, col + 64, I.rb * 128, full + st * 8);
            if (++st == 4) { st = 0; ph ^= 1; }
          }
          continue;
        }
        const CUtensorMap *ma, *mb; int nkb = 8, kb0 = 0, n0;
        if (I.type == 0) { ma = &mp.xn; mb = I.nt < 16 ? &mp.wk : (I.nt < 32 ? &mp.wv : &mp.wq); n0 = (I.nt & 15) * 256; }
        else if (I.type == 1) { ma = &mp.y; mb = &mp.w1; n0 = I.nt * 256; }
        else if (I.type == 2) { ma = &mp.hid; mb = &mp.w2; n0 = I.nt * 256; nkb = 7; kb0 = I.ks * 7; }
        else { ma = &mp.o; mb = &mp.wo; n0 = I.nt * 256; kb0 = I.ks * 8; }
        for (int kb = kb0; kb < kb0 + nkb; kb++) {
          mbar_wait(empty + st * 8, ph ^ 1);
          mbar_expect(full + st * 8, 49152);
          uint32_t sa = sb + st * 49152;
          tma2d(sa, ma, kb * 64, I.rb * 128, full + st * 8);
          #pragma unroll
          for (int q = 0; q < 4; q++) tma2d(sa + 16384 + q * 8192, mb, n0 + q * 64, kb * 64, full + st * 8);
          if (++st == 4) { st = 0; ph ^= 1; }
        }
      }
    } else if (warp == 9) {
      for (int n = 0;; n++) {
        mbar_wait(ifull + (n & 1) * 8, (n >> 1) & 1);
        int it = ring[n & 1];
        if (it >= I_END) break;
        Item I = decode(it);
        bar_sync(6 + (n & 1), 288);
        if (lane == 0) {
          if (I.type != 5) {
            fence_async(); __threadfence();
            int* f = I.type == 0 ? &g_fl.tile[I.rb][I.nt] : I.type == 1 ? &g_fl.hid[I.rb] : I.type == 2 ? &g_fl.z[I.rb][0] : I.type == 3 ? &g_fl.o[I.rb][I.nt >> 2] : &g_fl.s[I.rb][0];
            atomicAdd(f, 1);
          }
          mbar_arrive(iempty + (n & 1) * 8);
        }
      }
    }
    return;
  }
  asm volatile("setmaxnreg.inc.sync.aligned.u32 232;");
  const int wg = warp >> 2;
  const uint32_t stg = sb + B_STG + warp * 2304;
  const int lm = lane >> 3, lr = lane & 7;
  uint32_t st = 0, ph = 0;
  float d[128];
  #pragma unroll 1
  for (int n = 0;; n++) {
    mbar_wait(ifull + (n & 1) * 8, (n >> 1) & 1);
    const int it = ring[n & 1];
    __syncwarp(); if (lane == 0) mbar_arrive(iempty + (n & 1) * 8);
    if (it >= I_END) break;
    Item I = decode(it);
    const int row0 = I.rb * 128 + warp * 16;
    TB(0);
    if (I.type == 5) {
      #pragma unroll
      for (int i = 0; i < 4; i++) {
        size_t off = (size_t)(I.rb * 128 + I.nt * 16 + warp * 2 + (i >> 1)) * DM + (i & 1) * 256 + lane * 8;
        float4 s0 = __ldcg((const float4*)(g_s + off)), s1 = __ldcg((const float4*)(g_s + off + 4));
        float4 z0 = __ldcg((const float4*)(g_z + off)), z1 = __ldcg((const float4*)(g_z + off + 4));
        uint4 xv = *(const uint4*)(x + off), bv = *(const uint4*)(b2 + (i & 1) * 256 + lane * 8);
        float sa[8] = {s0.x, s0.y, s0.z, s0.w, s1.x, s1.y, s1.z, s1.w}, za[8] = {z0.x, z0.y, z0.z, z0.w, z1.x, z1.y, z1.z, z1.w}, r[8];
        #pragma unroll
        for (int e = 0; e < 8; e++) { float xx = __bfloat162float(((const bf16*)&xv)[e]), bb = __bfloat162float(((const bf16*)&bv)[e]);
          float u = rbf(rbf(za[e]) + bb); float gg = rbf(__fdividef(u, 1.f + __expf(-u))); r[e] = xx + rbf(rbf(sa[e]) * gg); }
        *(uint4*)(out + off) = make_uint4(pack2(r[0], r[1]), pack2(r[2], r[3]), pack2(r[4], r[5]), pack2(r[6], r[7]));
      }
      bar_arrive(6 + (n & 1), 288);
      continue;
    }
    if (I.type == 3) {
      const int h = I.nt, seg = warp >> 1, half = warp & 1, step = I.rb * 4 + seg;
      uint32_t kmr[16], vmr[16];
      { const uint32_t* km = (const uint32_t*)(g_km + ((size_t)(step * 32 + h)) * 1024) + g * 64 + t;
        const uint32_t* vm = (const uint32_t*)(g_vmT + ((size_t)(step * 32 + h)) * 1024) + g * 4 + t;
        #pragma unroll
        for (int i = 0; i < 16; i++) { kmr[i] = __ldcg(km + i * 4); vmr[i] = __ldcg(vm + i * 32); } }
      uint32_t sQ = sb + st * 49152; mbar_wait(full + st * 8, ph); uint32_t eQ = empty + st * 8; if (++st == 4) { st = 0; ph ^= 1; }
      uint32_t sK = sb + st * 49152; mbar_wait(full + st * 8, ph); uint32_t eK = empty + st * 8; if (++st == 4) { st = 0; ph ^= 1; }
      float sc[5][4];
      #pragma unroll
      for (int i = 0; i < 5; i++) { sc[i][0] = sc[i][1] = sc[i][2] = sc[i][3] = 0.f; }
      #pragma unroll
      for (int ks = 0; ks < 8; ks++) {
        uint32_t a[4]; { int r = warp * 16 + 8 * (lm & 1) + lr, c8 = 2 * ks + (lm >> 1); ldsm4(a, sQ + (c8 >> 3) * 16384 + r * 128 + (((c8 & 7) ^ (r & 7)) << 4)); }
        #pragma unroll
        for (int np = 0; np < 2; np++) {
          if (np == 1 && half == 0) continue;
          uint32_t b[4]; int r = seg * 32 + 16 * np + 8 * (lm >> 1) + lr, c8 = 2 * ks + (lm & 1);
          ldsm4(b, sK + (c8 >> 3) * 16384 + r * 128 + (((c8 & 7) ^ (r & 7)) << 4));
          mma16(sc[2*np], a[0], a[1], a[2], a[3], b[0], b[1]); mma16(sc[2*np+1], a[0], a[1], a[2], a[3], b[2], b[3]);
        }
        mma16(sc[4], a[0], a[1], a[2], a[3], kmr[2*ks], kmr[2*ks+1]);
      }
      __syncwarp(); if (lane == 0) { mbar_arrive(eQ); mbar_arrive(eK); }
      const float scale = 0.08838834764831845f;
      uint32_t P[5][2];
      #pragma unroll
      for (int rr = 0; rr < 2; rr++) {
        const int qi = 16 * half + g + 8 * rr;
        float mx = -3.0e38f;
        #pragma unroll
        for (int i = 0; i < 5; i++)
          #pragma unroll
          for (int e = 0; e < 2; e++) { float v = rbf(rbf(sc[i][2*rr+e]) * scale); if (i < 4 && 8 * i + 2 * t + e > qi) v = -1.0e9f; sc[i][2*rr+e] = v; mx = fmaxf(mx, v); }
        mx = fmaxf(mx, __shfl_xor_sync(~0u, mx, 1)); mx = fmaxf(mx, __shfl_xor_sync(~0u, mx, 2));
        float sum = 0;
        #pragma unroll
        for (int i = 0; i < 5; i++)
          #pragma unroll
          for (int e = 0; e < 2; e++) { float v = __expf(sc[i][2*rr+e] - mx); sc[i][2*rr+e] = v; sum += v; }
        sum += __shfl_xor_sync(~0u, sum, 1); sum += __shfl_xor_sync(~0u, sum, 2);
        float inv = __fdividef(1.f, sum);
        #pragma unroll
        for (int i = 0; i < 5; i++) P[i][rr] = pack2(sc[i][2*rr] * inv, sc[i][2*rr+1] * inv);
      }
      uint32_t sV = sb + st * 49152; mbar_wait(full + st * 8, ph); uint32_t eV = empty + st * 8; if (++st == 4) { st = 0; ph ^= 1; }
      #pragma unroll
      for (int i = 0; i < 64; i++) d[i] = 0.f;
      #pragma unroll
      for (int n2 = 0; n2 < 8; n2++) {
        #pragma unroll
        for (int kk = 0; kk < 2; kk++) {
          if (kk == 1 && half == 0) continue;
          uint32_t b[4]; int r = seg * 32 + 16 * kk + 8 * (lm & 1) + lr, c8 = 2 * n2 + (lm >> 1);
          ldsm4t(b, sV + (c8 >> 3) * 16384 + r * 128 + (((c8 & 7) ^ (r & 7)) << 4));
          mma16(d + 8 * n2, P[2*kk][0], P[2*kk][1], P[2*kk+1][0], P[2*kk+1][1], b[0], b[1]);
          mma16(d + 8 * n2 + 4, P[2*kk][0], P[2*kk][1], P[2*kk+1][0], P[2*kk+1][1], b[2], b[3]);
        }
        mma8(d + 8 * n2, P[4][0], P[4][1], vmr[2*n2]); mma8(d + 8 * n2 + 4, P[4][0], P[4][1], vmr[2*n2+1]);
      }
      __syncwarp(); if (lane == 0) mbar_arrive(eV);
      #pragma unroll
      for (int ch = 0; ch < 2; ch++) {
        #pragma unroll
        for (int i = 0; i < 8; i++) { const float* a = d + ch * 32 + i * 4;
          sts32(stg + g * 144 + i * 16 + t * 4, pack2(a[0], a[1])); sts32(stg + (g + 8) * 144 + i * 16 + t * 4, pack2(a[2], a[3])); }
        __syncwarp();
        #pragma unroll
        for (int i = 0; i < 4; i++) { int r = i * 4 + lm; uint4 v = lds128(stg + r * 144 + lr * 16);
          *(uint4*)(g_o + (size_t)(row0 + r) * 4096 + h * 128 + ch * 64 + lr * 8) = v; }
        __syncwarp();
      }
      bar_arrive(6 + (n & 1), 288);
      continue;
    }
    const int nkb = I.type == 2 ? 7 : 8;
    uint32_t prev = 0;
    for (int kb = 0; kb < nkb; kb++) {
      mbar_wait(full + st * 8, ph);
      uint32_t sa = sb + st * 49152;
      asm volatile("wgmma.fence.sync.aligned;" ::: "memory");
      #pragma unroll
      for (int k = 0; k < 4; k++)
        wgmma256(d, mkdesc(sa + wg * 8192 + k * 32, 16, 1024), mkdesc(sa + 16384 + k * 2048, 8192, 1024), (kb | k) != 0);
      asm volatile("wgmma.commit_group.sync.aligned;" ::: "memory");
      if (kb > 0) { asm volatile("wgmma.wait_group.sync.aligned 1;" ::: "memory"); if (lane == 0) mbar_arrive(prev); }
      prev = empty + st * 8;
      if (++st == 4) { st = 0; ph ^= 1; }
    }
    asm volatile("wgmma.wait_group.sync.aligned 0;" ::: "memory");
    if (lane == 0) mbar_arrive(prev);
    TB(1);
    if (I.type <= 1) {
      bf16* dst; int ld;
      if (I.type == 0) { dst = g_qkv + (size_t)row0 * QW + I.nt * 256; ld = QW; } else { dst = g_hid + (size_t)row0 * FF + I.nt * 256; ld = FF; }
      #pragma unroll
      for (int ch = 0; ch < 4; ch++) {
        #pragma unroll
        for (int i = 0; i < 8; i++) { float* a = d + ch * 32 + i * 4;
          if (I.type == 1) { float2 bb = __bfloat1622float2(*(const __nv_bfloat162*)(b1 + I.nt * 256 + ch * 64 + i * 8 + 2 * t));
            a[0] = gelu_t(rbf(rbf(a[0]) + bb.x)); a[1] = gelu_t(rbf(rbf(a[1]) + bb.y)); a[2] = gelu_t(rbf(rbf(a[2]) + bb.x)); a[3] = gelu_t(rbf(rbf(a[3]) + bb.y)); }
          sts32(stg + g * 144 + i * 16 + t * 4, pack2(a[0], a[1])); sts32(stg + (g + 8) * 144 + i * 16 + t * 4, pack2(a[2], a[3])); }
        __syncwarp();
        #pragma unroll
        for (int i = 0; i < 4; i++) { int r = i * 4 + lm; uint4 v = lds128(stg + r * 144 + lr * 16); *(uint4*)(dst + (size_t)r * ld + ch * 64 + lr * 8) = v; }
        __syncwarp();
      }
    } else {
      float* dst = (I.type == 2 ? g_z : g_s) + (size_t)(row0 + g) * DM + I.nt * 256 + 2 * t;
      #pragma unroll
      for (int i = 0; i < 32; i++) {
        asm volatile("red.relaxed.gpu.global.add.v2.f32 [%0], {%1,%2};" ::"l"(dst + i * 8), "f"(d[4*i]), "f"(d[4*i+1]) : "memory");
        asm volatile("red.relaxed.gpu.global.add.v2.f32 [%0], {%1,%2};" ::"l"(dst + 8 * DM + i * 8), "f"(d[4*i+2]), "f"(d[4*i+3]) : "memory");
      }
    }
    bar_arrive(6 + (n & 1), 288);
  }
}

__global__ void __cluster_dims__(2, 1, 1) __launch_bounds__(384, 1)
main_kernel(const __grid_constant__ Maps mp, const bf16* x, const bf16* Wq, const bf16* Wk, const bf16* Wv, const bf16* Wo, const bf16* b1, const bf16* b2, bf16* out) {
  const uint32_t sb = smem_u32(smem_raw);
  if (sb & 1023) __trap();
  if (threadIdx.x == 0) {
    if (blockIdx.x < NREC) { mbar_init(sb + R_BAR, 1); mbar_init(sb + R_BAR + 8, 1); mbar_init(sb + R_BAR + 16, 1); }
    else { for (int i = 0; i < 4; i++) { mbar_init(sb + B_BAR + i * 8, 1); mbar_init(sb + B_BAR + 32 + i * 8, 8); }
      for (int i = 0; i < 2; i++) { mbar_init(sb + B_BAR + 64 + i * 8, 1); mbar_init(sb + B_BAR + 80 + i * 8, 9); } }
    asm volatile("fence.mbarrier_init.release.cluster;" ::: "memory");
  }
  asm volatile("barrier.cluster.arrive.release.aligned; barrier.cluster.wait.acquire.aligned;" ::: "memory");
  if (blockIdx.x < NREC) recurrence(sb, Wq, Wk, Wv, Wo);
  else bulk(sb, mp, x, b1, b2, out);
}

typedef CUresult (*EncFn)(CUtensorMap*, CUtensorMapDataType, cuuint32_t, void*, const cuuint64_t*, const cuuint64_t*, const cuuint32_t*, const cuuint32_t*, CUtensorMapInterleave, CUtensorMapSwizzle, CUtensorMapL2promotion, CUtensorMapFloatOOBfill);
static void mk(EncFn f, CUtensorMap* m, const void* p, uint64_t rows, uint64_t cols, uint32_t boxr) {
  cuuint64_t dims[2] = {cols, rows}, str[1] = {cols * 2}; cuuint32_t box[2] = {64, boxr}, es[2] = {1, 1};
  f(m, CU_TENSOR_MAP_DATA_TYPE_BFLOAT16, 2, (void*)p, dims, str, box, es, CU_TENSOR_MAP_INTERLEAVE_NONE, CU_TENSOR_MAP_SWIZZLE_128B, CU_TENSOR_MAP_L2_PROMOTION_L2_256B, CU_TENSOR_MAP_FLOAT_OOB_FILL_NONE);
}
extern "C" void kernel_launch(void* const* d_in, const int* in_sizes, int n_in, void* d_out, int out_size) {
  const bf16 *x = (const bf16*)d_in[0], *mem0 = (const bf16*)d_in[1], *Wq = (const bf16*)d_in[2], *Wk = (const bf16*)d_in[3], *Wv = (const bf16*)d_in[4], *Wo = (const bf16*)d_in[5];
  const bf16 *w1 = (const bf16*)d_in[8], *b1 = (const bf16*)d_in[9], *w2 = (const bf16*)d_in[10], *b2 = (const bf16*)d_in[11];
  void* fn = nullptr; cudaDriverEntryPointQueryResult qr;
  cudaGetDriverEntryPoint("cuTensorMapEncodeTiled", &fn, cudaEnableDefault, &qr);
  EncFn f = (EncFn)fn;
  void *pxn, *py, *ph, *po, *pq;
  cudaGetSymbolAddress(&pxn, g_xn); cudaGetSymbolAddress(&py, g_y); cudaGetSymbolAddress(&ph, g_hid); cudaGetSymbolAddress(&po, g_o); cudaGetSymbolAddress(&pq, g_qkv);
  Maps mp;
  mk(f, &mp.xn, pxn, SEQ, DM, 128); mk(f, &mp.y, py, SEQ, DM, 128); mk(f, &mp.hid, ph, SEQ, FF, 128); mk(f, &mp.o, po, SEQ, 4096, 128); mk(f, &mp.qkv, pq, SEQ, QW, 128);
  mk(f, &mp.wk, Wk, DM, 4096, 64); mk(f, &mp.wv, Wv, DM, 4096, 64); mk(f, &mp.wq, Wq, DM, 4096, 64);
  mk(f, &mp.w1, w1, DM, FF, 64); mk(f, &mp.w2, w2, FF, DM, 64); mk(f, &mp.wo, Wo, 4096, DM, 64);
  cudaFuncSetAttribute(main_kernel, cudaFuncAttributeMaxDynamicSharedMemorySize, SMEM_BYTES);
  prologue_kernel<<<256, 256, 0, cudaStreamPerThread>>>(x, mem0);
  main_kernel<<<NCTA, 384, SMEM_BYTES, cudaStreamPerThread>>>(mp, x, Wq, Wk, Wv, Wo, b1, b2, (bf16*)d_out);
}
```

```cpp
#include <cuda_runtime.h>
#include <cuda_bf16.h>
#include <cuda.h>
#include <stdint.h>

typedef __nv_bfloat16 bf16;
constexpr int SEQ = 2048, DM = 512, FF = 1792, QW = 12288, NSTEP = 64;
constexpr int NREC = 64, NBULK = 68, NCTA = 132;
constexpr int SPIN_LIMIT = 1 << 22;
#define THR 2
#define PDELAY 500

__device__ bf16 g_xn[SEQ * DM];
__device__ bf16 g_y[SEQ * DM];
__device__ bf16 g_qkv[(size_t)SEQ * QW];
__device__ bf16 g_hid[SEQ * FF];
__device__ bf16 g_o[(size_t)SEQ * 4096];
__device__ float g_z[SEQ * DM];
__device__ float g_s[SEQ * DM];
__device__ float4 g_acc[NSTEP][2][768];
__device__ bf16 g_km[NSTEP * 32 * 8 * 128];
__device__ bf16 g_vmT[NSTEP * 32 * 128 * 8];
struct Flags { int tile[16][48]; int hid[16]; int z[16][2]; int o[16][8]; int s[16][2]; int prog[16][32]; int next; };
__device__ Flags g_fl;

#define TR(i)
#define TB(i)
struct Maps { CUtensorMap xn, y, hid, o, qkv, wk, wv, wq, w1, w2, wo; };

extern __shared__ __align__(1024) uint8_t smem_raw[];
__device__ __forceinline__ uint4 ldc(uint32_t off) { return *(const uint4*)(smem_raw + off); }
__device__ __forceinline__ uint32_t smem_u32(const void* p) { return (uint32_t)__cvta_generic_to_shared(p); }
__device__ __forceinline__ int otid() { int t; asm volatile("mov.u32 %0, %%tid.x;" : "=r"(t)); return t; }
__device__ __forceinline__ uint32_t mapa(uint32_t a, uint32_t r) { uint32_t o; asm volatile("mapa.shared::cluster.u32 %0, %1, %2;" : "=r"(o) : "r"(a), "r"(r)); return o; }
__device__ __forceinline__ void st_async_v4(uint32_t addr, float a, float b, float c, float d, uint32_t mbar) {
  asm volatile("st.async.weak.shared::cluster.mbarrier::complete_tx::bytes.v4.b32 [%0], {%1,%2,%3,%4}, [%5];" ::"r"(addr), "r"(__float_as_uint(a)), "r"(__float_as_uint(b)), "r"(__float_as_uint(c)), "r"(__float_as_uint(d)), "r"(mbar) : "memory"); }
__device__ __forceinline__ void mbar_init(uint32_t m, int c) { asm volatile("mbarrier.init.shared::cta.b64 [%0], %1;" ::"r"(m), "r"(c) : "memory"); }
__device__ __forceinline__ void mbar_expect(uint32_t m, int bytes) { asm volatile("mbarrier.arrive.expect_tx.shared::cta.b64 _, [%0], %1;" ::"r"(m), "r"(bytes) : "memory"); }
__device__ __forceinline__ void mbar_arrive(uint32_t m) { asm volatile("mbarrier.arrive.shared::cta.b64 _, [%0];" ::"r"(m) : "memory"); }
__device__ __forceinline__ void mbar_wait(uint32_t m, uint32_t parity) {
  uint32_t ok; int it = 0;
  do { asm volatile("{.reg .pred p; mbarrier.try_wait.parity.shared::cta.b64 p, [%1], %2; selp.u32 %0,1,0,p;}" : "=r"(ok) : "r"(m), "r"(parity) : "memory"); } while (!ok && ++it < SPIN_LIMIT); }
__device__ __forceinline__ void mbar_spin(uint32_t m, uint32_t parity) {
  uint32_t ok; int it = 0;
  do { asm volatile("{.reg .pred p; mbarrier.test_wait.parity.shared::cta.b64 p, [%1], %2; selp.u32 %0,1,0,p;}" : "=r"(ok) : "r"(m), "r"(parity) : "memory"); } while (!ok && ++it < SPIN_LIMIT); }
__device__ __forceinline__ void bar_sync(int id, int n) { asm volatile("bar.sync %0, %1;" ::"r"(id), "r"(n) : "memory"); }
__device__ __forceinline__ void bar_arrive(int id, int n) { asm volatile("bar.arrive %0, %1;" ::"r"(id), "r"(n) : "memory"); }
__device__ __forceinline__ int ld_acq(const int* p) { int v; asm volatile("ld.acquire.gpu.global.s32 %0, [%1];" : "=r"(v) : "l"(p) : "memory"); return v; }
__device__ __forceinline__ void wait_flag(const int* p, int target) { int it = 0; while (ld_acq(p) < target && ++it < SPIN_LIMIT) { __nanosleep(40); } }
__device__ __forceinline__ void fence_async() { asm volatile("fence.proxy.async.global;" ::: "memory"); }
__device__ __forceinline__ uint4 lds128(uint32_t a) { uint4 v; asm volatile("ld.shared.v4.u32 {%0,%1,%2,%3}, [%4];" : "=r"(v.x), "=r"(v.y), "=r"(v.z), "=r"(v.w) : "r"(a) : "memory"); return v; }
__device__ __forceinline__ void sts128(uint32_t a, uint4 v) { asm volatile("st.shared.v4.u32 [%0], {%1,%2,%3,%4};" ::"r"(a), "r"(v.x), "r"(v.y), "r"(v.z), "r"(v.w) : "memory"); }
__device__ __forceinline__ void sts32(uint32_t a, uint32_t v) { asm volatile("st.shared.u32 [%0], %1;" ::"r"(a), "r"(v) : "memory"); }
__device__ __forceinline__ void sts16(uint32_t a, float f) { unsigned short h = __bfloat16_as_ushort(__float2bfloat16(f)); asm volatile("st.shared.u16 [%0], %1;" ::"r"(a), "h"(h) : "memory"); }
__device__ __forceinline__ void ldsm4(uint32_t* r, uint32_t a) { asm volatile("ldmatrix.sync.aligned.m8n8.x4.shared.b16 {%0,%1,%2,%3}, [%4];" : "=r"(r[0]), "=r"(r[1]), "=r"(r[2]), "=r"(r[3]) : "r"(a) : "memory"); }
__device__ __forceinline__ void ldsm4t(uint32_t* r, uint32_t a) { asm volatile("ldmatrix.sync.aligned.m8n8.x4.trans.shared.b16 {%0,%1,%2,%3}, [%4];" : "=r"(r[0]), "=r"(r[1]), "=r"(r[2]), "=r"(r[3]) : "r"(a) : "memory"); }
__device__ __forceinline__ void mma16(float* c, uint32_t a0, uint32_t a1, uint32_t a2, uint32_t a3, uint32_t b0, uint32_t b1) {
  asm("mma.sync.aligned.m16n8k16.row.col.f32.bf16.bf16.f32 {%0,%1,%2,%3}, {%4,%5,%6,%7}, {%8,%9}, {%0,%1,%2,%3};" : "+f"(c[0]), "+f"(c[1]), "+f"(c[2]), "+f"(c[3]) : "r"(a0), "r"(a1), "r"(a2), "r"(a3), "r"(b0), "r"(b1)); }
__device__ __forceinline__ void mma8(float* c, uint32_t a0, uint32_t a1, uint32_t b0) {
  asm("mma.sync.aligned.m16n8k8.row.col.f32.bf16.bf16.f32 {%0,%1,%2,%3}, {%4,%5}, {%6}, {%0,%1,%2,%3};" : "+f"(c[0]), "+f"(c[1]), "+f"(c[2]), "+f"(c[3]) : "r"(a0), "r"(a1), "r"(b0)); }
__device__ __forceinline__ uint32_t pack2(float a, float b) { __nv_bfloat162 h = __floats2bfloat162_rn(a, b); return *(uint32_t*)&h; }
__device__ __forceinline__ float rbf(float x) { uint32_t r; asm("cvt.rn.bf16x2.f32 %0, %1, %2;" : "=r"(r) : "f"(x), "f"(0.f)); return __uint_as_float(r); }
__device__ __forceinline__ void cp16(uint32_t d, const void* s) { asm volatile("cp.async.cg.shared.global [%0], [%1], 16;" ::"r"(d), "l"(s) : "memory"); }
__device__ __forceinline__ void tma2d(uint32_t dst, const CUtensorMap* m, int c0, int c1, uint32_t mbar) {
  asm volatile("cp.async.bulk.tensor.2d.shared::cluster.global.mbarrier::complete_tx::bytes [%0], [%1, {%2,%3}], [%4];" ::"r"(dst), "l"(m), "r"(c0), "r"(c1), "r"(mbar) : "memory"); }
__device__ __forceinline__ uint64_t mkdesc(uint32_t addr, uint32_t lbo, uint32_t sbo) {
  return (uint64_t)((addr & 0x3FFFF) >> 4) | ((uint64_t)(lbo >> 4) << 16) | ((uint64_t)(sbo >> 4) << 32) | (1ull << 62); }

#define R8(i) "+f"(d[i]), "+f"(d[i+1]), "+f"(d[i+2]), "+f"(d[i+3]), "+f"(d[i+4]), "+f"(d[i+5]), "+f"(d[i+6]), "+f"(d[i+7])
__device__ __forceinline__ void wgmma256(float* d, uint64_t da, uint64_t db, int acc) {
  asm volatile("{.reg .pred p; setp.ne.b32 p, %130, 0;\n"
    "wgmma.mma_async.sync.aligned.m64n256k16.f32.bf16.bf16 {"
    "%0,%1,%2,%3,%4,%5,%6,%7,%8,%9,%10,%11,%12,%13,%14,%15,%16,%17,%18,%19,%20,%21,%22,%23,%24,%25,%26,%27,%28,%29,%30,%31,"
    "%32,%33,%34,%35,%36,%37,%38,%39,%40,%41,%42,%43,%44,%45,%46,%47,%48,%49,%50,%51,%52,%53,%54,%55,%56,%57,%58,%59,%60,%61,%62,%63,"
    "%64,%65,%66,%67,%68,%69,%70,%71,%72,%73,%74,%75,%76,%77,%78,%79,%80,%81,%82,%83,%84,%85,%86,%87,%88,%89,%90,%91,%92,%93,%94,%95,"
    "%96,%97,%98,%99,%100,%101,%102,%103,%104,%105,%106,%107,%108,%109,%110,%111,%112,%113,%114,%115,%116,%117,%118,%119,%120,%121,%122,%123,%124,%125,%126,%127"
    "}, %128, %129, p, 1, 1, 0, 1;}"
    : R8(0), R8(8), R8(16), R8(24), R8(32), R8(40), R8(48), R8(56), R8(64), R8(72), R8(80), R8(88), R8(96), R8(104), R8(112), R8(120)
    : "l"(da), "l"(db), "r"(acc)); }

__global__ void __launch_bounds__(256) prologue_kernel(const bf16* __restrict__ x, const bf16* __restrict__ mem0) {
  int tid = threadIdx.x, lane = tid & 31, warp = tid >> 5;
  int row = blockIdx.x * 8 + warp;
  {
    const uint4* src = (const uint4*)(x + (size_t)row * DM);
    uint4 u[2] = { src[lane], src[lane + 32] };
    float v[16];
    #pragma unroll
    for (int i = 0; i < 2; i++) { const __nv_bfloat162* h = (const __nv_bfloat162*)&u[i];
      #pragma unroll
      for (int k = 0; k < 4; k++) { float2 f = __bfloat1622float2(h[k]); v[i * 8 + 2 * k] = f.x; v[i * 8 + 2 * k + 1] = f.y; } }
    #pragma unroll
    for (int pass = 0; pass < 2; pass++) {
      float s = 0;
      #pragma unroll
      for (int i = 0; i < 16; i++) s += v[i];
      #pragma unroll
      for (int o = 16; o; o >>= 1) s += __shfl_xor_sync(~0u, s, o);
      float mf = s * (1.f / DM);
      float q = 0;
      #pragma unroll
      for (int i = 0; i < 16; i++) { float dd = v[i] - mf; q += dd * dd; }
      #pragma unroll
      for (int o = 16; o; o >>= 1) q += __shfl_xor_sync(~0u, q, o);
      float m = rbf(mf), var = rbf(q * (1.f / DM));
      float den = rbf(sqrtf(rbf(var + 1e-5f)));
      #pragma unroll
      for (int i = 0; i < 16; i++) v[i] = rbf(rbf(v[i] - m) / den);
      uint4 o4[2];
      #pragma unroll
      for (int i = 0; i < 2; i++) { o4[i].x = pack2(v[i*8], v[i*8+1]); o4[i].y = pack2(v[i*8+2], v[i*8+3]); o4[i].z = pack2(v[i*8+4], v[i*8+5]); o4[i].w = pack2(v[i*8+6], v[i*8+7]); }
      uint4* dst = (uint4*)((pass ? g_y : g_xn) + (size_t)row * DM);
      dst[lane] = o4[0]; dst[lane + 32] = o4[1];
    }
  }
  int gt = blockIdx.x * 256 + tid;
  float4 z4 = make_float4(0, 0, 0, 0);
  #pragma unroll
  for (int i = 0; i < 4; i++) { ((float4*)g_z)[gt + i * 65536] = z4; ((float4*)g_s)[gt + i * 65536] = z4; }
  for (int i = gt; i < NSTEP * 1536; i += 65536) {
    float4 val = z4;
    if (i < 1536) {
      int j = i / 768, c = i % 768, ci = c >> 8, w = (c & 255) >> 5, l = c & 31, g = l >> 2, t = l & 3;
      float e3[3];
      #pragma unroll
      for (int k = 0; k < 3; k++) { int e = ci * 3 + k; int mt = e >> 2, cc = e & 3;
        e3[k] = e < 8 ? __bfloat162float(mem0[(2 * t + (cc & 1)) * DM + 256 * j + 32 * w + 16 * mt + g + 8 * (cc >> 1)]) : 0.f; }
      val = make_float4(e3[0], e3[1], e3[2], 32.f);
    }
    (&g_acc[0][0][0])[i] = val;
  }
  if (gt < (int)(sizeof(Flags) / 4)) ((int*)&g_fl)[gt] = 0;
}

constexpr int R_WR = 0, R_KT = 65536, KT_SZ = 40 * 256, R_VT = R_KT + 2 * KT_SZ, VT_SZ = 40 * 272,
              R_MEM = R_VT + 2 * VT_SZ, R_Q = R_MEM + 32 * 160, R_O = R_Q + 8 * 256, R_S = R_O + 8 * 256,
              R_SM = R_S + 8 * 40 * 4, R_RQK = R_SM + 1024, R_RV = R_RQK + 8192, R_WQ = R_RV + 4096, R_BAR = 232448 - 64, R_END = R_BAR + 64;
#define KD 150
#define VCH 2
#define VP 4
__device__ __forceinline__ void wgmma8(float* d, uint64_t da, uint64_t db, int acc) {
  asm volatile("{.reg .pred p; setp.ne.b32 p, %6, 0;\n wgmma.mma_async.sync.aligned.m64n8k16.f32.bf16.bf16 {%0,%1,%2,%3}, %4, %5, p, 1, 1, 0, 0;}"
    : "+f"(d[0]), "+f"(d[1]), "+f"(d[2]), "+f"(d[3]) : "l"(da), "l"(db), "r"(acc)); }
__device__ __forceinline__ void stsm4(uint32_t a, uint32_t r0, uint32_t r1, uint32_t r2, uint32_t r3) { asm volatile("stmatrix.sync.aligned.m8n8.x4.shared.b16 [%0], {%1,%2,%3,%4};" ::"r"(a), "r"(r0), "r"(r1), "r"(r2), "r"(r3) : "memory"); }
__device__ __forceinline__ uint32_t swz(uint32_t r) { return ((r & 1) << 2) | ((r >> 1) & 3); }
__device__ __forceinline__ void stsm4t(uint32_t a, uint32_t r0, uint32_t r1, uint32_t r2, uint32_t r3) { asm volatile("stmatrix.sync.aligned.m8n8.x4.trans.shared.b16 [%0], {%1,%2,%3,%4};" ::"r"(a), "r"(r0), "r"(r1), "r"(r2), "r"(r3) : "memory"); }
__device__ __forceinline__ void stsm2(uint32_t a, uint32_t r0, uint32_t r1) { asm volatile("stmatrix.sync.aligned.m8n8.x2.shared.b16 [%0], {%1,%2};" ::"r"(a), "r"(r0), "r"(r1) : "memory"); }
__device__ __forceinline__ float ex2(float x) { float r; asm("ex2.approx.ftz.f32 %0, %1;" : "=f"(r) : "f"(x)); return r; }
#define REDV4(p, a, b, c) asm volatile("red.relaxed.gpu.global.add.v4.f32 [%0], {%1,%2,%3,%4};" ::"l"(p), "f"(a), "f"(b), "f"(c), "f"(1.0f) : "memory")
constexpr int SMEM_BYTES = 232448;
static_assert(R_END <= SMEM_BYTES, "smem");

__device__ __forceinline__ void recurrence(uint32_t sb, const bf16* __restrict__ Wq, const bf16* __restrict__ Wk, const bf16* __restrict__ Wv, const bf16* __restrict__ Wo) {
  const int tid = threadIdx.x, warp = tid >> 5, lane = tid & 31, g = lane >> 2, t = lane & 3;
  const int h = blockIdx.x >> 1, j = blockIdx.x & 1;
  const uint32_t peer = j ^ 1;
  const uint32_t mQ = sb + R_BAR, mV = sb + R_BAR + 8, mK = sb + R_BAR + 16;
  uint32_t A[2][16][4];
  const uint32_t stA = sb + 65536, stB = stA + 69632;
  const int lm = lane >> 3, lr = lane & 7;
  for (int i = tid; i < 256 * 16; i += 384) { int r = i >> 4, c = i & 15; size_t o = ((size_t)(256 * j + r)) * 4096 + h * 128 + c * 8;
    cp16(stA + r * 272 + c * 16, Wv + o); cp16(stB + r * 272 + c * 16, Wq + o); }
  asm volatile("cp.async.wait_all;" ::: "memory"); __syncthreads();
  if (warp < 4) {
    #pragma unroll
    for (int mt = 0; mt < 2; mt++)
      #pragma unroll
      for (int ks = 0; ks < 16; ks++) {
        int k = 32 * (ks >> 1) + 8 * (lr >> 1) + (lr & 1) + 4 * (ks & 1) + 2 * (lm >> 1);
        ldsm4t(A[mt][ks], stB + k * 272 + (32 * warp + 16 * mt + 8 * (lm & 1)) * 2);
      }
  } else {
    #pragma unroll 4
    for (int i = 0; i < 16; i++) { const int mt = (warp >> 2) - 1, ks = i, k = 32 * (ks >> 1) + 8 * (lr >> 1) + (lr & 1) + 4 * (ks & 1) + 2 * (lm >> 1); uint32_t r[4];
      ldsm4t(r, stA + k * 272 + (32 * (warp & 3) + 16 * mt + 8 * (lm & 1)) * 2);
      sts128(sb + R_WR + (((warp & 3) * 32 + ks * 2 + mt) * 32 + lane) * 16, make_uint4(r[0], r[1], r[2], r[3])); }
  }
  __syncthreads();
  for (int i = tid; i < 256 * 16; i += 384) { int r = i >> 4, c = i & 15; cp16(stA + r * 272 + c * 16, Wk + ((size_t)(256 * j + r)) * 4096 + h * 128 + c * 8);
    r = i >> 5; c = i & 31; cp16(stB + r * 528 + c * 16, Wo + ((size_t)(h * 128 + r)) * DM + 256 * j + c * 8); }
  asm volatile("cp.async.wait_all;" ::: "memory"); __syncthreads();
  if (warp >= 4) {
    #pragma unroll
    for (int mt = 0; mt < 2; mt++)
      #pragma unroll
      for (int ks = 0; ks < 16; ks++) {
        int k = 32 * (ks >> 1) + 8 * (lr >> 1) + (lr & 1) + 4 * (ks & 1) + 2 * (lm >> 1);
        ldsm4t(A[mt][ks], warp < 8 ? stA + k * 272 + (32 * (warp & 3) + 16 * mt + 8 * (lm & 1)) * 2
                                   : stB + (k & 127) * 528 + (64 * (warp & 3) + 32 * mt + 16 * (ks >> 3) + 8 * (lm & 1)) * 2);
      }
  }
  __syncthreads();
  if (warp < 4) {
    #pragma unroll
    for (int i = 0; i < 16; i++) sts128(sb + R_WQ + ((warp * 16 + i) * 32 + lane) * 16, make_uint4(A[1][i][0], A[1][i][1], A[1][i][2], A[1][i][3]));
  }
  __syncthreads();
  if (warp >= 8) {
    #pragma unroll 1
    for (int s = 0; s < NSTEP; s++) {
      const int tid = otid(), lane = tid & 31, wv = (tid >> 5) - 8, g = lane >> 2, t = lane & 3;
      if (tid == 256) mbar_expect(mV, 4096);
      const uint32_t fo = (t ^ swz(g)) << 4;
      const int wo = R_WR + (wv * 1024 + lane) * 16;
      uint4 a0 = ldc(wo), a1 = ldc(wo + 512), a2 = ldc(wo + 1024), a3 = ldc(wo + 1536);
      TR(1);
      bar_sync(4, 384);
      TR(2);
      float c[4][4];
      #pragma unroll
      for (int i = 0; i < 4; i++) { c[i][0] = c[i][1] = c[i][2] = c[i][3] = 0.f; }
      #pragma unroll
      for (int p = 0; p < 8; p++) {
        uint4 b = ldc(R_MEM + g * 16 + t * 160 + p * 640);
        mma16(c[0], a0.x, a0.y, a0.z, a0.w, b.x, b.y); if (p < 7) a0 = ldc(wo + p * 2048 + 2048);
        mma16(c[1], a1.x, a1.y, a1.z, a1.w, b.x, b.y); if (p < 7) a1 = ldc(wo + p * 2048 + 2560);
        mma16(c[VCH], a2.x, a2.y, a2.z, a2.w, b.z, b.w); if (p < 7) a2 = ldc(wo + p * 2048 + 3072);
        mma16(c[VCH + 1], a3.x, a3.y, a3.z, a3.w, b.z, b.w); if (p < 7) a3 = ldc(wo + p * 2048 + 3584);
      }
      TR(3);
      if (VCH) {
        #pragma unroll
        for (int i = 0; i < 4; i++) { c[0][i] += c[2][i]; c[1][i] += c[3][i]; }
      }
      const uint32_t rx = sb + R_RV + (wv * 64 + lane) * 16;
      { uint32_t ra = mapa(rx, peer), rm = mapa(mV, peer);
        st_async_v4(ra, c[0][0], c[0][1], c[0][2], c[0][3], rm);
        st_async_v4(ra + 512, c[1][0], c[1][1], c[1][2], c[1][3], rm); }
      TR(4);
      const bool more = s < NSTEP - 1;
      mbar_wait(mV, s & 1);
      TR(5);
      { uint4 r0 = lds128(rx), r1 = lds128(rx + 512);
        stsm4t(sb + R_VT + (s & 1) * VT_SZ + (32 + (lane & 7)) * 272 + (4 * wv + (lane >> 3)) * 16,
          pack2(c[0][0] + __uint_as_float(r0.x), c[0][1] + __uint_as_float(r0.y)), pack2(c[0][2] + __uint_as_float(r0.z), c[0][3] + __uint_as_float(r0.w)),
          pack2(c[1][0] + __uint_as_float(r1.x), c[1][1] + __uint_as_float(r1.y)), pack2(c[1][2] + __uint_as_float(r1.z), c[1][3] + __uint_as_float(r1.w))); }
      if (more) {
      bar_arrive(3, 256);
      TR(8);
      bar_sync(7, 256);
      TR(9);
      #pragma unroll
      for (int i = 0; i < 4; i++) { c[i][0] = c[i][1] = c[i][2] = c[i][3] = 0.f; }
      #pragma unroll
      for (int p = 0; p < 4; p++) {
        uint4 b = ldc(R_O + g * 256 + (p >> 1) * 128 + (fo ^ ((p & 1) << 6)));
        #pragma unroll
        for (int mt = 0; mt < 4; mt++) { const uint32_t* a = A[mt >> 1][(mt & 1) * 8 + 2 * p]; mma16(c[mt], a[0], a[1], a[2], a[3], b.x, b.y); }
        #pragma unroll
        for (int mt = 0; mt < 4; mt++) { const uint32_t* a = A[mt >> 1][(mt & 1) * 8 + 2 * p + 1]; mma16(c[mt], a[0], a[1], a[2], a[3], b.z, b.w); }
      }
      TR(6);
      float4* dst = &g_acc[s + 1][j][wv * 64 + lane];
      REDV4(dst, c[0][0], c[0][1], c[0][2]); REDV4(dst + 256, c[0][3], c[1][0], c[1][1]); REDV4(dst + 512, c[1][2], c[1][3], 0.f);
      REDV4(dst + 32, c[2][0], c[2][1], c[2][2]); REDV4(dst + 288, c[2][3], c[3][0], c[3][1]); REDV4(dst + 544, c[3][2], c[3][3], 0.f);
      bar_arrive(8, 384);
      TR(7);
      } else bar_sync(6, 256);
      { const int vt = tid - 256;
        if (j == 0) { const int r = vt >> 4, cc = vt & 15; uint4 v = lds128(sb + R_KT + (s & 1) * KT_SZ + (32 + r) * 256 + ((cc ^ swz(r)) << 4));
          __stcg((uint4*)(g_km + ((size_t)(s * 32 + h)) * 1024) + vt, v); }
        else { uint32_t vb = sb + R_VT + (s & 1) * VT_SZ + 32 * 272 + vt * 2; uint32_t e[8];
          #pragma unroll
          for (int k = 0; k < 8; k++) { unsigned short x; asm volatile("ld.shared.u16 %0, [%1];" : "=h"(x) : "r"(vb + k * 272) : "memory"); e[k] = x; }
          __stcg((uint4*)(g_vmT + ((size_t)(s * 32 + h)) * 1024) + vt, make_uint4(e[0] | (e[1] << 16), e[2] | (e[3] << 16), e[4] | (e[5] << 16), e[6] | (e[7] << 16))); }
        __syncwarp(); if (lane == 0) { __threadfence(); atomicAdd(&g_fl.prog[s >> 2][h], 1); } __syncwarp(); }
    }
    return;
  }
  const float scale = 0.08838834764831845f, l2e = 1.4426950408889634f;
  auto prefetch = [&](int s) {
    const int vt = otid() - 160;
    if ((s & 3) == 0) { wait_flag(&g_fl.tile[s >> 2][h >> 1], 1); wait_flag(&g_fl.tile[s >> 2][16 + (h >> 1)], 1); }
    const int r = vt >> 4, c = vt & 15;
    const bf16* src = g_qkv + (size_t)(32 * s + r) * QW + h * 128 + c * 8;
    uint32_t kb = sb + R_KT + (s & 1) * KT_SZ + r * 256, vb = sb + R_VT + (s & 1) * VT_SZ + r * 272 + c * 16;
    #pragma unroll
    for (int i = 0; i < 8; i++) { cp16(kb + i * 1024 + ((c ^ swz(r + 4 * i)) << 4), src + (size_t)i * 4 * QW); cp16(vb + i * 1088, src + (size_t)i * 4 * QW + 4096); }
  };
  if (warp >= 4) {
  if (warp == 5 || warp == 6) prefetch(0);
  #pragma unroll 1
  for (int s = 0; s < NSTEP; s++) {
    TR(0); TR(1);
    const int tid = otid(), lane = tid & 31, warp = tid >> 5, g = lane >> 2, t = lane & 3;
    const uint32_t fo = (t ^ swz(g)) << 4;
    {
      if (tid == 0) mbar_expect(mQ, 4096);
      if (tid == 128) mbar_expect(mK, 4096);
      const float4* src = &g_acc[s][j][tid];
      uint4 v0, v1, v2; int it = 0; bool ok;
      do {
        asm volatile("ld.relaxed.gpu.global.v4.u32 {%0,%1,%2,%3}, [%4];" : "=r"(v0.x), "=r"(v0.y), "=r"(v0.z), "=r"(v0.w) : "l"(src) : "memory");
        asm volatile("ld.relaxed.gpu.global.v4.u32 {%0,%1,%2,%3}, [%4];" : "=r"(v1.x), "=r"(v1.y), "=r"(v1.z), "=r"(v1.w) : "l"(src + 256) : "memory");
        asm volatile("ld.relaxed.gpu.global.v4.u32 {%0,%1,%2,%3}, [%4];" : "=r"(v2.x), "=r"(v2.y), "=r"(v2.z), "=r"(v2.w) : "l"(src + 512) : "memory");
        ok = (v0.w == 0x42000000u) && (v1.w == 0x42000000u) && (v2.w == 0x42000000u);
      } while (!ok && ++it < SPIN_LIMIT);
      __syncwarp();
      stsm4t(sb + R_MEM + (lane & 7) * 16 + (4 * warp + (lane >> 3)) * 160,
        pack2(__uint_as_float(v0.x), __uint_as_float(v0.y)), pack2(__uint_as_float(v0.z), __uint_as_float(v1.x)),
        pack2(__uint_as_float(v1.y), __uint_as_float(v1.z)), pack2(__uint_as_float(v2.x), __uint_as_float(v2.y)));
    }
    TR(2);
    asm volatile("cp.async.wait_all;" ::: "memory");
    bar_sync(1, 256);
    { long long t0 = clock64(); while (clock64() - t0 < KD); }
    if (VP < 0) bar_arrive(4, 384);
    TR(3);
    float c[4][4];
    #pragma unroll
    for (int i = 0; i < 4; i++) { c[i][0] = c[i][1] = c[i][2] = c[i][3] = 0.f; }
    #pragma unroll
    for (int p = 0; p < 8; p++) {
      uint4 b = ldc(R_MEM + g * 16 + t * 160 + p * 640);
      mma16(c[0], A[0][2*p][0], A[0][2*p][1], A[0][2*p][2], A[0][2*p][3], b.x, b.y);
      mma16(c[1], A[1][2*p][0], A[1][2*p][1], A[1][2*p][2], A[1][2*p][3], b.x, b.y);
      mma16(c[2], A[0][2*p+1][0], A[0][2*p+1][1], A[0][2*p+1][2], A[0][2*p+1][3], b.z, b.w);
      mma16(c[3], A[1][2*p+1][0], A[1][2*p+1][1], A[1][2*p+1][2], A[1][2*p+1][3], b.z, b.w);
      if (p == VP) asm volatile("bar.arrive 4, 384;");
    }
    #pragma unroll
    for (int i = 0; i < 4; i++) { c[0][i] += c[2][i]; c[1][i] += c[3][i]; }
    const uint32_t rx = sb + R_RQK + (warp * 64 + lane) * 16;
    { uint32_t ra = mapa(rx, peer), rm = mapa(mK, peer);
      st_async_v4(ra, c[0][0], c[0][1], c[0][2], c[0][3], rm);
      st_async_v4(ra + 512, c[1][0], c[1][1], c[1][2], c[1][3], rm); }
    if (VP > 7) bar_arrive(4, 384);
    TR(4);
    const uint32_t so = (lane & 7) * 256 + (((4 * (warp & 3) + (lane >> 3)) ^ swz(lane & 7)) << 4);
    mbar_wait(mK, s & 1);
    TR(5);
    uint32_t m0, m1, m2, m3;
    { uint4 r0 = lds128(rx), r1 = lds128(rx + 512);
      m0 = pack2(c[0][0] + __uint_as_float(r0.x), c[0][1] + __uint_as_float(r0.y)); m1 = pack2(c[0][2] + __uint_as_float(r0.z), c[0][3] + __uint_as_float(r0.w));
      m2 = pack2(c[1][0] + __uint_as_float(r1.x), c[1][1] + __uint_as_float(r1.y)); m3 = pack2(c[1][2] + __uint_as_float(r1.z), c[1][3] + __uint_as_float(r1.w)); }
    stsm4t(sb + R_KT + (s & 1) * KT_SZ + 32 * 256 + so, m0, m1, m2, m3);
    if (s == NSTEP - 1) { bar_arrive(6, 256); break; }
    asm("movmatrix.sync.aligned.m8n8.trans.b16 %0, %0;" : "+r"(m0)); asm("movmatrix.sync.aligned.m8n8.trans.b16 %0, %0;" : "+r"(m1));
    asm("movmatrix.sync.aligned.m8n8.trans.b16 %0, %0;" : "+r"(m2)); asm("movmatrix.sync.aligned.m8n8.trans.b16 %0, %0;" : "+r"(m3));
    TR(8);
    bar_sync(9, 256);
    TR(9);
    { uint32_t qa[4]; ldsm4(qa, sb + R_Q + so);
      #pragma unroll
      for (int i = 0; i < 2; i++) { c[i][0] = c[i][1] = c[i][2] = c[i][3] = 0.f; }
      mma16(c[0], qa[0], 0, qa[1], 0, m0, m1); mma16(c[1], qa[2], 0, qa[3], 0, m2, m3);
      asm volatile("st.shared.v2.f32 [%0], {%1,%2};" ::"r"(sb + R_SM + (warp - 4) * 256 + lane * 8), "f"(c[0][0] + c[1][0]), "f"(c[0][1] + c[1][1]) : "memory"); }
    bar_arrive(2, 256);
    TR(10);
    if ((warp == 5 || warp == 6) && s < NSTEP - 2) prefetch(s + 1);
    TR(7);
    bar_sync(8, 384);
    { long long t0 = clock64(); while (clock64() - t0 < PDELAY); }
  }
  return;
  }
  #pragma unroll 1
  for (int s = 0; s < NSTEP; s++) {
    TR(0); TR(1);
    const int tid = otid(), lane = tid & 31, warp = tid >> 5, g = lane >> 2, t = lane & 3;
    const uint32_t fo = (t ^ swz(g)) << 4;
    {
      if (tid == 0) mbar_expect(mQ, 4096);
      if (tid == 128) mbar_expect(mK, 4096);
      const float4* src = &g_acc[s][j][tid];
      uint4 v0, v1, v2; int it = 0; bool ok;
      do {
        asm volatile("ld.relaxed.gpu.global.v4.u32 {%0,%1,%2,%3}, [%4];" : "=r"(v0.x), "=r"(v0.y), "=r"(v0.z), "=r"(v0.w) : "l"(src) : "memory");
        asm volatile("ld.relaxed.gpu.global.v4.u32 {%0,%1,%2,%3}, [%4];" : "=r"(v1.x), "=r"(v1.y), "=r"(v1.z), "=r"(v1.w) : "l"(src + 256) : "memory");
        asm volatile("ld.relaxed.gpu.global.v4.u32 {%0,%1,%2,%3}, [%4];" : "=r"(v2.x), "=r"(v2.y), "=r"(v2.z), "=r"(v2.w) : "l"(src + 512) : "memory");
        ok = (v0.w == 0x42000000u) && (v1.w == 0x42000000u) && (v2.w == 0x42000000u);
      } while (!ok && ++it < SPIN_LIMIT);
      __syncwarp();
      stsm4t(sb + R_MEM + (lane & 7) * 16 + (4 * warp + (lane >> 3)) * 160,
        pack2(__uint_as_float(v0.x), __uint_as_float(v0.y)), pack2(__uint_as_float(v0.z), __uint_as_float(v1.x)),
        pack2(__uint_as_float(v1.y), __uint_as_float(v1.z)), pack2(__uint_as_float(v2.x), __uint_as_float(v2.y)));
    }
    TR(2);

    bar_sync(1, 256);
    bar_arrive(4, 384);
    TR(3);
    float c[4][4];
    #pragma unroll
    for (int i = 0; i < 4; i++) { c[i][0] = c[i][1] = c[i][2] = c[i][3] = 0.f; }
    #pragma unroll
    for (int p = 0; p < 8; p++) {
      uint4 b = ldc(R_MEM + g * 16 + t * 160 + p * 640);
      mma16(c[0], A[0][2*p][0], A[0][2*p][1], A[0][2*p][2], A[0][2*p][3], b.x, b.y);
      mma16(c[1], A[1][2*p][0], A[1][2*p][1], A[1][2*p][2], A[1][2*p][3], b.x, b.y);
      mma16(c[2], A[0][2*p+1][0], A[0][2*p+1][1], A[0][2*p+1][2], A[0][2*p+1][3], b.z, b.w);
      mma16(c[3], A[1][2*p+1][0], A[1][2*p+1][1], A[1][2*p+1][2], A[1][2*p+1][3], b.z, b.w);
    }
    #pragma unroll
    for (int i = 0; i < 4; i++) { c[0][i] += c[2][i]; c[1][i] += c[3][i]; }
    const uint32_t rx = sb + R_RQK + (warp * 64 + lane) * 16;
    { uint32_t ra = mapa(rx, peer), rm = mapa(mQ, peer);
      st_async_v4(ra, c[0][0], c[0][1], c[0][2], c[0][3], rm);
      st_async_v4(ra + 512, c[1][0], c[1][1], c[1][2], c[1][3], rm); }
    TR(4);
    const uint32_t so = (lane & 7) * 256 + (((4 * (warp & 3) + (lane >> 3)) ^ swz(lane & 7)) << 4);
    if (s == NSTEP - 1) { mbar_wait(mQ, s & 1); break; }
    uint4 kf[4]; uint32_t vf[4][4];
    const uint32_t vb = sb + R_VT + (s & 1) * VT_SZ + (lane & 15) * 272 + (32 * warp + 8 * (lane >> 4)) * 2;
    #pragma unroll
    for (int p = 0; p < 4; p++) kf[p] = lds128(sb + R_KT + (s & 1) * KT_SZ + warp * 2048 + g * 256 + (p >> 1) * 128 + (fo ^ ((p & 1) << 6)));
    #pragma unroll
    for (int i = 0; i < 4; i++) ldsm4t(vf[i], vb + (i >> 1) * 16 * 272 + (i & 1) * 32);
    mbar_wait(mQ, s & 1);
    TR(5);
    uint32_t m0, m1, m2, m3;
    { uint4 r0 = lds128(rx), r1 = lds128(rx + 512);
      m0 = pack2(c[0][0] + __uint_as_float(r0.x), c[0][1] + __uint_as_float(r0.y)); m1 = pack2(c[0][2] + __uint_as_float(r0.z), c[0][3] + __uint_as_float(r0.w));
      m2 = pack2(c[1][0] + __uint_as_float(r1.x), c[1][1] + __uint_as_float(r1.y)); m3 = pack2(c[1][2] + __uint_as_float(r1.z), c[1][3] + __uint_as_float(r1.w)); }
    stsm4t(sb + R_Q + so, m0, m1, m2, m3);
    TR(8);
    bar_arrive(9, 256); bar_sync(5, 128);
    TR(9);
    {
      uint4 qa[4];
      #pragma unroll
      for (int p = 0; p < 4; p++) qa[p] = lds128(sb + R_Q + g * 256 + (p >> 1) * 128 + (fo ^ ((p & 1) << 6)));
      #pragma unroll
      for (int i = 0; i < 4; i++) { c[i][0] = c[i][1] = c[i][2] = c[i][3] = 0.f; }
      #pragma unroll
      for (int p = 0; p < 4; p++) { mma16(c[(p & 1) * 2], qa[p].x, 0, qa[p].y, 0, kf[p].x, kf[p].y); mma16(c[(p & 1) * 2 + 1], qa[p].z, 0, qa[p].w, 0, kf[p].z, kf[p].w); }
      float a = rbf(rbf((c[0][0] + c[1][0]) + (c[2][0] + c[3][0])) * scale) * l2e, b = rbf(rbf((c[0][1] + c[1][1]) + (c[2][1] + c[3][1])) * scale) * l2e;
      asm volatile("st.shared.v2.f32 [%0], {%1,%2};" ::"r"(sb + R_S + g * 160 + (8 * warp + 2 * t) * 4), "f"(a), "f"(b) : "memory");
    }
    TR(10);
    bar_sync(10, 128);
    float sv[8], pm[8];
    #pragma unroll
    for (int i = 0; i < 4; i++) asm volatile("ld.shared.v2.f32 {%0,%1}, [%2];" : "=f"(sv[2*i]), "=f"(sv[2*i+1]) : "r"(sb + R_S + g * 160 + (8 * i + 2 * t) * 4) : "memory");
    float mx = fmaxf(fmaxf(fmaxf(sv[0], sv[1]), fmaxf(sv[2], sv[3])), fmaxf(fmaxf(sv[4], sv[5]), fmaxf(sv[6], sv[7])));
    mx = fmaxf(mx, __shfl_xor_sync(~0u, mx, 1)); mx = fmaxf(mx, __shfl_xor_sync(~0u, mx, 2));
    uint32_t P[5];
    #pragma unroll
    for (int i = 0; i < 4; i++) P[i] = pack2(ex2(sv[2*i] - mx), ex2(sv[2*i+1] - mx));
    #pragma unroll
    for (int i = 0; i < 4; i++) { c[i][0] = c[i][1] = c[i][2] = c[i][3] = 0.f; }
    #pragma unroll
    for (int kk = 0; kk < 2; kk++) {
      mma16(c[0], P[2*kk], 0, P[2*kk+1], 0, vf[2*kk][0], vf[2*kk][1]); mma16(c[1], P[2*kk], 0, P[2*kk+1], 0, vf[2*kk][2], vf[2*kk][3]);
      mma16(c[2], P[2*kk], 0, P[2*kk+1], 0, vf[2*kk+1][0], vf[2*kk+1][1]); mma16(c[3], P[2*kk], 0, P[2*kk+1], 0, vf[2*kk+1][2], vf[2*kk+1][3]);
    }
    float sum = 0.f;
    #pragma unroll
    for (int i = 0; i < 4; i++) sum += __uint_as_float(P[i] << 16) + __uint_as_float(P[i] & 0xffff0000u);
    TR(11);
    bar_sync(2, 256);
    #pragma unroll
    for (int i = 0; i < 4; i++) asm volatile("ld.shared.v2.f32 {%0,%1}, [%2];" : "=f"(pm[2*i]), "=f"(pm[2*i+1]) : "r"(sb + R_SM + i * 256 + lane * 8) : "memory");
    const float s8 = rbf(rbf((pm[0] + pm[2]) + (pm[4] + pm[6])) * scale) * l2e, s9 = rbf(rbf((pm[1] + pm[3]) + (pm[5] + pm[7])) * scale) * l2e;
    float mg = fmaxf(mx, fmaxf(s8, s9));
    mg = fmaxf(mg, __shfl_xor_sync(~0u, mg, 1)); mg = fmaxf(mg, __shfl_xor_sync(~0u, mg, 2));
    const float fs = ex2(mx - mg);
    P[4] = pack2(ex2(s8 - mg), ex2(s9 - mg));
    #pragma unroll
    for (int i = 0; i < 4; i++) { c[i][0] *= fs; c[i][1] *= fs; }
    sum = fmaf(sum, fs, __uint_as_float(P[4] << 16) + __uint_as_float(P[4] & 0xffff0000u));
    sum += __shfl_xor_sync(~0u, sum, 1); sum += __shfl_xor_sync(~0u, sum, 2);
    float inv; asm("rcp.approx.ftz.f32 %0, %1;" : "=f"(inv) : "f"(sum));
    TR(6);
    bar_sync(3, 256);
    { uint32_t r[4]; ldsm4t(r, sb + R_VT + (s & 1) * VT_SZ + (32 + (lane & 7)) * 272 + (4 * warp + (lane >> 3)) * 16);
      #pragma unroll
      for (int i = 0; i < 4; i++) mma8(c[i], P[4], 0, r[i]); }
    asm volatile("stmatrix.sync.aligned.m8n8.x4.shared.b16 [%0], {%1,%2,%3,%4};" ::"r"(sb + R_O + so),
      "r"(pack2(c[0][0] * inv, c[0][1] * inv)), "r"(pack2(c[1][0] * inv, c[1][1] * inv)), "r"(pack2(c[2][0] * inv, c[2][1] * inv)), "r"(pack2(c[3][0] * inv, c[3][1] * inv)) : "memory");
    bar_arrive(7, 256);
    TR(7);
    bar_sync(8, 384);
    long long t0 = clock64();
    #pragma unroll
    for (int i = 0; i < 16; i++) { uint4 v = lds128(sb + R_WQ + ((warp * 16 + i) * 32 + lane) * 16); A[1][i][0] = v.x; A[1][i][1] = v.y; A[1][i][2] = v.z; A[1][i][3] = v.w; }
    while (clock64() - t0 < PDELAY);
  }
}

constexpr int I_M1 = 512, I_Q = 624, I_M2 = 880, I_AT = 1008, I_G = I_AT + 32, GSZ = 56, I_END = I_G + 15 * GSZ + 24;
constexpr int B_STG = 4 * 49152, B_BAR = B_STG + 8 * 2304;
struct Item { int type, rb, nt, ks; };
__device__ __forceinline__ Item decode(int it) {
  Item r; r.ks = 0;
  if (it < I_M1) { r.type = 0; r.rb = it >> 5; r.nt = it & 31; }
  else if (it < I_Q) { int i = it - I_M1; r.type = 1; r.rb = i / 7; r.nt = i % 7; }
  else if (it < I_M2) { int i = it - I_Q; r.type = 0; r.rb = i >> 4; r.nt = 32 + (i & 15); }
  else if (it < I_AT) { int i = it - I_M2; r.type = 2; r.rb = i >> 3; r.nt = (i >> 2) & 1; r.ks = i & 3; }
  else if (it < I_G) { r.type = 3; r.rb = 0; r.nt = it - I_AT; }
  else {
    int i = it - I_G, gi = i / GSZ, q = i % GSZ; if (gi == 15) q += 32;
    if (q < 32) { r.type = 3; r.rb = gi + 1; r.nt = q; }
    else if (q < 48) { r.type = 4; r.rb = gi; r.nt = (q - 32) >> 3; r.ks = (q - 32) & 7; }
    else { r.type = 5; r.rb = gi; r.nt = q - 48; } }
  return r;
}
__device__ __forceinline__ float gelu_t(float x) { float u = 0.7978845608028654f * (x + 0.044715f * x * x * x); float th; asm("tanh.approx.f32 %0, %1;" : "=f"(th) : "f"(u)); float hx = 0.5f * x; return fmaf(hx, th, hx); }

__device__ __forceinline__ void bulk(uint32_t sb, const Maps& mp, const bf16* __restrict__ x, const bf16* __restrict__ b1, const bf16* __restrict__ b2, bf16* __restrict__ out) {
  const int tid = threadIdx.x, warp = tid >> 5, lane = tid & 31, g = lane >> 2, t = lane & 3;
  const int bid = blockIdx.x - NREC;
  const uint32_t full = sb + B_BAR, empty = sb + B_BAR + 32, ifull = sb + B_BAR + 64, iempty = sb + B_BAR + 80;
  volatile int* ring = (volatile int*)(__cvta_shared_to_generic(sb + B_BAR + 96));
  if (warp >= 8) {
    asm volatile("setmaxnreg.dec.sync.aligned.u32 40;");
    if (tid == 256) {
      uint32_t st = 0, ph = 0;
      for (int n = 0;; n++) {
        int it = n == 0 ? bid : NBULK + atomicAdd(&g_fl.next, 1);
        Item I = decode(it);
        if (it < I_END) {
          if (I.type == 5) { wait_flag(&g_fl.s[I.rb][0], 16); wait_flag(&g_fl.z[I.rb][0], 8); }
          else if (I.type == 3) { wait_flag(&g_fl.prog[I.rb][I.nt], 32); wait_flag(&g_fl.tile[I.rb][I.nt >> 1], 1); wait_flag(&g_fl.tile[I.rb][16 + (I.nt >> 1)], 1); wait_flag(&g_fl.tile[I.rb][32 + (I.nt >> 1)], 1); fence_async(); }
          else if (I.type == 2) { wait_flag(&g_fl.hid[I.rb], 7); fence_async(); }
          else if (I.type == 4) { wait_flag(&g_fl.o[I.rb][I.ks], 4); fence_async(); }
        }
        mbar_wait(iempty + (n & 1) * 8, ((n >> 1) & 1) ^ 1);
        ring[n & 1] = it; mbar_arrive(ifull + (n & 1) * 8);
        if (it >= I_END) break;
        if (I.type == 5) continue;
        if (I.type == 3) {
          for (int m = 0; m < 3; m++) {
            mbar_wait(empty + st * 8, ph ^ 1);
            mbar_expect(full + st * 8, 32768);
            int col = (m == 0 ? 8192 : (m == 1 ? 0 : 4096)) + I.nt * 128;
            tma2d(sb + st * 49152, &mp.qkv, col, I.rb * 128, full + st * 8);
            tma2d(sb + st * 49152 + 16384, &mp.qkv, col + 64, I.rb * 128, full + st * 8);
            if (++st == 4) { st = 0; ph ^= 1; }
          }
          continue;
        }
        const CUtensorMap *ma, *mb; int nkb = 8, kb0 = 0, n0;
        if (I.type == 0) { ma = &mp.xn; mb = I.nt < 16 ? &mp.wk : (I.nt < 32 ? &mp.wv : &mp.wq); n0 = (I.nt & 15) * 256; }
        else if (I.type == 1) { ma = &mp.y; mb = &mp.w1; n0 = I.nt * 256; }
        else if (I.type == 2) { ma = &mp.hid; mb = &mp.w2; n0 = I.nt * 256; nkb = 7; kb0 = I.ks * 7; }
        else { ma = &mp.o; mb = &mp.wo; n0 = I.nt * 256; kb0 = I.ks * 8; }
        for (int kb = kb0; kb < kb0 + nkb; kb++) {
          mbar_wait(empty + st * 8, ph ^ 1);
          mbar_expect(full + st * 8, 49152);
          uint32_t sa = sb + st * 49152;
          tma2d(sa, ma, kb * 64, I.rb * 128, full + st * 8);
          #pragma unroll
          for (int q = 0; q < 4; q++) tma2d(sa + 16384 + q * 8192, mb, n0 + q * 64, kb * 64, full + st * 8);
          if (++st == 4) { st = 0; ph ^= 1; }
        }
      }
    } else if (warp == 9) {
      for (int n = 0;; n++) {
        mbar_wait(ifull + (n & 1) * 8, (n >> 1) & 1);
        int it = ring[n & 1];
        if (it >= I_END) break;
        Item I = decode(it);
        bar_sync(6 + (n & 1), 288);
        if (lane == 0) {
          if (I.type != 5) {
            fence_async(); __threadfence();
            int* f = I.type == 0 ? &g_fl.tile[I.rb][I.nt] : I.type == 1 ? &g_fl.hid[I.rb] : I.type == 2 ? &g_fl.z[I.rb][0] : I.type == 3 ? &g_fl.o[I.rb][I.nt >> 2] : &g_fl.s[I.rb][0];
            atomicAdd(f, 1);
          }
          mbar_arrive(iempty + (n & 1) * 8);
        }
      }
    }
    return;
  }
  asm volatile("setmaxnreg.inc.sync.aligned.u32 232;");
  const int wg = warp >> 2;
  const uint32_t stg = sb + B_STG + warp * 2304;
  const int lm = lane >> 3, lr = lane & 7;
  uint32_t st = 0, ph = 0;
  float d[128];
  #pragma unroll 1
  for (int n = 0;; n++) {
    mbar_wait(ifull + (n & 1) * 8, (n >> 1) & 1);
    const int it = ring[n & 1];
    __syncwarp(); if (lane == 0) mbar_arrive(iempty + (n & 1) * 8);
    if (it >= I_END) break;
    Item I = decode(it);
    const int row0 = I.rb * 128 + warp * 16;
    TB(0);
    if (I.type == 5) {
      #pragma unroll
      for (int i = 0; i < 4; i++) {
        size_t off = (size_t)(I.rb * 128 + I.nt * 16 + warp * 2 + (i >> 1)) * DM + (i & 1) * 256 + lane * 8;
        float4 s0 = __ldcg((const float4*)(g_s + off)), s1 = __ldcg((const float4*)(g_s + off + 4));
        float4 z0 = __ldcg((const float4*)(g_z + off)), z1 = __ldcg((const float4*)(g_z + off + 4));
        uint4 xv = *(const uint4*)(x + off), bv = *(const uint4*)(b2 + (i & 1) * 256 + lane * 8);
        float sa[8] = {s0.x, s0.y, s0.z, s0.w, s1.x, s1.y, s1.z, s1.w}, za[8] = {z0.x, z0.y, z0.z, z0.w, z1.x, z1.y, z1.z, z1.w}, r[8];
        #pragma unroll
        for (int e = 0; e < 8; e++) { float xx = __bfloat162float(((const bf16*)&xv)[e]), bb = __bfloat162float(((const bf16*)&bv)[e]);
          float u = rbf(rbf(za[e]) + bb); float gg = rbf(__fdividef(u, 1.f + __expf(-u))); r[e] = xx + rbf(rbf(sa[e]) * gg); }
        *(uint4*)(out + off) = make_uint4(pack2(r[0], r[1]), pack2(r[2], r[3]), pack2(r[4], r[5]), pack2(r[6], r[7]));
      }
      bar_arrive(6 + (n & 1), 288);
      continue;
    }
    if (I.type == 3) {
      const int h = I.nt, seg = warp >> 1, half = warp & 1, step = I.rb * 4 + seg;
      uint32_t kmr[16], vmr[16];
      { const uint32_t* km = (const uint32_t*)(g_km + ((size_t)(step * 32 + h)) * 1024) + g * 64 + t;
        const uint32_t* vm = (const uint32_t*)(g_vmT + ((size_t)(step * 32 + h)) * 1024) + g * 4 + t;
        #pragma unroll
        for (int i = 0; i < 16; i++) { kmr[i] = __ldcg(km + i * 4); vmr[i] = __ldcg(vm + i * 32); } }
      uint32_t sQ = sb + st * 49152; mbar_wait(full + st * 8, ph); uint32_t eQ = empty + st * 8; if (++st == 4) { st = 0; ph ^= 1; }
      uint32_t sK = sb + st * 49152; mbar_wait(full + st * 8, ph); uint32_t eK = empty + st * 8; if (++st == 4) { st = 0; ph ^= 1; }
      float sc[5][4];
      #pragma unroll
      for (int i = 0; i < 5; i++) { sc[i][0] = sc[i][1] = sc[i][2] = sc[i][3] = 0.f; }
      #pragma unroll
      for (int ks = 0; ks < 8; ks++) {
        uint32_t a[4]; { int r = warp * 16 + 8 * (lm & 1) + lr, c8 = 2 * ks + (lm >> 1); ldsm4(a, sQ + (c8 >> 3) * 16384 + r * 128 + (((c8 & 7) ^ (r & 7)) << 4)); }
        #pragma unroll
        for (int np = 0; np < 2; np++) {
          if (np == 1 && half == 0) continue;
          uint32_t b[4]; int r = seg * 32 + 16 * np + 8 * (lm >> 1) + lr, c8 = 2 * ks + (lm & 1);
          ldsm4(b, sK + (c8 >> 3) * 16384 + r * 128 + (((c8 & 7) ^ (r & 7)) << 4));
          mma16(sc[2*np], a[0], a[1], a[2], a[3], b[0], b[1]); mma16(sc[2*np+1], a[0], a[1], a[2], a[3], b[2], b[3]);
        }
        mma16(sc[4], a[0], a[1], a[2], a[3], kmr[2*ks], kmr[2*ks+1]);
      }
      __syncwarp(); if (lane == 0) { mbar_arrive(eQ); mbar_arrive(eK); }
      const float scale = 0.08838834764831845f;
      uint32_t P[5][2];
      #pragma unroll
      for (int rr = 0; rr < 2; rr++) {
        const int qi = 16 * half + g + 8 * rr;
        float mx = -3.0e38f;
        #pragma unroll
        for (int i = 0; i < 5; i++)
          #pragma unroll
          for (int e = 0; e < 2; e++) { float v = rbf(rbf(sc[i][2*rr+e]) * scale); if (i < 4 && 8 * i + 2 * t + e > qi) v = -1.0e9f; sc[i][2*rr+e] = v; mx = fmaxf(mx, v); }
        mx = fmaxf(mx, __shfl_xor_sync(~0u, mx, 1)); mx = fmaxf(mx, __shfl_xor_sync(~0u, mx, 2));
        float sum = 0;
        #pragma unroll
        for (int i = 0; i < 5; i++)
          #pragma unroll
          for (int e = 0; e < 2; e++) { float v = __expf(sc[i][2*rr+e] - mx); sc[i][2*rr+e] = v; sum += v; }
        sum += __shfl_xor_sync(~0u, sum, 1); sum += __shfl_xor_sync(~0u, sum, 2);
        float inv = __fdividef(1.f, sum);
        #pragma unroll
        for (int i = 0; i < 5; i++) P[i][rr] = pack2(sc[i][2*rr] * inv, sc[i][2*rr+1] * inv);
      }
      uint32_t sV = sb + st * 49152; mbar_wait(full + st * 8, ph); uint32_t eV = empty + st * 8; if (++st == 4) { st = 0; ph ^= 1; }
      #pragma unroll
      for (int i = 0; i < 64; i++) d[i] = 0.f;
      #pragma unroll
      for (int n2 = 0; n2 < 8; n2++) {
        #pragma unroll
        for (int kk = 0; kk < 2; kk++) {
          if (kk == 1 && half == 0) continue;
          uint32_t b[4]; int r = seg * 32 + 16 * kk + 8 * (lm & 1) + lr, c8 = 2 * n2 + (lm >> 1);
          ldsm4t(b, sV + (c8 >> 3) * 16384 + r * 128 + (((c8 & 7) ^ (r & 7)) << 4));
          mma16(d + 8 * n2, P[2*kk][0], P[2*kk][1], P[2*kk+1][0], P[2*kk+1][1], b[0], b[1]);
          mma16(d + 8 * n2 + 4, P[2*kk][0], P[2*kk][1], P[2*kk+1][0], P[2*kk+1][1], b[2], b[3]);
        }
        mma8(d + 8 * n2, P[4][0], P[4][1], vmr[2*n2]); mma8(d + 8 * n2 + 4, P[4][0], P[4][1], vmr[2*n2+1]);
      }
      __syncwarp(); if (lane == 0) mbar_arrive(eV);
      #pragma unroll
      for (int ch = 0; ch < 2; ch++) {
        #pragma unroll
        for (int i = 0; i < 8; i++) { const float* a = d + ch * 32 + i * 4;
          sts32(stg + g * 144 + i * 16 + t * 4, pack2(a[0], a[1])); sts32(stg + (g + 8) * 144 + i * 16 + t * 4, pack2(a[2], a[3])); }
        __syncwarp();
        #pragma unroll
        for (int i = 0; i < 4; i++) { int r = i * 4 + lm; uint4 v = lds128(stg + r * 144 + lr * 16);
          *(uint4*)(g_o + (size_t)(row0 + r) * 4096 + h * 128 + ch * 64 + lr * 8) = v; }
        __syncwarp();
      }
      bar_arrive(6 + (n & 1), 288);
      continue;
    }
    const int nkb = I.type == 2 ? 7 : 8;
    uint32_t prev = 0;
    for (int kb = 0; kb < nkb; kb++) {
      mbar_wait(full + st * 8, ph);
      uint32_t sa = sb + st * 49152;
      asm volatile("wgmma.fence.sync.aligned;" ::: "memory");
      #pragma unroll
      for (int k = 0; k < 4; k++)
        wgmma256(d, mkdesc(sa + wg * 8192 + k * 32, 16, 1024), mkdesc(sa + 16384 + k * 2048, 8192, 1024), (kb | k) != 0);
      asm volatile("wgmma.commit_group.sync.aligned;" ::: "memory");
      if (kb > 0) { asm volatile("wgmma.wait_group.sync.aligned 1;" ::: "memory"); if (lane == 0) mbar_arrive(prev); }
      prev = empty + st * 8;
      if (++st == 4) { st = 0; ph ^= 1; }
    }
    asm volatile("wgmma.wait_group.sync.aligned 0;" ::: "memory");
    if (lane == 0) mbar_arrive(prev);
    TB(1);
    if (I.type <= 1) {
      bf16* dst; int ld;
      if (I.type == 0) { dst = g_qkv + (size_t)row0 * QW + I.nt * 256; ld = QW; } else { dst = g_hid + (size_t)row0 * FF + I.nt * 256; ld = FF; }
      #pragma unroll
      for (int ch = 0; ch < 4; ch++) {
        #pragma unroll
        for (int i = 0; i < 8; i++) { float* a = d + ch * 32 + i * 4;
          if (I.type == 1) { float2 bb = __bfloat1622float2(*(const __nv_bfloat162*)(b1 + I.nt * 256 + ch * 64 + i * 8 + 2 * t));
            a[0] = gelu_t(rbf(rbf(a[0]) + bb.x)); a[1] = gelu_t(rbf(rbf(a[1]) + bb.y)); a[2] = gelu_t(rbf(rbf(a[2]) + bb.x)); a[3] = gelu_t(rbf(rbf(a[3]) + bb.y)); }
          sts32(stg + g * 144 + i * 16 + t * 4, pack2(a[0], a[1])); sts32(stg + (g + 8) * 144 + i * 16 + t * 4, pack2(a[2], a[3])); }
        __syncwarp();
        #pragma unroll
        for (int i = 0; i < 4; i++) { int r = i * 4 + lm; uint4 v = lds128(stg + r * 144 + lr * 16); *(uint4*)(dst + (size_t)r * ld + ch * 64 + lr * 8) = v; }
        __syncwarp();
      }
    } else {
      float* dst = (I.type == 2 ? g_z : g_s) + (size_t)(row0 + g) * DM + I.nt * 256 + 2 * t;
      #pragma unroll
      for (int i = 0; i < 32; i++) {
        asm volatile("red.relaxed.gpu.global.add.v2.f32 [%0], {%1,%2};" ::"l"(dst + i * 8), "f"(d[4*i]), "f"(d[4*i+1]) : "memory");
        asm volatile("red.relaxed.gpu.global.add.v2.f32 [%0], {%1,%2};" ::"l"(dst + 8 * DM + i * 8), "f"(d[4*i+2]), "f"(d[4*i+3]) : "memory");
      }
    }
    bar_arrive(6 + (n & 1), 288);
  }
}

__global__ void __cluster_dims__(2, 1, 1) __launch_bounds__(384, 1)
main_kernel(const __grid_constant__ Maps mp, const bf16* x, const bf16* Wq, const bf16* Wk, const bf16* Wv, const bf16* Wo, const bf16* b1, const bf16* b2, bf16* out) {
  const uint32_t sb = smem_u32(smem_raw);
  if (sb & 1023) __trap();
  if (threadIdx.x == 0) {
    if (blockIdx.x < NREC) { mbar_init(sb + R_BAR, 1); mbar_init(sb + R_BAR + 8, 1); mbar_init(sb + R_BAR + 16, 1); }
    else { for (int i = 0; i < 4; i++) { mbar_init(sb + B_BAR + i * 8, 1); mbar_init(sb + B_BAR + 32 + i * 8, 8); }
      for (int i = 0; i < 2; i++) { mbar_init(sb + B_BAR + 64 + i * 8, 1); mbar_init(sb + B_BAR + 80 + i * 8, 9); } }
    asm volatile("fence.mbarrier_init.release.cluster;" ::: "memory");
  }
  asm volatile("barrier.cluster.arrive.release.aligned; barrier.cluster.wait.acquire.aligned;" ::: "memory");
  if (blockIdx.x < NREC) recurrence(sb, Wq, Wk, Wv, Wo);
  else bulk(sb, mp, x, b1, b2, out);
}

typedef CUresult (*EncFn)(CUtensorMap*, CUtensorMapDataType, cuuint32_t, void*, const cuuint64_t*, const cuuint64_t*, const cuuint32_t*, const cuuint32_t*, CUtensorMapInterleave, CUtensorMapSwizzle, CUtensorMapL2promotion, CUtensorMapFloatOOBfill);
static void mk(EncFn f, CUtensorMap* m, const void* p, uint64_t rows, uint64_t cols, uint32_t boxr) {
  cuuint64_t dims[2] = {cols, rows}, str[1] = {cols * 2}; cuuint32_t box[2] = {64, boxr}, es[2] = {1, 1};
  f(m, CU_TENSOR_MAP_DATA_TYPE_BFLOAT16, 2, (void*)p, dims, str, box, es, CU_TENSOR_MAP_INTERLEAVE_NONE, CU_TENSOR_MAP_SWIZZLE_128B, CU_TENSOR_MAP_L2_PROMOTION_L2_256B, CU_TENSOR_MAP_FLOAT_OOB_FILL_NONE);
}
extern "C" void kernel_launch(void* const* d_in, const int* in_sizes, int n_in, void* d_out, int out_size) {
  const bf16 *x = (const bf16*)d_in[0], *mem0 = (const bf16*)d_in[1], *Wq = (const bf16*)d_in[2], *Wk = (const bf16*)d_in[3], *Wv = (const bf16*)d_in[4], *Wo = (const bf16*)d_in[5];
  const bf16 *w1 = (const bf16*)d_in[8], *b1 = (const bf16*)d_in[9], *w2 = (const bf16*)d_in[10], *b2 = (const bf16*)d_in[11];
  void* fn = nullptr; cudaDriverEntryPointQueryResult qr;
  cudaGetDriverEntryPoint("cuTensorMapEncodeTiled", &fn, cudaEnableDefault, &qr);
  EncFn f = (EncFn)fn;
  void *pxn, *py, *ph, *po, *pq;
  cudaGetSymbolAddress(&pxn, g_xn); cudaGetSymbolAddress(&py, g_y); cudaGetSymbolAddress(&ph, g_hid); cudaGetSymbolAddress(&po, g_o); cudaGetSymbolAddress(&pq, g_qkv);
  Maps mp;
  mk(f, &mp.xn, pxn, SEQ, DM, 128); mk(f, &mp.y, py, SEQ, DM, 128); mk(f, &mp.hid, ph, SEQ, FF, 128); mk(f, &mp.o, po, SEQ, 4096, 128); mk(f, &mp.qkv, pq, SEQ, QW, 128);
  mk(f, &mp.wk, Wk, DM, 4096, 64); mk(f, &mp.wv, Wv, DM, 4096, 64); mk(f, &mp.wq, Wq, DM, 4096, 64);
  mk(f, &mp.w1, w1, DM, FF, 64); mk(f, &mp.w2, w2, FF, DM, 64); mk(f, &mp.wo, Wo, 4096, DM, 64);
  cudaFuncSetAttribute(main_kernel, cudaFuncAttributeMaxDynamicSharedMemorySize, SMEM_BYTES);
  prologue_kernel<<<256, 256, 0, cudaStreamPerThread>>>(x, mem0);
  main_kernel<<<NCTA, 384, SMEM_BYTES, cudaStreamPerThread>>>(mp, x, Wq, Wk, Wv, Wo, b1, b2, (bf16*)d_out);
}
```

```cpp
#include <cuda_runtime.h>
#include <cuda_bf16.h>
#include <cuda.h>
#include <stdint.h>

typedef __nv_bfloat16 bf16;
constexpr int SEQ = 2048, DM = 512, FF = 1792, QW = 12288, NSTEP = 64;
constexpr int NREC = 64, NBULK = 68, NCTA = 132;
constexpr int SPIN_LIMIT = 1 << 22;
#define THR 2
#define PDELAY 500

__device__ bf16 g_xn[SEQ * DM];
__device__ bf16 g_y[SEQ * DM];
__device__ bf16 g_qkv[(size_t)SEQ * QW];
__device__ bf16 g_hid[SEQ * FF];
__device__ bf16 g_o[(size_t)SEQ * 4096];
__device__ float g_z[SEQ * DM];
__device__ float g_s[SEQ * DM];
__device__ float4 g_acc[NSTEP][2][768];
__device__ bf16 g_km[NSTEP * 32 * 8 * 128];
__device__ bf16 g_vmT[NSTEP * 32 * 128 * 8];
struct Flags { int tile[16][48]; int hid[16]; int z[16][2]; int o[16][8]; int s[16][2]; int prog[16][32]; int next; };
__device__ Flags g_fl;

#define TR(i)
#define TB(i)
struct Maps { CUtensorMap xn, y, hid, o, qkv, wk, wv, wq, w1, w2, wo; };

extern __shared__ __align__(1024) uint8_t smem_raw[];
__device__ __forceinline__ uint4 ldc(uint32_t off) { return *(const uint4*)(smem_raw + off); }
__device__ __forceinline__ uint32_t smem_u32(const void* p) { return (uint32_t)__cvta_generic_to_shared(p); }
__device__ __forceinline__ int otid() { int t; asm volatile("mov.u32 %0, %%tid.x;" : "=r"(t)); return t; }
__device__ __forceinline__ uint32_t mapa(uint32_t a, uint32_t r) { uint32_t o; asm volatile("mapa.shared::cluster.u32 %0, %1, %2;" : "=r"(o) : "r"(a), "r"(r)); return o; }
__device__ __forceinline__ void st_async_v4(uint32_t addr, float a, float b, float c, float d, uint32_t mbar) {
  asm volatile("st.async.weak.shared::cluster.mbarrier::complete_tx::bytes.v4.b32 [%0], {%1,%2,%3,%4}, [%5];" ::"r"(addr), "r"(__float_as_uint(a)), "r"(__float_as_uint(b)), "r"(__float_as_uint(c)), "r"(__float_as_uint(d)), "r"(mbar) : "memory"); }
__device__ __forceinline__ void mbar_init(uint32_t m, int c) { asm volatile("mbarrier.init.shared::cta.b64 [%0], %1;" ::"r"(m), "r"(c) : "memory"); }
__device__ __forceinline__ void mbar_expect(uint32_t m, int bytes) { asm volatile("mbarrier.arrive.expect_tx.shared::cta.b64 _, [%0], %1;" ::"r"(m), "r"(bytes) : "memory"); }
__device__ __forceinline__ void mbar_arrive(uint32_t m) { asm volatile("mbarrier.arrive.shared::cta.b64 _, [%0];" ::"r"(m) : "memory"); }
__device__ __forceinline__ void mbar_wait(uint32_t m, uint32_t parity) {
  uint32_t ok; int it = 0;
  do { asm volatile("{.reg .pred p; mbarrier.try_wait.parity.shared::cta.b64 p, [%1], %2; selp.u32 %0,1,0,p;}" : "=r"(ok) : "r"(m), "r"(parity) : "memory"); } while (!ok && ++it < SPIN_LIMIT); }
__device__ __forceinline__ void mbar_spin(uint32_t m, uint32_t parity) {
  uint32_t ok; int it = 0;
  do { asm volatile("{.reg .pred p; mbarrier.test_wait.parity.shared::cta.b64 p, [%1], %2; selp.u32 %0,1,0,p;}" : "=r"(ok) : "r"(m), "r"(parity) : "memory"); } while (!ok && ++it < SPIN_LIMIT); }
__device__ __forceinline__ void bar_sync(int id, int n) { asm volatile("bar.sync %0, %1;" ::"r"(id), "r"(n) : "memory"); }
__device__ __forceinline__ void bar_arrive(int id, int n) { asm volatile("bar.arrive %0, %1;" ::"r"(id), "r"(n) : "memory"); }
__device__ __forceinline__ int ld_acq(const int* p) { int v; asm volatile("ld.acquire.gpu.global.s32 %0, [%1];" : "=r"(v) : "l"(p) : "memory"); return v; }
__device__ __forceinline__ void wait_flag(const int* p, int target) { int it = 0; while (ld_acq(p) < target && ++it < SPIN_LIMIT) { __nanosleep(40); } }
__device__ __forceinline__ void fence_async() { asm volatile("fence.proxy.async.global;" ::: "memory"); }
__device__ __forceinline__ uint4 lds128(uint32_t a) { uint4 v; asm volatile("ld.shared.v4.u32 {%0,%1,%2,%3}, [%4];" : "=r"(v.x), "=r"(v.y), "=r"(v.z), "=r"(v.w) : "r"(a) : "memory"); return v; }
__device__ __forceinline__ void sts128(uint32_t a, uint4 v) { asm volatile("st.shared.v4.u32 [%0], {%1,%2,%3,%4};" ::"r"(a), "r"(v.x), "r"(v.y), "r"(v.z), "r"(v.w) : "memory"); }
__device__ __forceinline__ void sts32(uint32_t a, uint32_t v) { asm volatile("st.shared.u32 [%0], %1;" ::"r"(a), "r"(v) : "memory"); }
__device__ __forceinline__ void sts16(uint32_t a, float f) { unsigned short h = __bfloat16_as_ushort(__float2bfloat16(f)); asm volatile("st.shared.u16 [%0], %1;" ::"r"(a), "h"(h) : "memory"); }
__device__ __forceinline__ void ldsm4(uint32_t* r, uint32_t a) { asm volatile("ldmatrix.sync.aligned.m8n8.x4.shared.b16 {%0,%1,%2,%3}, [%4];" : "=r"(r[0]), "=r"(r[1]), "=r"(r[2]), "=r"(r[3]) : "r"(a) : "memory"); }
__device__ __forceinline__ void ldsm4t(uint32_t* r, uint32_t a) { asm volatile("ldmatrix.sync.aligned.m8n8.x4.trans.shared.b16 {%0,%1,%2,%3}, [%4];" : "=r"(r[0]), "=r"(r[1]), "=r"(r[2]), "=r"(r[3]) : "r"(a) : "memory"); }
__device__ __forceinline__ void mma16(float* c, uint32_t a0, uint32_t a1, uint32_t a2, uint32_t a3, uint32_t b0, uint32_t b1) {
  asm("mma.sync.aligned.m16n8k16.row.col.f32.bf16.bf16.f32 {%0,%1,%2,%3}, {%4,%5,%6,%7}, {%8,%9}, {%0,%1,%2,%3};" : "+f"(c[0]), "+f"(c[1]), "+f"(c[2]), "+f"(c[3]) : "r"(a0), "r"(a1), "r"(a2), "r"(a3), "r"(b0), "r"(b1)); }
__device__ __forceinline__ void mma8(float* c, uint32_t a0, uint32_t a1, uint32_t b0) {
  asm("mma.sync.aligned.m16n8k8.row.col.f32.bf16.bf16.f32 {%0,%1,%2,%3}, {%4,%5}, {%6}, {%0,%1,%2,%3};" : "+f"(c[0]), "+f"(c[1]), "+f"(c[2]), "+f"(c[3]) : "r"(a0), "r"(a1), "r"(b0)); }
__device__ __forceinline__ uint32_t pack2(float a, float b) { __nv_bfloat162 h = __floats2bfloat162_rn(a, b); return *(uint32_t*)&h; }
__device__ __forceinline__ float rbf(float x) { uint32_t r; asm("cvt.rn.bf16x2.f32 %0, %1, %2;" : "=r"(r) : "f"(x), "f"(0.f)); return __uint_as_float(r); }
__device__ __forceinline__ void cp16(uint32_t d, const void* s) { asm volatile("cp.async.cg.shared.global [%0], [%1], 16;" ::"r"(d), "l"(s) : "memory"); }
__device__ __forceinline__ void tma2d(uint32_t dst, const CUtensorMap* m, int c0, int c1, uint32_t mbar) {
  asm volatile("cp.async.bulk.tensor.2d.shared::cluster.global.mbarrier::complete_tx::bytes [%0], [%1, {%2,%3}], [%4];" ::"r"(dst), "l"(m), "r"(c0), "r"(c1), "r"(mbar) : "memory"); }
__device__ __forceinline__ uint64_t mkdesc(uint32_t addr, uint32_t lbo, uint32_t sbo) {
  return (uint64_t)((addr & 0x3FFFF) >> 4) | ((uint64_t)(lbo >> 4) << 16) | ((uint64_t)(sbo >> 4) << 32) | (1ull << 62); }

#define R8(i) "+f"(d[i]), "+f"(d[i+1]), "+f"(d[i+2]), "+f"(d[i+3]), "+f"(d[i+4]), "+f"(d[i+5]), "+f"(d[i+6]), "+f"(d[i+7])
__device__ __forceinline__ void wgmma256(float* d, uint64_t da, uint64_t db, int acc) {
  asm volatile("{.reg .pred p; setp.ne.b32 p, %130, 0;\n"
    "wgmma.mma_async.sync.aligned.m64n256k16.f32.bf16.bf16 {"
    "%0,%1,%2,%3,%4,%5,%6,%7,%8,%9,%10,%11,%12,%13,%14,%15,%16,%17,%18,%19,%20,%21,%22,%23,%24,%25,%26,%27,%28,%29,%30,%31,"
    "%32,%33,%34,%35,%36,%37,%38,%39,%40,%41,%42,%43,%44,%45,%46,%47,%48,%49,%50,%51,%52,%53,%54,%55,%56,%57,%58,%59,%60,%61,%62,%63,"
    "%64,%65,%66,%67,%68,%69,%70,%71,%72,%73,%74,%75,%76,%77,%78,%79,%80,%81,%82,%83,%84,%85,%86,%87,%88,%89,%90,%91,%92,%93,%94,%95,"
    "%96,%97,%98,%99,%100,%101,%102,%103,%104,%105,%106,%107,%108,%109,%110,%111,%112,%113,%114,%115,%116,%117,%118,%119,%120,%121,%122,%123,%124,%125,%126,%127"
    "}, %128, %129, p, 1, 1, 0, 1;}"
    : R8(0), R8(8), R8(16), R8(24), R8(32), R8(40), R8(48), R8(56), R8(64), R8(72), R8(80), R8(88), R8(96), R8(104), R8(112), R8(120)
    : "l"(da), "l"(db), "r"(acc)); }

__global__ void __launch_bounds__(256) prologue_kernel(const bf16* __restrict__ x, const bf16* __restrict__ mem0) {
  int tid = threadIdx.x, lane = tid & 31, warp = tid >> 5;
  int row = blockIdx.x * 8 + warp;
  {
    const uint4* src = (const uint4*)(x + (size_t)row * DM);
    uint4 u[2] = { src[lane], src[lane + 32] };
    float v[16];
    #pragma unroll
    for (int i = 0; i < 2; i++) { const __nv_bfloat162* h = (const __nv_bfloat162*)&u[i];
      #pragma unroll
      for (int k = 0; k < 4; k++) { float2 f = __bfloat1622float2(h[k]); v[i * 8 + 2 * k] = f.x; v[i * 8 + 2 * k + 1] = f.y; } }
    #pragma unroll
    for (int pass = 0; pass < 2; pass++) {
      float s = 0;
      #pragma unroll
      for (int i = 0; i < 16; i++) s += v[i];
      #pragma unroll
      for (int o = 16; o; o >>= 1) s += __shfl_xor_sync(~0u, s, o);
      float mf = s * (1.f / DM);
      float q = 0;
      #pragma unroll
      for (int i = 0; i < 16; i++) { float dd = v[i] - mf; q += dd * dd; }
      #pragma unroll
      for (int o = 16; o; o >>= 1) q += __shfl_xor_sync(~0u, q, o);
      float m = rbf(mf), var = rbf(q * (1.f / DM));
      float den = rbf(sqrtf(rbf(var + 1e-5f)));
      #pragma unroll
      for (int i = 0; i < 16; i++) v[i] = rbf(rbf(v[i] - m) / den);
      uint4 o4[2];
      #pragma unroll
      for (int i = 0; i < 2; i++) { o4[i].x = pack2(v[i*8], v[i*8+1]); o4[i].y = pack2(v[i*8+2], v[i*8+3]); o4[i].z = pack2(v[i*8+4], v[i*8+5]); o4[i].w = pack2(v[i*8+6], v[i*8+7]); }
      uint4* dst = (uint4*)((pass ? g_y : g_xn) + (size_t)row * DM);
      dst[lane] = o4[0]; dst[lane + 32] = o4[1];
    }
  }
  int gt = blockIdx.x * 256 + tid;
  float4 z4 = make_float4(0, 0, 0, 0);
  #pragma unroll
  for (int i = 0; i < 4; i++) { ((float4*)g_z)[gt + i * 65536] = z4; ((float4*)g_s)[gt + i * 65536] = z4; }
  for (int i = gt; i < NSTEP * 1536; i += 65536) {
    float4 val = z4;
    if (i < 1536) {
      int j = i / 768, c = i % 768, ci = c >> 8, w = (c & 255) >> 5, l = c & 31, g = l >> 2, t = l & 3;
      float e3[3];
      #pragma unroll
      for (int k = 0; k < 3; k++) { int e = ci * 3 + k; int mt = e >> 2, cc = e & 3;
        e3[k] = e < 8 ? __bfloat162float(mem0[(2 * t + (cc & 1)) * DM + 256 * j + 32 * w + 16 * mt + g + 8 * (cc >> 1)]) : 0.f; }
      val = make_float4(e3[0], e3[1], e3[2], 32.f);
    }
    (&g_acc[0][0][0])[i] = val;
  }
  if (gt < (int)(sizeof(Flags) / 4)) ((int*)&g_fl)[gt] = 0;
}

constexpr int R_WR = 0, R_WO = 65536, R_KT = 131072, KT_SZ = 40 * 256, R_VT = R_KT + 2 * KT_SZ, VT_SZ = 40 * 272,
              R_MEM = R_VT + 2 * VT_SZ, R_Q = R_MEM + 32 * 160, R_O = R_Q + 8 * 256, R_S = R_O + 8 * 256,
              R_SM = R_S + 8 * 40 * 4, R_RQK = R_SM + 1024, R_RV = R_RQK + 8192, R_WQ = R_RV + 4096, R_BAR = 232448 - 64, R_END = R_BAR + 64;
static_assert(R_WQ + 32768 <= R_BAR, "smem");
#define NW0 8
#define VD 0
#define KD 150
#define VCH 2
#define VP 4
__device__ __forceinline__ void wgmma8(float* d, uint64_t da, uint64_t db, int acc) {
  asm volatile("{.reg .pred p; setp.ne.b32 p, %6, 0;\n wgmma.mma_async.sync.aligned.m64n8k16.f32.bf16.bf16 {%0,%1,%2,%3}, %4, %5, p, 1, 1, 0, 0;}"
    : "+f"(d[0]), "+f"(d[1]), "+f"(d[2]), "+f"(d[3]) : "l"(da), "l"(db), "r"(acc)); }
__device__ __forceinline__ void stsm4(uint32_t a, uint32_t r0, uint32_t r1, uint32_t r2, uint32_t r3) { asm volatile("stmatrix.sync.aligned.m8n8.x4.shared.b16 [%0], {%1,%2,%3,%4};" ::"r"(a), "r"(r0), "r"(r1), "r"(r2), "r"(r3) : "memory"); }
__device__ __forceinline__ uint32_t swz(uint32_t r) { return ((r & 1) << 2) | ((r >> 1) & 3); }
__device__ __forceinline__ void stsm4t(uint32_t a, uint32_t r0, uint32_t r1, uint32_t r2, uint32_t r3) { asm volatile("stmatrix.sync.aligned.m8n8.x4.trans.shared.b16 [%0], {%1,%2,%3,%4};" ::"r"(a), "r"(r0), "r"(r1), "r"(r2), "r"(r3) : "memory"); }
__device__ __forceinline__ void stsm2(uint32_t a, uint32_t r0, uint32_t r1) { asm volatile("stmatrix.sync.aligned.m8n8.x2.shared.b16 [%0], {%1,%2};" ::"r"(a), "r"(r0), "r"(r1) : "memory"); }
__device__ __forceinline__ float ex2(float x) { float r; asm("ex2.approx.ftz.f32 %0, %1;" : "=f"(r) : "f"(x)); return r; }
#define REDV4(p, a, b, c) asm volatile("red.relaxed.gpu.global.add.v4.f32 [%0], {%1,%2,%3,%4};" ::"l"(p), "f"(a), "f"(b), "f"(c), "f"(1.0f) : "memory")
constexpr int SMEM_BYTES = 232448;
static_assert(R_END <= SMEM_BYTES, "smem");

__device__ __forceinline__ void recurrence(uint32_t sb, const bf16* __restrict__ Wq, const bf16* __restrict__ Wk, const bf16* __restrict__ Wv, const bf16* __restrict__ Wo) {
  const int tid = threadIdx.x, warp = tid >> 5, lane = tid & 31, g = lane >> 2, t = lane & 3;
  const int h = blockIdx.x >> 1, j = blockIdx.x & 1;
  const uint32_t peer = j ^ 1;
  const uint32_t mQ = sb + R_BAR, mV = sb + R_BAR + 8, mK = sb + R_BAR + 16;
  uint32_t A[2][16][4];
  const uint32_t stA = sb + 65536, stB = stA + 69632;
  const int lm = lane >> 3, lr = lane & 7;
  for (int i = tid; i < 256 * 16; i += 384) { int r = i >> 4, c = i & 15; size_t o = ((size_t)(256 * j + r)) * 4096 + h * 128 + c * 8;
    cp16(stA + r * 272 + c * 16, Wv + o); cp16(stB + r * 272 + c * 16, Wq + o); }
  asm volatile("cp.async.wait_all;" ::: "memory"); __syncthreads();
  if (warp < 4) {
    #pragma unroll
    for (int mt = 0; mt < 2; mt++)
      #pragma unroll
      for (int ks = 0; ks < 16; ks++) {
        int k = 32 * (ks >> 1) + 8 * (lr >> 1) + (lr & 1) + 4 * (ks & 1) + 2 * (lm >> 1);
        ldsm4t(A[mt][ks], stB + k * 272 + (32 * warp + 16 * mt + 8 * (lm & 1)) * 2);
      }
  } else {
    #pragma unroll 4
    for (int i = 0; i < 16; i++) { const int mt = (warp >> 2) - 1, ks = i, k = 32 * (ks >> 1) + 8 * (lr >> 1) + (lr & 1) + 4 * (ks & 1) + 2 * (lm >> 1); uint32_t r[4];
      ldsm4t(r, stA + k * 272 + (32 * (warp & 3) + 16 * mt + 8 * (lm & 1)) * 2);
      sts128(sb + R_WR + (((warp & 3) * 32 + ks * 2 + mt) * 32 + lane) * 16, make_uint4(r[0], r[1], r[2], r[3])); }
  }
  __syncthreads();
  for (int i = tid; i < 256 * 16; i += 384) { int r = i >> 4, c = i & 15; cp16(stA + r * 272 + c * 16, Wk + ((size_t)(256 * j + r)) * 4096 + h * 128 + c * 8);
    r = i >> 5; c = i & 31; cp16(stB + r * 528 + c * 16, Wo + ((size_t)(h * 128 + r)) * DM + 256 * j + c * 8); }
  asm volatile("cp.async.wait_all;" ::: "memory"); __syncthreads();
  if (warp >= 4) {
    #pragma unroll
    for (int mt = 0; mt < 2; mt++)
      #pragma unroll
      for (int ks = 0; ks < 16; ks++) {
        int k = 32 * (ks >> 1) + 8 * (lr >> 1) + (lr & 1) + 4 * (ks & 1) + 2 * (lm >> 1);
        ldsm4t(A[mt][ks], warp < 8 ? stA + k * 272 + (32 * (warp & 3) + 16 * mt + 8 * (lm & 1)) * 2
                                   : stB + (k & 127) * 528 + (64 * (warp & 3) + 32 * mt + 16 * (ks >> 3) + 8 * (lm & 1)) * 2);
      }
  }
  __syncthreads();
  if (warp < 4) {
    #pragma unroll
    for (int i = 0; i < 16; i++) sts128(sb + R_WQ + ((warp * 16 + i) * 32 + lane) * 16, make_uint4(A[1][i][0], A[1][i][1], A[1][i][2], A[1][i][3]));
  }
  __syncthreads();
  if (warp >= 8) {
    const uint32_t zero = blockIdx.y;
    #pragma unroll
    for (int i = 0; i < 32; i++) sts128(sb + R_WO + (((warp - 8) * 32 + i) * 32 + lane) * 16, make_uint4(A[i >> 4][i & 15][0], A[i >> 4][i & 15][1], A[i >> 4][i & 15][2], A[i >> 4][i & 15][3]));
    #pragma unroll
    for (int i = 0; i < 32; i++) { uint4 v = lds128(sb + R_WR + (((warp - 8) * 32 + i) * 32 + lane) * 16); A[i & 1][i >> 1][0] = v.x; A[i & 1][i >> 1][1] = v.y; A[i & 1][i >> 1][2] = v.z; A[i & 1][i >> 1][3] = v.w; }
    #pragma unroll 1
    for (int s = 0; s < NSTEP; s++) {
      const int tid = otid(), lane = tid & 31, wv = (tid >> 5) - 8, g = lane >> 2, t = lane & 3;
      if (tid == 256) mbar_expect(mV, 4096);
      const uint32_t fo = (t ^ swz(g)) << 4;
      TR(1);
      bar_sync(4, 384);
      if (VD) { long long t0 = clock64(); while (clock64() - t0 < VD); }
      TR(2);
      float c[4][4];
      #pragma unroll
      for (int i = 0; i < 4; i++) { c[i][0] = c[i][1] = c[i][2] = c[i][3] = 0.f; }
      #pragma unroll
      for (int p = 0; p < 8; p++) {
        uint4 b = ldc(R_MEM + g * 16 + t * 160 + p * 640);
        mma16(c[0], A[0][2*p][0], A[0][2*p][1], A[0][2*p][2], A[0][2*p][3], b.x, b.y);
        mma16(c[1], A[1][2*p][0], A[1][2*p][1], A[1][2*p][2], A[1][2*p][3], b.x, b.y);
        mma16(c[2], A[0][2*p+1][0], A[0][2*p+1][1], A[0][2*p+1][2], A[0][2*p+1][3], b.z, b.w);
        mma16(c[3], A[1][2*p+1][0], A[1][2*p+1][1], A[1][2*p+1][2], A[1][2*p+1][3], b.z, b.w);
      }
      #pragma unroll
      for (int i = 0; i < 4; i++) { c[0][i] += c[2][i]; c[1][i] += c[3][i]; }
      const uint32_t rx = sb + R_RV + (wv * 64 + lane) * 16;
      { uint32_t ra = mapa(rx, peer), rm = mapa(mV, peer);
        st_async_v4(ra, c[0][0], c[0][1], c[0][2], c[0][3], rm);
        st_async_v4(ra + 512, c[1][0], c[1][1], c[1][2], c[1][3], rm); }
      TR(4);
      const bool more = s < NSTEP - 1;
      uint32_t wb = sb + (wv * 1024 + lane) * 16;
      #pragma unroll
      for (int i = 0; i < NW0; i++) { uint4 v = lds128(wb + R_WO + i * 512); A[i >> 4][i & 15][0] = v.x; A[i >> 4][i & 15][1] = v.y; A[i >> 4][i & 15][2] = v.z; A[i >> 4][i & 15][3] = v.w; }
      TR(3);
      mbar_wait(mV, s & 1);
      TR(5);
      { uint4 r0 = lds128(rx), r1 = lds128(rx + 512);
        stsm4t(sb + R_VT + (s & 1) * VT_SZ + (32 + (lane & 7)) * 272 + (4 * wv + (lane >> 3)) * 16,
          pack2(c[0][0] + __uint_as_float(r0.x), c[0][1] + __uint_as_float(r0.y)), pack2(c[0][2] + __uint_as_float(r0.z), c[0][3] + __uint_as_float(r0.w)),
          pack2(c[1][0] + __uint_as_float(r1.x), c[1][1] + __uint_as_float(r1.y)), pack2(c[1][2] + __uint_as_float(r1.z), c[1][3] + __uint_as_float(r1.w))); }
      if (more) {
      bar_arrive(3, 256);
      TR(8);
      #pragma unroll
      for (int i = NW0; i < 32; i++) { uint4 v = lds128(wb + R_WO + i * 512); A[i >> 4][i & 15][0] = v.x; A[i >> 4][i & 15][1] = v.y; A[i >> 4][i & 15][2] = v.z; A[i >> 4][i & 15][3] = v.w;
        if ((i % THR) == THR - 1) wb += v.x & zero; }
      TR(10);
      bar_sync(7, 256);
      TR(9);
      #pragma unroll
      for (int i = 0; i < 4; i++) { c[i][0] = c[i][1] = c[i][2] = c[i][3] = 0.f; }
      #pragma unroll
      for (int p = 0; p < 4; p++) {
        uint4 b = ldc(R_O + g * 256 + (p >> 1) * 128 + (fo ^ ((p & 1) << 6)));
        #pragma unroll
        for (int mt = 0; mt < 4; mt++) { const uint32_t* a = A[mt >> 1][(mt & 1) * 8 + 2 * p]; mma16(c[mt], a[0], a[1], a[2], a[3], b.x, b.y); }
        #pragma unroll
        for (int mt = 0; mt < 4; mt++) { const uint32_t* a = A[mt >> 1][(mt & 1) * 8 + 2 * p + 1]; mma16(c[mt], a[0], a[1], a[2], a[3], b.z, b.w); }
      }
      TR(6);
      float4* dst = &g_acc[s + 1][j][wv * 64 + lane];
      REDV4(dst, c[0][0], c[0][1], c[0][2]); REDV4(dst + 256, c[0][3], c[1][0], c[1][1]); REDV4(dst + 512, c[1][2], c[1][3], 0.f);
      REDV4(dst + 32, c[2][0], c[2][1], c[2][2]); REDV4(dst + 288, c[2][3], c[3][0], c[3][1]); REDV4(dst + 544, c[3][2], c[3][3], 0.f);
      bar_arrive(8, 352);
      TR(7);
      } else bar_sync(6, 256);
      { const int vt = tid - 256;
        if (j == 0) { const int r = vt >> 4, cc = vt & 15; uint4 v = lds128(sb + R_KT + (s & 1) * KT_SZ + (32 + r) * 256 + ((cc ^ swz(r)) << 4));
          __stcg((uint4*)(g_km + ((size_t)(s * 32 + h)) * 1024) + vt, v); }
        else { uint32_t vb = sb + R_VT + (s & 1) * VT_SZ + 32 * 272 + vt * 2; uint32_t e[8];
          #pragma unroll
          for (int k = 0; k < 8; k++) { unsigned short x; asm volatile("ld.shared.u16 %0, [%1];" : "=h"(x) : "r"(vb + k * 272) : "memory"); e[k] = x; }
          __stcg((uint4*)(g_vmT + ((size_t)(s * 32 + h)) * 1024) + vt, make_uint4(e[0] | (e[1] << 16), e[2] | (e[3] << 16), e[4] | (e[5] << 16), e[6] | (e[7] << 16))); }
        if (!more) { __syncwarp(); if (lane == 0) { __threadfence(); atomicAdd(&g_fl.prog[15][h], 1); } } }
      #pragma unroll
      for (int i = 0; i < 32; i++) { uint4 v = lds128(wb + R_WR + i * 512); A[i & 1][i >> 1][0] = v.x; A[i & 1][i >> 1][1] = v.y; A[i & 1][i >> 1][2] = v.z; A[i & 1][i >> 1][3] = v.w; }
    }
    return;
  }
  const float scale = 0.08838834764831845f, l2e = 1.4426950408889634f;
  auto prefetch = [&](int s) {
    const int vt = otid() - 160;
    if ((s & 3) == 0) { wait_flag(&g_fl.tile[s >> 2][h >> 1], 1); wait_flag(&g_fl.tile[s >> 2][16 + (h >> 1)], 1); }
    const int r = vt >> 4, c = vt & 15;
    const bf16* src = g_qkv + (size_t)(32 * s + r) * QW + h * 128 + c * 8;
    uint32_t kb = sb + R_KT + (s & 1) * KT_SZ + r * 256, vb = sb + R_VT + (s & 1) * VT_SZ + r * 272 + c * 16;
    #pragma unroll
    for (int i = 0; i < 8; i++) { cp16(kb + i * 1024 + ((c ^ swz(r + 4 * i)) << 4), src + (size_t)i * 4 * QW); cp16(vb + i * 1088, src + (size_t)i * 4 * QW + 4096); }
  };
  if (warp >= 4) {
  if (warp == 5 || warp == 6) prefetch(0);
  #pragma unroll 1
  for (int s = 0; s < NSTEP; s++) {
    TR(0); TR(1);
    const int tid = otid(), lane = tid & 31, warp = tid >> 5, g = lane >> 2, t = lane & 3;
    const uint32_t fo = (t ^ swz(g)) << 4;
    {
      if (tid == 0) mbar_expect(mQ, 4096);
      if (tid == 128) mbar_expect(mK, 4096);
      const float4* src = &g_acc[s][j][tid];
      uint4 v0, v1, v2; int it = 0; bool ok;
      do {
        asm volatile("ld.relaxed.gpu.global.v4.u32 {%0,%1,%2,%3}, [%4];" : "=r"(v0.x), "=r"(v0.y), "=r"(v0.z), "=r"(v0.w) : "l"(src) : "memory");
        asm volatile("ld.relaxed.gpu.global.v4.u32 {%0,%1,%2,%3}, [%4];" : "=r"(v1.x), "=r"(v1.y), "=r"(v1.z), "=r"(v1.w) : "l"(src + 256) : "memory");
        asm volatile("ld.relaxed.gpu.global.v4.u32 {%0,%1,%2,%3}, [%4];" : "=r"(v2.x), "=r"(v2.y), "=r"(v2.z), "=r"(v2.w) : "l"(src + 512) : "memory");
        ok = (v0.w == 0x42000000u) && (v1.w == 0x42000000u) && (v2.w == 0x42000000u);
      } while (!ok && ++it < SPIN_LIMIT);
      __syncwarp();
      stsm4t(sb + R_MEM + (lane & 7) * 16 + (4 * warp + (lane >> 3)) * 160,
        pack2(__uint_as_float(v0.x), __uint_as_float(v0.y)), pack2(__uint_as_float(v0.z), __uint_as_float(v1.x)),
        pack2(__uint_as_float(v1.y), __uint_as_float(v1.z)), pack2(__uint_as_float(v2.x), __uint_as_float(v2.y)));
    }
    TR(2);
    asm volatile("cp.async.wait_all;" ::: "memory");
    bar_sync(1, 256);
    { long long t0 = clock64(); while (clock64() - t0 < KD); }
    if (VP < 0) bar_arrive(4, 384);
    TR(3);
    float c[4][4];
    #pragma unroll
    for (int i = 0; i < 4; i++) { c[i][0] = c[i][1] = c[i][2] = c[i][3] = 0.f; }
    #pragma unroll
    for (int p = 0; p < 8; p++) {
      uint4 b = ldc(R_MEM + g * 16 + t * 160 + p * 640);
      mma16(c[0], A[0][2*p][0], A[0][2*p][1], A[0][2*p][2], A[0][2*p][3], b.x, b.y);
      mma16(c[1], A[1][2*p][0], A[1][2*p][1], A[1][2*p][2], A[1][2*p][3], b.x, b.y);
      mma16(c[2], A[0][2*p+1][0], A[0][2*p+1][1], A[0][2*p+1][2], A[0][2*p+1][3], b.z, b.w);
      mma16(c[3], A[1][2*p+1][0], A[1][2*p+1][1], A[1][2*p+1][2], A[1][2*p+1][3], b.z, b.w);
      if (p == VP) asm volatile("bar.arrive 4, 384;");
    }
    #pragma unroll
    for (int i = 0; i < 4; i++) { c[0][i] += c[2][i]; c[1][i] += c[3][i]; }
    const uint32_t rx = sb + R_RQK + (warp * 64 + lane) * 16;
    { uint32_t ra = mapa(rx, peer), rm = mapa(mK, peer);
      st_async_v4(ra, c[0][0], c[0][1], c[0][2], c[0][3], rm);
      st_async_v4(ra + 512, c[1][0], c[1][1], c[1][2], c[1][3], rm); }
    if (VP > 7) bar_arrive(4, 384);
    TR(4);
    const uint32_t so = (lane & 7) * 256 + (((4 * (warp & 3) + (lane >> 3)) ^ swz(lane & 7)) << 4);
    mbar_wait(mK, s & 1);
    TR(5);
    uint32_t m0, m1, m2, m3;
    { uint4 r0 = lds128(rx), r1 = lds128(rx + 512);
      m0 = pack2(c[0][0] + __uint_as_float(r0.x), c[0][1] + __uint_as_float(r0.y)); m1 = pack2(c[0][2] + __uint_as_float(r0.z), c[0][3] + __uint_as_float(r0.w));
      m2 = pack2(c[1][0] + __uint_as_float(r1.x), c[1][1] + __uint_as_float(r1.y)); m3 = pack2(c[1][2] + __uint_as_float(r1.z), c[1][3] + __uint_as_float(r1.w)); }
    stsm4t(sb + R_KT + (s & 1) * KT_SZ + 32 * 256 + so, m0, m1, m2, m3);
    if (s == NSTEP - 1) { bar_arrive(6, 256); break; }
    asm("movmatrix.sync.aligned.m8n8.trans.b16 %0, %0;" : "+r"(m0)); asm("movmatrix.sync.aligned.m8n8.trans.b16 %0, %0;" : "+r"(m1));
    asm("movmatrix.sync.aligned.m8n8.trans.b16 %0, %0;" : "+r"(m2)); asm("movmatrix.sync.aligned.m8n8.trans.b16 %0, %0;" : "+r"(m3));
    TR(8);
    bar_sync(9, 256);
    TR(9);
    { uint32_t qa[4]; ldsm4(qa, sb + R_Q + so);
      #pragma unroll
      for (int i = 0; i < 2; i++) { c[i][0] = c[i][1] = c[i][2] = c[i][3] = 0.f; }
      mma16(c[0], qa[0], 0, qa[1], 0, m0, m1); mma16(c[1], qa[2], 0, qa[3], 0, m2, m3);
      asm volatile("st.shared.v2.f32 [%0], {%1,%2};" ::"r"(sb + R_SM + (warp - 4) * 256 + lane * 8), "f"(c[0][0] + c[1][0]), "f"(c[0][1] + c[1][1]) : "memory"); }
    bar_arrive(2, 256);
    TR(10);
    if ((warp == 5 || warp == 6) && s < NSTEP - 2) prefetch(s + 1);
    TR(7);
    if (warp == 7) { if ((s & 3) == 1 && s > 1 && lane == 0) asm volatile("red.release.gpu.global.add.s32 [%0], 4;" ::"l"(&g_fl.prog[(s - 2) >> 2][h]) : "memory"); __syncwarp(); }
    else bar_sync(8, 352);
    { long long t0 = clock64(); while (clock64() - t0 < PDELAY); }
  }
  return;
  }
  #pragma unroll 1
  for (int s = 0; s < NSTEP; s++) {
    TR(0); TR(1);
    const int tid = otid(), lane = tid & 31, warp = tid >> 5, g = lane >> 2, t = lane & 3;
    const uint32_t fo = (t ^ swz(g)) << 4;
    {
      if (tid == 0) mbar_expect(mQ, 4096);
      if (tid == 128) mbar_expect(mK, 4096);
      const float4* src = &g_acc[s][j][tid];
      uint4 v0, v1, v2; int it = 0; bool ok;
      do {
        asm volatile("ld.relaxed.gpu.global.v4.u32 {%0,%1,%2,%3}, [%4];" : "=r"(v0.x), "=r"(v0.y), "=r"(v0.z), "=r"(v0.w) : "l"(src) : "memory");
        asm volatile("ld.relaxed.gpu.global.v4.u32 {%0,%1,%2,%3}, [%4];" : "=r"(v1.x), "=r"(v1.y), "=r"(v1.z), "=r"(v1.w) : "l"(src + 256) : "memory");
        asm volatile("ld.relaxed.gpu.global.v4.u32 {%0,%1,%2,%3}, [%4];" : "=r"(v2.x), "=r"(v2.y), "=r"(v2.z), "=r"(v2.w) : "l"(src + 512) : "memory");
        ok = (v0.w == 0x42000000u) && (v1.w == 0x42000000u) && (v2.w == 0x42000000u);
      } while (!ok && ++it < SPIN_LIMIT);
      __syncwarp();
      stsm4t(sb + R_MEM + (lane & 7) * 16 + (4 * warp + (lane >> 3)) * 160,
        pack2(__uint_as_float(v0.x), __uint_as_float(v0.y)), pack2(__uint_as_float(v0.z), __uint_as_float(v1.x)),
        pack2(__uint_as_float(v1.y), __uint_as_float(v1.z)), pack2(__uint_as_float(v2.x), __uint_as_float(v2.y)));
    }
    TR(2);

    bar_sync(1, 256);
    bar_arrive(4, 384);
    TR(3);
    float c[4][4];
    #pragma unroll
    for (int i = 0; i < 4; i++) { c[i][0] = c[i][1] = c[i][2] = c[i][3] = 0.f; }
    #pragma unroll
    for (int p = 0; p < 8; p++) {
      uint4 b = ldc(R_MEM + g * 16 + t * 160 + p * 640);
      mma16(c[0], A[0][2*p][0], A[0][2*p][1], A[0][2*p][2], A[0][2*p][3], b.x, b.y);
      mma16(c[1], A[1][2*p][0], A[1][2*p][1], A[1][2*p][2], A[1][2*p][3], b.x, b.y);
      mma16(c[2], A[0][2*p+1][0], A[0][2*p+1][1], A[0][2*p+1][2], A[0][2*p+1][3], b.z, b.w);
      mma16(c[3], A[1][2*p+1][0], A[1][2*p+1][1], A[1][2*p+1][2], A[1][2*p+1][3], b.z, b.w);
    }
    #pragma unroll
    for (int i = 0; i < 4; i++) { c[0][i] += c[2][i]; c[1][i] += c[3][i]; }
    const uint32_t rx = sb + R_RQK + (warp * 64 + lane) * 16;
    { uint32_t ra = mapa(rx, peer), rm = mapa(mQ, peer);
      st_async_v4(ra, c[0][0], c[0][1], c[0][2], c[0][3], rm);
      st_async_v4(ra + 512, c[1][0], c[1][1], c[1][2], c[1][3], rm); }
    TR(4);
    const uint32_t so = (lane & 7) * 256 + (((4 * (warp & 3) + (lane >> 3)) ^ swz(lane & 7)) << 4);
    if (s == NSTEP - 1) { mbar_wait(mQ, s & 1); break; }
    uint4 kf[4]; uint32_t vf[4][4];
    const uint32_t vb = sb + R_VT + (s & 1) * VT_SZ + (lane & 15) * 272 + (32 * warp + 8 * (lane >> 4)) * 2;
    #pragma unroll
    for (int p = 0; p < 4; p++) kf[p] = lds128(sb + R_KT + (s & 1) * KT_SZ + warp * 2048 + g * 256 + (p >> 1) * 128 + (fo ^ ((p & 1) << 6)));
    #pragma unroll
    for (int i = 0; i < 4; i++) ldsm4t(vf[i], vb + (i >> 1) * 16 * 272 + (i & 1) * 32);
    mbar_wait(mQ, s & 1);
    TR(5);
    uint32_t m0, m1, m2, m3;
    { uint4 r0 = lds128(rx), r1 = lds128(rx + 512);
      m0 = pack2(c[0][0] + __uint_as_float(r0.x), c[0][1] + __uint_as_float(r0.y)); m1 = pack2(c[0][2] + __uint_as_float(r0.z), c[0][3] + __uint_as_float(r0.w));
      m2 = pack2(c[1][0] + __uint_as_float(r1.x), c[1][1] + __uint_as_float(r1.y)); m3 = pack2(c[1][2] + __uint_as_float(r1.z), c[1][3] + __uint_as_float(r1.w)); }
    stsm4t(sb + R_Q + so, m0, m1, m2, m3);
    TR(8);
    bar_arrive(9, 256); bar_sync(5, 128);
    TR(9);
    {
      uint4 qa[4];
      #pragma unroll
      for (int p = 0; p < 4; p++) qa[p] = lds128(sb + R_Q + g * 256 + (p >> 1) * 128 + (fo ^ ((p & 1) << 6)));
      #pragma unroll
      for (int i = 0; i < 4; i++) { c[i][0] = c[i][1] = c[i][2] = c[i][3] = 0.f; }
      #pragma unroll
      for (int p = 0; p < 4; p++) { mma16(c[(p & 1) * 2], qa[p].x, 0, qa[p].y, 0, kf[p].x, kf[p].y); mma16(c[(p & 1) * 2 + 1], qa[p].z, 0, qa[p].w, 0, kf[p].z, kf[p].w); }
      float a = rbf(rbf((c[0][0] + c[1][0]) + (c[2][0] + c[3][0])) * scale) * l2e, b = rbf(rbf((c[0][1] + c[1][1]) + (c[2][1] + c[3][1])) * scale) * l2e;
      asm volatile("st.shared.v2.f32 [%0], {%1,%2};" ::"r"(sb + R_S + g * 160 + (8 * warp + 2 * t) * 4), "f"(a), "f"(b) : "memory");
    }
    TR(10);
    bar_sync(10, 128);
    float sv[8], pm[8];
    #pragma unroll
    for (int i = 0; i < 4; i++) asm volatile("ld.shared.v2.f32 {%0,%1}, [%2];" : "=f"(sv[2*i]), "=f"(sv[2*i+1]) : "r"(sb + R_S + g * 160 + (8 * i + 2 * t) * 4) : "memory");
    float mx = fmaxf(fmaxf(fmaxf(sv[0], sv[1]), fmaxf(sv[2], sv[3])), fmaxf(fmaxf(sv[4], sv[5]), fmaxf(sv[6], sv[7])));
    mx = fmaxf(mx, __shfl_xor_sync(~0u, mx, 1)); mx = fmaxf(mx, __shfl_xor_sync(~0u, mx, 2));
    uint32_t P[5];
    #pragma unroll
    for (int i = 0; i < 4; i++) P[i] = pack2(ex2(sv[2*i] - mx), ex2(sv[2*i+1] - mx));
    #pragma unroll
    for (int i = 0; i < 4; i++) { c[i][0] = c[i][1] = c[i][2] = c[i][3] = 0.f; }
    #pragma unroll
    for (int kk = 0; kk < 2; kk++) {
      mma16(c[0], P[2*kk], 0, P[2*kk+1], 0, vf[2*kk][0], vf[2*kk][1]); mma16(c[1], P[2*kk], 0, P[2*kk+1], 0, vf[2*kk][2], vf[2*kk][3]);
      mma16(c[2], P[2*kk], 0, P[2*kk+1], 0, vf[2*kk+1][0], vf[2*kk+1][1]); mma16(c[3], P[2*kk], 0, P[2*kk+1], 0, vf[2*kk+1][2], vf[2*kk+1][3]);
    }
    float sum = 0.f;
    #pragma unroll
    for (int i = 0; i < 4; i++) sum += __uint_as_float(P[i] << 16) + __uint_as_float(P[i] & 0xffff0000u);
    TR(11);
    bar_sync(2, 256);
    #pragma unroll
    for (int i = 0; i < 4; i++) asm volatile("ld.shared.v2.f32 {%0,%1}, [%2];" : "=f"(pm[2*i]), "=f"(pm[2*i+1]) : "r"(sb + R_SM + i * 256 + lane * 8) : "memory");
    const float s8 = rbf(rbf((pm[0] + pm[2]) + (pm[4] + pm[6])) * scale) * l2e, s9 = rbf(rbf((pm[1] + pm[3]) + (pm[5] + pm[7])) * scale) * l2e;
    float mg = fmaxf(mx, fmaxf(s8, s9));
    mg = fmaxf(mg, __shfl_xor_sync(~0u, mg, 1)); mg = fmaxf(mg, __shfl_xor_sync(~0u, mg, 2));
    const float fs = ex2(mx - mg);
    P[4] = pack2(ex2(s8 - mg), ex2(s9 - mg));
    #pragma unroll
    for (int i = 0; i < 4; i++) { c[i][0] *= fs; c[i][1] *= fs; }
    sum = fmaf(sum, fs, __uint_as_float(P[4] << 16) + __uint_as_float(P[4] & 0xffff0000u));
    sum += __shfl_xor_sync(~0u, sum, 1); sum += __shfl_xor_sync(~0u, sum, 2);
    float inv; asm("rcp.approx.ftz.f32 %0, %1;" : "=f"(inv) : "f"(sum));
    TR(6);
    bar_sync(3, 256);
    { uint32_t r[4]; ldsm4t(r, sb + R_VT + (s & 1) * VT_SZ + (32 + (lane & 7)) * 272 + (4 * warp + (lane >> 3)) * 16);
      #pragma unroll
      for (int i = 0; i < 4; i++) mma8(c[i], P[4], 0, r[i]); }
    asm volatile("stmatrix.sync.aligned.m8n8.x4.shared.b16 [%0], {%1,%2,%3,%4};" ::"r"(sb + R_O + so),
      "r"(pack2(c[0][0] * inv, c[0][1] * inv)), "r"(pack2(c[1][0] * inv, c[1][1] * inv)), "r"(pack2(c[2][0] * inv, c[2][1] * inv)), "r"(pack2(c[3][0] * inv, c[3][1] * inv)) : "memory");
    bar_arrive(7, 256);
    TR(7);
    bar_sync(8, 352);
    long long t0 = clock64();
    #pragma unroll
    for (int i = 0; i < 16; i++) { uint4 v = lds128(sb + R_WQ + ((warp * 16 + i) * 32 + lane) * 16); A[1][i][0] = v.x; A[1][i][1] = v.y; A[1][i][2] = v.z; A[1][i][3] = v.w; }
    while (clock64() - t0 < PDELAY);
  }
}

constexpr int I_M1 = 512, I_Q = 624, I_M2 = 880, I_AT = 1008, I_G = I_AT + 32, GSZ = 56, I_END = I_G + 15 * GSZ + 24;
constexpr int B_STG = 4 * 49152, B_BAR = B_STG + 8 * 2304;
struct Item { int type, rb, nt, ks; };
__device__ __forceinline__ Item decode(int it) {
  Item r; r.ks = 0;
  if (it < I_M1) { r.type = 0; r.rb = it >> 5; r.nt = it & 31; }
  else if (it < I_Q) { int i = it - I_M1; r.type = 1; r.rb = i / 7; r.nt = i % 7; }
  else if (it < I_M2) { int i = it - I_Q; r.type = 0; r.rb = i >> 4; r.nt = 32 + (i & 15); }
  else if (it < I_AT) { int i = it - I_M2; r.type = 2; r.rb = i >> 3; r.nt = (i >> 2) & 1; r.ks = i & 3; }
  else if (it < I_G) { r.type = 3; r.rb = 0; r.nt = it - I_AT; }
  else {
    int i = it - I_G, gi = i / GSZ, q = i % GSZ; if (gi == 15) q += 32;
    if (q < 32) { r.type = 3; r.rb = gi + 1; r.nt = q; }
    else if (q < 48) { r.type = 4; r.rb = gi; r.nt = (q - 32) >> 3; r.ks = (q - 32) & 7; }
    else { r.type = 5; r.rb = gi; r.nt = q - 48; } }
  return r;
}
__device__ __forceinline__ float gelu_t(float x) { float u = 0.7978845608028654f * (x + 0.044715f * x * x * x); float th; asm("tanh.approx.f32 %0, %1;" : "=f"(th) : "f"(u)); float hx = 0.5f * x; return fmaf(hx, th, hx); }

__device__ __forceinline__ void bulk(uint32_t sb, const Maps& mp, const bf16* __restrict__ x, const bf16* __restrict__ b1, const bf16* __restrict__ b2, bf16* __restrict__ out) {
  const int tid = threadIdx.x, warp = tid >> 5, lane = tid & 31, g = lane >> 2, t = lane & 3;
  const int bid = blockIdx.x - NREC;
  const uint32_t full = sb + B_BAR, empty = sb + B_BAR + 32, ifull = sb + B_BAR + 64, iempty = sb + B_BAR + 80;
  volatile int* ring = (volatile int*)(__cvta_shared_to_generic(sb + B_BAR + 96));
  if (warp >= 8) {
    asm volatile("setmaxnreg.dec.sync.aligned.u32 40;");
    if (tid == 256) {
      uint32_t st = 0, ph = 0;
      for (int n = 0;; n++) {
        int it = n == 0 ? bid : NBULK + atomicAdd(&g_fl.next, 1);
        Item I = decode(it);
        if (it < I_END) {
          if (I.type == 5) { wait_flag(&g_fl.s[I.rb][0], 16); wait_flag(&g_fl.z[I.rb][0], 8); }
          else if (I.type == 3) { wait_flag(&g_fl.prog[I.rb][I.nt], 8); wait_flag(&g_fl.tile[I.rb][I.nt >> 1], 1); wait_flag(&g_fl.tile[I.rb][16 + (I.nt >> 1)], 1); wait_flag(&g_fl.tile[I.rb][32 + (I.nt >> 1)], 1); fence_async(); }
          else if (I.type == 2) { wait_flag(&g_fl.hid[I.rb], 7); fence_async(); }
          else if (I.type == 4) { wait_flag(&g_fl.o[I.rb][I.ks], 4); fence_async(); }
        }
        mbar_wait(iempty + (n & 1) * 8, ((n >> 1) & 1) ^ 1);
        ring[n & 1] = it; mbar_arrive(ifull + (n & 1) * 8);
        if (it >= I_END) break;
        if (I.type == 5) continue;
        if (I.type == 3) {
          for (int m = 0; m < 3; m++) {
            mbar_wait(empty + st * 8, ph ^ 1);
            mbar_expect(full + st * 8, 32768);
            int col = (m == 0 ? 8192 : (m == 1 ? 0 : 4096)) + I.nt * 128;
            tma2d(sb + st * 49152, &mp.qkv, col, I.rb * 128, full + st * 8);
            tma2d(sb + st * 49152 + 16384, &mp.qkv, col + 64, I.rb * 128, full + st * 8);
            if (++st == 4) { st = 0; ph ^= 1; }
          }
          continue;
        }
        const CUtensorMap *ma, *mb; int nkb = 8, kb0 = 0, n0;
        if (I.type == 0) { ma = &mp.xn; mb = I.nt < 16 ? &mp.wk : (I.nt < 32 ? &mp.wv : &mp.wq); n0 = (I.nt & 15) * 256; }
        else if (I.type == 1) { ma = &mp.y; mb = &mp.w1; n0 = I.nt * 256; }
        else if (I.type == 2) { ma = &mp.hid; mb = &mp.w2; n0 = I.nt * 256; nkb = 7; kb0 = I.ks * 7; }
        else { ma = &mp.o; mb = &mp.wo; n0 = I.nt * 256; kb0 = I.ks * 8; }
        for (int kb = kb0; kb < kb0 + nkb; kb++) {
          mbar_wait(empty + st * 8, ph ^ 1);
          mbar_expect(full + st * 8, 49152);
          uint32_t sa = sb + st * 49152;
          tma2d(sa, ma, kb * 64, I.rb * 128, full + st * 8);
          #pragma unroll
          for (int q = 0; q < 4; q++) tma2d(sa + 16384 + q * 8192, mb, n0 + q * 64, kb * 64, full + st * 8);
          if (++st == 4) { st = 0; ph ^= 1; }
        }
      }
    } else if (warp == 9) {
      for (int n = 0;; n++) {
        mbar_wait(ifull + (n & 1) * 8, (n >> 1) & 1);
        int it = ring[n & 1];
        if (it >= I_END) break;
        Item I = decode(it);
        bar_sync(6 + (n & 1), 288);
        if (lane == 0) {
          if (I.type != 5) {
            fence_async(); __threadfence();
            int* f = I.type == 0 ? &g_fl.tile[I.rb][I.nt] : I.type == 1 ? &g_fl.hid[I.rb] : I.type == 2 ? &g_fl.z[I.rb][0] : I.type == 3 ? &g_fl.o[I.rb][I.nt >> 2] : &g_fl.s[I.rb][0];
            atomicAdd(f, 1);
          }
          mbar_arrive(iempty + (n & 1) * 8);
        }
      }
    }
    return;
  }
  asm volatile("setmaxnreg.inc.sync.aligned.u32 232;");
  const int wg = warp >> 2;
  const uint32_t stg = sb + B_STG + warp * 2304;
  const int lm = lane >> 3, lr = lane & 7;
  uint32_t st = 0, ph = 0;
  float d[128];
  #pragma unroll 1
  for (int n = 0;; n++) {
    mbar_wait(ifull + (n & 1) * 8, (n >> 1) & 1);
    const int it = ring[n & 1];
    __syncwarp(); if (lane == 0) mbar_arrive(iempty + (n & 1) * 8);
    if (it >= I_END) break;
    Item I = decode(it);
    const int row0 = I.rb * 128 + warp * 16;
    TB(0);
    if (I.type == 5) {
      #pragma unroll
      for (int i = 0; i < 4; i++) {
        size_t off = (size_t)(I.rb * 128 + I.nt * 16 + warp * 2 + (i >> 1)) * DM + (i & 1) * 256 + lane * 8;
        float4 s0 = __ldcg((const float4*)(g_s + off)), s1 = __ldcg((const float4*)(g_s + off + 4));
        float4 z0 = __ldcg((const float4*)(g_z + off)), z1 = __ldcg((const float4*)(g_z + off + 4));
        uint4 xv = *(const uint4*)(x + off), bv = *(const uint4*)(b2 + (i & 1) * 256 + lane * 8);
        float sa[8] = {s0.x, s0.y, s0.z, s0.w, s1.x, s1.y, s1.z, s1.w}, za[8] = {z0.x, z0.y, z0.z, z0.w, z1.x, z1.y, z1.z, z1.w}, r[8];
        #pragma unroll
        for (int e = 0; e < 8; e++) { float xx = __bfloat162float(((const bf16*)&xv)[e]), bb = __bfloat162float(((const bf16*)&bv)[e]);
          float u = rbf(rbf(za[e]) + bb); float gg = rbf(__fdividef(u, 1.f + __expf(-u))); r[e] = xx + rbf(rbf(sa[e]) * gg); }
        *(uint4*)(out + off) = make_uint4(pack2(r[0], r[1]), pack2(r[2], r[3]), pack2(r[4], r[5]), pack2(r[6], r[7]));
      }
      bar_arrive(6 + (n & 1), 288);
      continue;
    }
    if (I.type == 3) {
      const int h = I.nt, seg = warp >> 1, half = warp & 1, step = I.rb * 4 + seg;
      uint32_t kmr[16], vmr[16];
      { const uint32_t* km = (const uint32_t*)(g_km + ((size_t)(step * 32 + h)) * 1024) + g * 64 + t;
        const uint32_t* vm = (const uint32_t*)(g_vmT + ((size_t)(step * 32 + h)) * 1024) + g * 4 + t;
        #pragma unroll
        for (int i = 0; i < 16; i++) { kmr[i] = __ldcg(km + i * 4); vmr[i] = __ldcg(vm + i * 32); } }
      uint32_t sQ = sb + st * 49152; mbar_wait(full + st * 8, ph); uint32_t eQ = empty + st * 8; if (++st == 4) { st = 0; ph ^= 1; }
      uint32_t sK = sb + st * 49152; mbar_wait(full + st * 8, ph); uint32_t eK = empty + st * 8; if (++st == 4) { st = 0; ph ^= 1; }
      float sc[5][4];
      #pragma unroll
      for (int i = 0; i < 5; i++) { sc[i][0] = sc[i][1] = sc[i][2] = sc[i][3] = 0.f; }
      #pragma unroll
      for (int ks = 0; ks < 8; ks++) {
        uint32_t a[4]; { int r = warp * 16 + 8 * (lm & 1) + lr, c8 = 2 * ks + (lm >> 1); ldsm4(a, sQ + (c8 >> 3) * 16384 + r * 128 + (((c8 & 7) ^ (r & 7)) << 4)); }
        #pragma unroll
        for (int np = 0; np < 2; np++) {
          if (np == 1 && half == 0) continue;
          uint32_t b[4]; int r = seg * 32 + 16 * np + 8 * (lm >> 1) + lr, c8 = 2 * ks + (lm & 1);
          ldsm4(b, sK + (c8 >> 3) * 16384 + r * 128 + (((c8 & 7) ^ (r & 7)) << 4));
          mma16(sc[2*np], a[0], a[1], a[2], a[3], b[0], b[1]); mma16(sc[2*np+1], a[0], a[1], a[2], a[3], b[2], b[3]);
        }
        mma16(sc[4], a[0], a[1], a[2], a[3], kmr[2*ks], kmr[2*ks+1]);
      }
      __syncwarp(); if (lane == 0) { mbar_arrive(eQ); mbar_arrive(eK); }
      const float scale = 0.08838834764831845f;
      uint32_t P[5][2];
      #pragma unroll
      for (int rr = 0; rr < 2; rr++) {
        const int qi = 16 * half + g + 8 * rr;
        float mx = -3.0e38f;
        #pragma unroll
        for (int i = 0; i < 5; i++)
          #pragma unroll
          for (int e = 0; e < 2; e++) { float v = rbf(rbf(sc[i][2*rr+e]) * scale); if (i < 4 && 8 * i + 2 * t + e > qi) v = -1.0e9f; sc[i][2*rr+e] = v; mx = fmaxf(mx, v); }
        mx = fmaxf(mx, __shfl_xor_sync(~0u, mx, 1)); mx = fmaxf(mx, __shfl_xor_sync(~0u, mx, 2));
        float sum = 0;
        #pragma unroll
        for (int i = 0; i < 5; i++)
          #pragma unroll
          for (int e = 0; e < 2; e++) { float v = __expf(sc[i][2*rr+e] - mx); sc[i][2*rr+e] = v; sum += v; }
        sum += __shfl_xor_sync(~0u, sum, 1); sum += __shfl_xor_sync(~0u, sum, 2);
        float inv = __fdividef(1.f, sum);
        #pragma unroll
        for (int i = 0; i < 5; i++) P[i][rr] = pack2(sc[i][2*rr] * inv, sc[i][2*rr+1] * inv);
      }
      uint32_t sV = sb + st * 49152; mbar_wait(full + st * 8, ph); uint32_t eV = empty + st * 8; if (++st == 4) { st = 0; ph ^= 1; }
      #pragma unroll
      for (int i = 0; i < 64; i++) d[i] = 0.f;
      #pragma unroll
      for (int n2 = 0; n2 < 8; n2++) {
        #pragma unroll
        for (int kk = 0; kk < 2; kk++) {
          if (kk == 1 && half == 0) continue;
          uint32_t b[4]; int r = seg * 32 + 16 * kk + 8 * (lm & 1) + lr, c8 = 2 * n2 + (lm >> 1);
          ldsm4t(b, sV + (c8 >> 3) * 16384 + r * 128 + (((c8 & 7) ^ (r & 7)) << 4));
          mma16(d + 8 * n2, P[2*kk][0], P[2*kk][1], P[2*kk+1][0], P[2*kk+1][1], b[0], b[1]);
          mma16(d + 8 * n2 + 4, P[2*kk][0], P[2*kk][1], P[2*kk+1][0], P[2*kk+1][1], b[2], b[3]);
        }
        mma8(d + 8 * n2, P[4][0], P[4][1], vmr[2*n2]); mma8(d + 8 * n2 + 4, P[4][0], P[4][1], vmr[2*n2+1]);
      }
      __syncwarp(); if (lane == 0) mbar_arrive(eV);
      #pragma unroll
      for (int ch = 0; ch < 2; ch++) {
        #pragma unroll
        for (int i = 0; i < 8; i++) { const float* a = d + ch * 32 + i * 4;
          sts32(stg + g * 144 + i * 16 + t * 4, pack2(a[0], a[1])); sts32(stg + (g + 8) * 144 + i * 16 + t * 4, pack2(a[2], a[3])); }
        __syncwarp();
        #pragma unroll
        for (int i = 0; i < 4; i++) { int r = i * 4 + lm; uint4 v = lds128(stg + r * 144 + lr * 16);
          *(uint4*)(g_o + (size_t)(row0 + r) * 4096 + h * 128 + ch * 64 + lr * 8) = v; }
        __syncwarp();
      }
      bar_arrive(6 + (n & 1), 288);
      continue;
    }
    const int nkb = I.type == 2 ? 7 : 8;
    uint32_t prev = 0;
    for (int kb = 0; kb < nkb; kb++) {
      mbar_wait(full + st * 8, ph);
      uint32_t sa = sb + st * 49152;
      asm volatile("wgmma.fence.sync.aligned;" ::: "memory");
      #pragma unroll
      for (int k = 0; k < 4; k++)
        wgmma256(d, mkdesc(sa + wg * 8192 + k * 32, 16, 1024), mkdesc(sa + 16384 + k * 2048, 8192, 1024), (kb | k) != 0);
      asm volatile("wgmma.commit_group.sync.aligned;" ::: "memory");
      if (kb > 0) { asm volatile("wgmma.wait_group.sync.aligned 1;" ::: "memory"); if (lane == 0) mbar_arrive(prev); }
      prev = empty + st * 8;
      if (++st == 4) { st = 0; ph ^= 1; }
    }
    asm volatile("wgmma.wait_group.sync.aligned 0;" ::: "memory");
    if (lane == 0) mbar_arrive(prev);
    TB(1);
    if (I.type <= 1) {
      bf16* dst; int ld;
      if (I.type == 0) { dst = g_qkv + (size_t)row0 * QW + I.nt * 256; ld = QW; } else { dst = g_hid + (size_t)row0 * FF + I.nt * 256; ld = FF; }
      #pragma unroll
      for (int ch = 0; ch < 4; ch++) {
        #pragma unroll
        for (int i = 0; i < 8; i++) { float* a = d + ch * 32 + i * 4;
          if (I.type == 1) { float2 bb = __bfloat1622float2(*(const __nv_bfloat162*)(b1 + I.nt * 256 + ch * 64 + i * 8 + 2 * t));
            a[0] = gelu_t(rbf(rbf(a[0]) + bb.x)); a[1] = gelu_t(rbf(rbf(a[1]) + bb.y)); a[2] = gelu_t(rbf(rbf(a[2]) + bb.x)); a[3] = gelu_t(rbf(rbf(a[3]) + bb.y)); }
          sts32(stg + g * 144 + i * 16 + t * 4, pack2(a[0], a[1])); sts32(stg + (g + 8) * 144 + i * 16 + t * 4, pack2(a[2], a[3])); }
        __syncwarp();
        #pragma unroll
        for (int i = 0; i < 4; i++) { int r = i * 4 + lm; uint4 v = lds128(stg + r * 144 + lr * 16); *(uint4*)(dst + (size_t)r * ld + ch * 64 + lr * 8) = v; }
        __syncwarp();
      }
    } else {
      float* dst = (I.type == 2 ? g_z : g_s) + (size_t)(row0 + g) * DM + I.nt * 256 + 2 * t;
      #pragma unroll
      for (int i = 0; i < 32; i++) {
        asm volatile("red.relaxed.gpu.global.add.v2.f32 [%0], {%1,%2};" ::"l"(dst + i * 8), "f"(d[4*i]), "f"(d[4*i+1]) : "memory");
        asm volatile("red.relaxed.gpu.global.add.v2.f32 [%0], {%1,%2};" ::"l"(dst + 8 * DM + i * 8), "f"(d[4*i+2]), "f"(d[4*i+3]) : "memory");
      }
    }
    bar_arrive(6 + (n & 1), 288);
  }
}

__global__ void __cluster_dims__(2, 1, 1) __launch_bounds__(384, 1)
main_kernel(const __grid_constant__ Maps mp, const bf16* x, const bf16* Wq, const bf16* Wk, const bf16* Wv, const bf16* Wo, const bf16* b1, const bf16* b2, bf16* out) {
  const uint32_t sb = smem_u32(smem_raw);
  if (sb & 1023) __trap();
  if (threadIdx.x == 0) {
    if (blockIdx.x < NREC) { mbar_init(sb + R_BAR, 1); mbar_init(sb + R_BAR + 8, 1); mbar_init(sb + R_BAR + 16, 1); }
    else { for (int i = 0; i < 4; i++) { mbar_init(sb + B_BAR + i * 8, 1); mbar_init(sb + B_BAR + 32 + i * 8, 8); }
      for (int i = 0; i < 2; i++) { mbar_init(sb + B_BAR + 64 + i * 8, 1); mbar_init(sb + B_BAR + 80 + i * 8, 9); } }
    asm volatile("fence.mbarrier_init.release.cluster;" ::: "memory");
  }
  asm volatile("barrier.cluster.arrive.release.aligned; barrier.cluster.wait.acquire.aligned;" ::: "memory");
  if (blockIdx.x < NREC) recurrence(sb, Wq, Wk, Wv, Wo);
  else bulk(sb, mp, x, b1, b2, out);
}

typedef CUresult (*EncFn)(CUtensorMap*, CUtensorMapDataType, cuuint32_t, void*, const cuuint64_t*, const cuuint64_t*, const cuuint32_t*, const cuuint32_t*, CUtensorMapInterleave, CUtensorMapSwizzle, CUtensorMapL2promotion, CUtensorMapFloatOOBfill);
static void mk(EncFn f, CUtensorMap* m, const void* p, uint64_t rows, uint64_t cols, uint32_t boxr) {
  cuuint64_t dims[2] = {cols, rows}, str[1] = {cols * 2}; cuuint32_t box[2] = {64, boxr}, es[2] = {1, 1};
  f(m, CU_TENSOR_MAP_DATA_TYPE_BFLOAT16, 2, (void*)p, dims, str, box, es, CU_TENSOR_MAP_INTERLEAVE_NONE, CU_TENSOR_MAP_SWIZZLE_128B, CU_TENSOR_MAP_L2_PROMOTION_L2_256B, CU_TENSOR_MAP_FLOAT_OOB_FILL_NONE);
}
extern "C" void kernel_launch(void* const* d_in, const int* in_sizes, int n_in, void* d_out, int out_size) {
  const bf16 *x = (const bf16*)d_in[0], *mem0 = (const bf16*)d_in[1], *Wq = (const bf16*)d_in[2], *Wk = (const bf16*)d_in[3], *Wv = (const bf16*)d_in[4], *Wo = (const bf16*)d_in[5];
  const bf16 *w1 = (const bf16*)d_in[8], *b1 = (const bf16*)d_in[9], *w2 = (const bf16*)d_in[10], *b2 = (const bf16*)d_in[11];
  void* fn = nullptr; cudaDriverEntryPointQueryResult qr;
  cudaGetDriverEntryPoint("cuTensorMapEncodeTiled", &fn, cudaEnableDefault, &qr);
  EncFn f = (EncFn)fn;
  void *pxn, *py, *ph, *po, *pq;
  cudaGetSymbolAddress(&pxn, g_xn); cudaGetSymbolAddress(&py, g_y); cudaGetSymbolAddress(&ph, g_hid); cudaGetSymbolAddress(&po, g_o); cudaGetSymbolAddress(&pq, g_qkv);
  Maps mp;
  mk(f, &mp.xn, pxn, SEQ, DM, 128); mk(f, &mp.y, py, SEQ, DM, 128); mk(f, &mp.hid, ph, SEQ, FF, 128); mk(f, &mp.o, po, SEQ, 4096, 128); mk(f, &mp.qkv, pq, SEQ, QW, 128);
  mk(f, &mp.wk, Wk, DM, 4096, 64); mk(f, &mp.wv, Wv, DM, 4096, 64); mk(f, &mp.wq, Wq, DM, 4096, 64);
  mk(f, &mp.w1, w1, DM, FF, 64); mk(f, &mp.w2, w2, FF, DM, 64); mk(f, &mp.wo, Wo, 4096, DM, 64);
  cudaFuncSetAttribute(main_kernel, cudaFuncAttributeMaxDynamicSharedMemorySize, SMEM_BYTES);
  prologue_kernel<<<256, 256, 0, cudaStreamPerThread>>>(x, mem0);
  main_kernel<<<NCTA, 384, SMEM_BYTES, cudaStreamPerThread>>>(mp, x, Wq, Wk, Wv, Wo, b1, b2, (bf16*)d_out);
}
```

```cpp
#include <cuda_runtime.h>
#include <cuda_bf16.h>
#include <cuda.h>
#include <stdint.h>

typedef __nv_bfloat16 bf16;
constexpr int SEQ = 2048, DM = 512, FF = 1792, QW = 12288, NSTEP = 64;
constexpr int NREC = 64, NBULK = 68, NCTA = 132;
constexpr int SPIN_LIMIT = 1 << 22;
#define THR 4
#define PDELAY 500

__device__ bf16 g_xn[SEQ * DM];
__device__ bf16 g_y[SEQ * DM];
__device__ bf16 g_qkv[(size_t)SEQ * QW];
__device__ bf16 g_hid[SEQ * FF];
__device__ bf16 g_o[(size_t)SEQ * 4096];
__device__ float g_z[SEQ * DM];
__device__ float g_s[SEQ * DM];
__device__ float4 g_acc[NSTEP][2][768];
__device__ bf16 g_km[NSTEP * 32 * 8 * 128];
__device__ bf16 g_vmT[NSTEP * 32 * 128 * 8];
struct Flags { int tile[16][48]; int hid[16]; int z[16][2]; int o[16][8]; int s[16][2]; int prog[16][32]; int next; };
__device__ Flags g_fl;

#define TR(i)
#define TB(i)
struct Maps { CUtensorMap xn, y, hid, o, qkv, wk, wv, wq, w1, w2, wo; };

extern __shared__ __align__(1024) uint8_t smem_raw[];
__device__ __forceinline__ uint4 ldc(uint32_t off) { return *(const uint4*)(smem_raw + off); }
__device__ __forceinline__ uint32_t smem_u32(const void* p) { return (uint32_t)__cvta_generic_to_shared(p); }
__device__ __forceinline__ int otid() { int t; asm volatile("mov.u32 %0, %%tid.x;" : "=r"(t)); return t; }
__device__ __forceinline__ uint32_t mapa(uint32_t a, uint32_t r) { uint32_t o; asm volatile("mapa.shared::cluster.u32 %0, %1, %2;" : "=r"(o) : "r"(a), "r"(r)); return o; }
__device__ __forceinline__ void st_async_v4(uint32_t addr, float a, float b, float c, float d, uint32_t mbar) {
  asm volatile("st.async.weak.shared::cluster.mbarrier::complete_tx::bytes.v4.b32 [%0], {%1,%2,%3,%4}, [%5];" ::"r"(addr), "r"(__float_as_uint(a)), "r"(__float_as_uint(b)), "r"(__float_as_uint(c)), "r"(__float_as_uint(d)), "r"(mbar) : "memory"); }
__device__ __forceinline__ void mbar_init(uint32_t m, int c) { asm volatile("mbarrier.init.shared::cta.b64 [%0], %1;" ::"r"(m), "r"(c) : "memory"); }
__device__ __forceinline__ void mbar_expect(uint32_t m, int bytes) { asm volatile("mbarrier.arrive.expect_tx.shared::cta.b64 _, [%0], %1;" ::"r"(m), "r"(bytes) : "memory"); }
__device__ __forceinline__ void mbar_arrive(uint32_t m) { asm volatile("mbarrier.arrive.shared::cta.b64 _, [%0];" ::"r"(m) : "memory"); }
__device__ __forceinline__ void mbar_wait(uint32_t m, uint32_t parity) {
  uint32_t ok; int it = 0;
  do { asm volatile("{.reg .pred p; mbarrier.try_wait.parity.shared::cta.b64 p, [%1], %2; selp.u32 %0,1,0,p;}" : "=r"(ok) : "r"(m), "r"(parity) : "memory"); } while (!ok && ++it < SPIN_LIMIT); }
__device__ __forceinline__ void mbar_spin(uint32_t m, uint32_t parity) {
  uint32_t ok; int it = 0;
  do { asm volatile("{.reg .pred p; mbarrier.test_wait.parity.shared::cta.b64 p, [%1], %2; selp.u32 %0,1,0,p;}" : "=r"(ok) : "r"(m), "r"(parity) : "memory"); } while (!ok && ++it < SPIN_LIMIT); }
__device__ __forceinline__ void bar_sync(int id, int n) { asm volatile("bar.sync %0, %1;" ::"r"(id), "r"(n) : "memory"); }
__device__ __forceinline__ void bar_arrive(int id, int n) { asm volatile("bar.arrive %0, %1;" ::"r"(id), "r"(n) : "memory"); }
__device__ __forceinline__ int ld_acq(const int* p) { int v; asm volatile("ld.acquire.gpu.global.s32 %0, [%1];" : "=r"(v) : "l"(p) : "memory"); return v; }
__device__ __forceinline__ void wait_flag(const int* p, int target) { int it = 0; while (ld_acq(p) < target && ++it < SPIN_LIMIT) { __nanosleep(40); } }
__device__ __forceinline__ void fence_async() { asm volatile("fence.proxy.async.global;" ::: "memory"); }
__device__ __forceinline__ uint4 lds128(uint32_t a) { uint4 v; asm volatile("ld.shared.v4.u32 {%0,%1,%2,%3}, [%4];" : "=r"(v.x), "=r"(v.y), "=r"(v.z), "=r"(v.w) : "r"(a) : "memory"); return v; }
__device__ __forceinline__ void sts128(uint32_t a, uint4 v) { asm volatile("st.shared.v4.u32 [%0], {%1,%2,%3,%4};" ::"r"(a), "r"(v.x), "r"(v.y), "r"(v.z), "r"(v.w) : "memory"); }
__device__ __forceinline__ void sts32(uint32_t a, uint32_t v) { asm volatile("st.shared.u32 [%0], %1;" ::"r"(a), "r"(v) : "memory"); }
__device__ __forceinline__ void sts16(uint32_t a, float f) { unsigned short h = __bfloat16_as_ushort(__float2bfloat16(f)); asm volatile("st.shared.u16 [%0], %1;" ::"r"(a), "h"(h) : "memory"); }
__device__ __forceinline__ void ldsm4(uint32_t* r, uint32_t a) { asm volatile("ldmatrix.sync.aligned.m8n8.x4.shared.b16 {%0,%1,%2,%3}, [%4];" : "=r"(r[0]), "=r"(r[1]), "=r"(r[2]), "=r"(r[3]) : "r"(a) : "memory"); }
__device__ __forceinline__ void ldsm4t(uint32_t* r, uint32_t a) { asm volatile("ldmatrix.sync.aligned.m8n8.x4.trans.shared.b16 {%0,%1,%2,%3}, [%4];" : "=r"(r[0]), "=r"(r[1]), "=r"(r[2]), "=r"(r[3]) : "r"(a) : "memory"); }
__device__ __forceinline__ void mma16(float* c, uint32_t a0, uint32_t a1, uint32_t a2, uint32_t a3, uint32_t b0, uint32_t b1) {
  asm("mma.sync.aligned.m16n8k16.row.col.f32.bf16.bf16.f32 {%0,%1,%2,%3}, {%4,%5,%6,%7}, {%8,%9}, {%0,%1,%2,%3};" : "+f"(c[0]), "+f"(c[1]), "+f"(c[2]), "+f"(c[3]) : "r"(a0), "r"(a1), "r"(a2), "r"(a3), "r"(b0), "r"(b1)); }
__device__ __forceinline__ void mma8(float* c, uint32_t a0, uint32_t a1, uint32_t b0) {
  asm("mma.sync.aligned.m16n8k8.row.col.f32.bf16.bf16.f32 {%0,%1,%2,%3}, {%4,%5}, {%6}, {%0,%1,%2,%3};" : "+f"(c[0]), "+f"(c[1]), "+f"(c[2]), "+f"(c[3]) : "r"(a0), "r"(a1), "r"(b0)); }
__device__ __forceinline__ uint32_t pack2(float a, float b) { __nv_bfloat162 h = __floats2bfloat162_rn(a, b); return *(uint32_t*)&h; }
__device__ __forceinline__ float rbf(float x) { uint32_t r; asm("cvt.rn.bf16x2.f32 %0, %1, %2;" : "=r"(r) : "f"(x), "f"(0.f)); return __uint_as_float(r); }
__device__ __forceinline__ void cp16(uint32_t d, const void* s) { asm volatile("cp.async.cg.shared.global [%0], [%1], 16;" ::"r"(d), "l"(s) : "memory"); }
__device__ __forceinline__ void tma2d(uint32_t dst, const CUtensorMap* m, int c0, int c1, uint32_t mbar) {
  asm volatile("cp.async.bulk.tensor.2d.shared::cluster.global.mbarrier::complete_tx::bytes [%0], [%1, {%2,%3}], [%4];" ::"r"(dst), "l"(m), "r"(c0), "r"(c1), "r"(mbar) : "memory"); }
__device__ __forceinline__ uint64_t mkdesc(uint32_t addr, uint32_t lbo, uint32_t sbo) {
  return (uint64_t)((addr & 0x3FFFF) >> 4) | ((uint64_t)(lbo >> 4) << 16) | ((uint64_t)(sbo >> 4) << 32) | (1ull << 62); }

#define R8(i) "+f"(d[i]), "+f"(d[i+1]), "+f"(d[i+2]), "+f"(d[i+3]), "+f"(d[i+4]), "+f"(d[i+5]), "+f"(d[i+6]), "+f"(d[i+7])
__device__ __forceinline__ void wgmma256(float* d, uint64_t da, uint64_t db, int acc) {
  asm volatile("{.reg .pred p; setp.ne.b32 p, %130, 0;\n"
    "wgmma.mma_async.sync.aligned.m64n256k16.f32.bf16.bf16 {"
    "%0,%1,%2,%3,%4,%5,%6,%7,%8,%9,%10,%11,%12,%13,%14,%15,%16,%17,%18,%19,%20,%21,%22,%23,%24,%25,%26,%27,%28,%29,%30,%31,"
    "%32,%33,%34,%35,%36,%37,%38,%39,%40,%41,%42,%43,%44,%45,%46,%47,%48,%49,%50,%51,%52,%53,%54,%55,%56,%57,%58,%59,%60,%61,%62,%63,"
    "%64,%65,%66,%67,%68,%69,%70,%71,%72,%73,%74,%75,%76,%77,%78,%79,%80,%81,%82,%83,%84,%85,%86,%87,%88,%89,%90,%91,%92,%93,%94,%95,"
    "%96,%97,%98,%99,%100,%101,%102,%103,%104,%105,%106,%107,%108,%109,%110,%111,%112,%113,%114,%115,%116,%117,%118,%119,%120,%121,%122,%123,%124,%125,%126,%127"
    "}, %128, %129, p, 1, 1, 0, 1;}"
    : R8(0), R8(8), R8(16), R8(24), R8(32), R8(40), R8(48), R8(56), R8(64), R8(72), R8(80), R8(88), R8(96), R8(104), R8(112), R8(120)
    : "l"(da), "l"(db), "r"(acc)); }

__global__ void __launch_bounds__(256) prologue_kernel(const bf16* __restrict__ x, const bf16* __restrict__ mem0) {
  int tid = threadIdx.x, lane = tid & 31, warp = tid >> 5;
  int row = blockIdx.x * 8 + warp;
  {
    const uint4* src = (const uint4*)(x + (size_t)row * DM);
    uint4 u[2] = { src[lane], src[lane + 32] };
    float v[16];
    #pragma unroll
    for (int i = 0; i < 2; i++) { const __nv_bfloat162* h = (const __nv_bfloat162*)&u[i];
      #pragma unroll
      for (int k = 0; k < 4; k++) { float2 f = __bfloat1622float2(h[k]); v[i * 8 + 2 * k] = f.x; v[i * 8 + 2 * k + 1] = f.y; } }
    #pragma unroll
    for (int pass = 0; pass < 2; pass++) {
      float s = 0;
      #pragma unroll
      for (int i = 0; i < 16; i++) s += v[i];
      #pragma unroll
      for (int o = 16; o; o >>= 1) s += __shfl_xor_sync(~0u, s, o);
      float mf = s * (1.f / DM);
      float q = 0;
      #pragma unroll
      for (int i = 0; i < 16; i++) { float dd = v[i] - mf; q += dd * dd; }
      #pragma unroll
      for (int o = 16; o; o >>= 1) q += __shfl_xor_sync(~0u, q, o);
      float m = rbf(mf), var = rbf(q * (1.f / DM));
      float den = rbf(sqrtf(rbf(var + 1e-5f)));
      #pragma unroll
      for (int i = 0; i < 16; i++) v[i] = rbf(rbf(v[i] - m) / den);
      uint4 o4[2];
      #pragma unroll
      for (int i = 0; i < 2; i++) { o4[i].x = pack2(v[i*8], v[i*8+1]); o4[i].y = pack2(v[i*8+2], v[i*8+3]); o4[i].z = pack2(v[i*8+4], v[i*8+5]); o4[i].w = pack2(v[i*8+6], v[i*8+7]); }
      uint4* dst = (uint4*)((pass ? g_y : g_xn) + (size_t)row * DM);
      dst[lane] = o4[0]; dst[lane + 32] = o4[1];
    }
  }
  int gt = blockIdx.x * 256 + tid;
  float4 z4 = make_float4(0, 0, 0, 0);
  #pragma unroll
  for (int i = 0; i < 4; i++) { ((float4*)g_z)[gt + i * 65536] = z4; ((float4*)g_s)[gt + i * 65536] = z4; }
  for (int i = gt; i < NSTEP * 1536; i += 65536) {
    float4 val = z4;
    if (i < 1536) {
      int j = i / 768, c = i % 768, ci = c >> 8, w = (c & 255) >> 5, l = c & 31, g = l >> 2, t = l & 3;
      float e3[3];
      #pragma unroll
      for (int k = 0; k < 3; k++) { int e = ci * 3 + k; int mt = e >> 2, cc = e & 3;
        e3[k] = e < 8 ? __bfloat162float(mem0[(2 * t + (cc & 1)) * DM + 256 * j + 32 * w + 16 * mt + g + 8 * (cc >> 1)]) : 0.f; }
      val = make_float4(e3[0], e3[1], e3[2], 32.f);
    }
    (&g_acc[0][0][0])[i] = val;
  }
  if (gt < (int)(sizeof(Flags) / 4)) ((int*)&g_fl)[gt] = 0;
}

constexpr int R_WR = 0, R_WO = 65536, R_KT = 131072, KT_SZ = 40 * 256, R_VT = R_KT + 2 * KT_SZ, VT_SZ = 40 * 272,
              R_MEM = R_VT + 2 * VT_SZ, R_Q = R_MEM + 32 * 160, R_O = R_Q + 8 * 256, R_S = R_O + 8 * 256,
              R_SM = R_S + 8 * 40 * 4, R_RQK = R_SM + 1024, R_RV = R_RQK + 8192, R_WQ = R_RV + 4096, R_BAR = 232448 - 64, R_END = R_BAR + 64;
static_assert(R_WQ + 32768 <= R_BAR, "smem");
#define PI 350
#define LD1(v, p) asm volatile("ld.relaxed.gpu.global.v4.u32 {%0,%1,%2,%3}, [%4];" : "=r"(v.x), "=r"(v.y), "=r"(v.z), "=r"(v.w) : "l"(p) : "memory")
#define LD3(a, b, c) do { LD1(a, src); LD1(b, src + 256); LD1(c, src + 512); } while (0)
#define OK3(a, b, c) __all_sync(~0u, (a.w == 0x42000000u) && (b.w == 0x42000000u) && (c.w == 0x42000000u))
#define NW0 8
#define VD 0
#define KD 150
#define VCH 2
#define VP 3
__device__ __forceinline__ void wgmma8(float* d, uint64_t da, uint64_t db, int acc) {
  asm volatile("{.reg .pred p; setp.ne.b32 p, %6, 0;\n wgmma.mma_async.sync.aligned.m64n8k16.f32.bf16.bf16 {%0,%1,%2,%3}, %4, %5, p, 1, 1, 0, 0;}"
    : "+f"(d[0]), "+f"(d[1]), "+f"(d[2]), "+f"(d[3]) : "l"(da), "l"(db), "r"(acc)); }
__device__ __forceinline__ void stsm4(uint32_t a, uint32_t r0, uint32_t r1, uint32_t r2, uint32_t r3) { asm volatile("stmatrix.sync.aligned.m8n8.x4.shared.b16 [%0], {%1,%2,%3,%4};" ::"r"(a), "r"(r0), "r"(r1), "r"(r2), "r"(r3) : "memory"); }
__device__ __forceinline__ uint32_t swz(uint32_t r) { return ((r & 1) << 2) | ((r >> 1) & 3); }
__device__ __forceinline__ void stsm4t(uint32_t a, uint32_t r0, uint32_t r1, uint32_t r2, uint32_t r3) { asm volatile("stmatrix.sync.aligned.m8n8.x4.trans.shared.b16 [%0], {%1,%2,%3,%4};" ::"r"(a), "r"(r0), "r"(r1), "r"(r2), "r"(r3) : "memory"); }
__device__ __forceinline__ void stsm2(uint32_t a, uint32_t r0, uint32_t r1) { asm volatile("stmatrix.sync.aligned.m8n8.x2.shared.b16 [%0], {%1,%2};" ::"r"(a), "r"(r0), "r"(r1) : "memory"); }
__device__ __forceinline__ float ex2(float x) { float r; asm("ex2.approx.ftz.f32 %0, %1;" : "=f"(r) : "f"(x)); return r; }
#define REDV4(p, a, b, c) asm volatile("red.relaxed.gpu.global.add.v4.f32 [%0], {%1,%2,%3,%4};" ::"l"(p), "f"(a), "f"(b), "f"(c), "f"(1.0f) : "memory")
constexpr int SMEM_BYTES = 232448;
static_assert(R_END <= SMEM_BYTES, "smem");

__device__ __forceinline__ void recurrence(uint32_t sb, const bf16* __restrict__ Wq, const bf16* __restrict__ Wk, const bf16* __restrict__ Wv, const bf16* __restrict__ Wo) {
  const int tid = threadIdx.x, warp = tid >> 5, lane = tid & 31, g = lane >> 2, t = lane & 3;
  const int h = blockIdx.x >> 1, j = blockIdx.x & 1;
  const uint32_t peer = j ^ 1;
  const uint32_t mQ = sb + R_BAR, mV = sb + R_BAR + 8, mK = sb + R_BAR + 16;
  uint32_t A[2][16][4];
  const uint32_t stA = sb + 65536, stB = stA + 69632;
  const int lm = lane >> 3, lr = lane & 7;
  for (int i = tid; i < 256 * 16; i += 384) { int r = i >> 4, c = i & 15; size_t o = ((size_t)(256 * j + r)) * 4096 + h * 128 + c * 8;
    cp16(stA + r * 272 + c * 16, Wv + o); cp16(stB + r * 272 + c * 16, Wq + o); }
  asm volatile("cp.async.wait_all;" ::: "memory"); __syncthreads();
  if (warp < 4) {
    #pragma unroll
    for (int mt = 0; mt < 2; mt++)
      #pragma unroll
      for (int ks = 0; ks < 16; ks++) {
        int k = 32 * (ks >> 1) + 8 * (lr >> 1) + (lr & 1) + 4 * (ks & 1) + 2 * (lm >> 1);
        ldsm4t(A[mt][ks], stB + k * 272 + (32 * warp + 16 * mt + 8 * (lm & 1)) * 2);
      }
  } else {
    #pragma unroll 4
    for (int i = 0; i < 16; i++) { const int mt = (warp >> 2) - 1, ks = i, k = 32 * (ks >> 1) + 8 * (lr >> 1) + (lr & 1) + 4 * (ks & 1) + 2 * (lm >> 1); uint32_t r[4];
      ldsm4t(r, stA + k * 272 + (32 * (warp & 3) + 16 * mt + 8 * (lm & 1)) * 2);
      sts128(sb + R_WR + (((warp & 3) * 32 + ks * 2 + mt) * 32 + lane) * 16, make_uint4(r[0], r[1], r[2], r[3])); }
  }
  __syncthreads();
  for (int i = tid; i < 256 * 16; i += 384) { int r = i >> 4, c = i & 15; cp16(stA + r * 272 + c * 16, Wk + ((size_t)(256 * j + r)) * 4096 + h * 128 + c * 8);
    r = i >> 5; c = i & 31; cp16(stB + r * 528 + c * 16, Wo + ((size_t)(h * 128 + r)) * DM + 256 * j + c * 8); }
  asm volatile("cp.async.wait_all;" ::: "memory"); __syncthreads();
  if (warp >= 4) {
    #pragma unroll
    for (int mt = 0; mt < 2; mt++)
      #pragma unroll
      for (int ks = 0; ks < 16; ks++) {
        int k = 32 * (ks >> 1) + 8 * (lr >> 1) + (lr & 1) + 4 * (ks & 1) + 2 * (lm >> 1);
        ldsm4t(A[mt][ks], warp < 8 ? stA + k * 272 + (32 * (warp & 3) + 16 * mt + 8 * (lm & 1)) * 2
                                   : stB + (k & 127) * 528 + (64 * (warp & 3) + 32 * mt + 16 * (ks >> 3) + 8 * (lm & 1)) * 2);
      }
  }
  __syncthreads();
  if (warp < 4) {
    #pragma unroll
    for (int i = 0; i < 16; i++) sts128(sb + R_WQ + ((warp * 16 + i) * 32 + lane) * 16, make_uint4(A[1][i][0], A[1][i][1], A[1][i][2], A[1][i][3]));
  }
  __syncthreads();
  if (warp >= 8) {
    const uint32_t zero = blockIdx.y;
    #pragma unroll
    for (int i = 0; i < 32; i++) sts128(sb + R_WO + (((warp - 8) * 32 + i) * 32 + lane) * 16, make_uint4(A[i >> 4][i & 15][0], A[i >> 4][i & 15][1], A[i >> 4][i & 15][2], A[i >> 4][i & 15][3]));
    #pragma unroll
    for (int i = 0; i < 32; i++) { uint4 v = lds128(sb + R_WR + (((warp - 8) * 32 + i) * 32 + lane) * 16); A[i & 1][i >> 1][0] = v.x; A[i & 1][i >> 1][1] = v.y; A[i & 1][i >> 1][2] = v.z; A[i & 1][i >> 1][3] = v.w; }
    #pragma unroll 1
    for (int s = 0; s < NSTEP; s++) {
      const int tid = otid(), lane = tid & 31, wv = (tid >> 5) - 8, g = lane >> 2, t = lane & 3;
      if (tid == 256) mbar_expect(mV, 4096);
      const uint32_t fo = (t ^ swz(g)) << 4;
      TR(1);
      bar_sync(4, 384);
      if (VD) { long long t0 = clock64(); while (clock64() - t0 < VD); }
      TR(2);
      float c[4][4];
      #pragma unroll
      for (int i = 0; i < 4; i++) { c[i][0] = c[i][1] = c[i][2] = c[i][3] = 0.f; }
      #pragma unroll
      for (int p = 0; p < 8; p++) {
        uint4 b = ldc(R_MEM + g * 16 + t * 160 + p * 640);
        mma16(c[0], A[0][2*p][0], A[0][2*p][1], A[0][2*p][2], A[0][2*p][3], b.x, b.y);
        mma16(c[1], A[1][2*p][0], A[1][2*p][1], A[1][2*p][2], A[1][2*p][3], b.x, b.y);
        mma16(c[2], A[0][2*p+1][0], A[0][2*p+1][1], A[0][2*p+1][2], A[0][2*p+1][3], b.z, b.w);
        mma16(c[3], A[1][2*p+1][0], A[1][2*p+1][1], A[1][2*p+1][2], A[1][2*p+1][3], b.z, b.w);
      }
      #pragma unroll
      for (int i = 0; i < 4; i++) { c[0][i] += c[2][i]; c[1][i] += c[3][i]; }
      const uint32_t rx = sb + R_RV + (wv * 64 + lane) * 16;
      { uint32_t ra = mapa(rx, peer), rm = mapa(mV, peer);
        st_async_v4(ra, c[0][0], c[0][1], c[0][2], c[0][3], rm);
        st_async_v4(ra + 512, c[1][0], c[1][1], c[1][2], c[1][3], rm); }
      TR(4);
      const bool more = s < NSTEP - 1;
      uint32_t wb = sb + (wv * 1024 + lane) * 16;
      #pragma unroll
      for (int i = 0; i < NW0; i++) { uint4 v = lds128(wb + R_WO + i * 512); A[i >> 4][i & 15][0] = v.x; A[i >> 4][i & 15][1] = v.y; A[i >> 4][i & 15][2] = v.z; A[i >> 4][i & 15][3] = v.w; }
      TR(3);
      mbar_wait(mV, s & 1);
      TR(5);
      { uint4 r0 = lds128(rx), r1 = lds128(rx + 512);
        stsm4t(sb + R_VT + (s & 1) * VT_SZ + (32 + (lane & 7)) * 272 + (4 * wv + (lane >> 3)) * 16,
          pack2(c[0][0] + __uint_as_float(r0.x), c[0][1] + __uint_as_float(r0.y)), pack2(c[0][2] + __uint_as_float(r0.z), c[0][3] + __uint_as_float(r0.w)),
          pack2(c[1][0] + __uint_as_float(r1.x), c[1][1] + __uint_as_float(r1.y)), pack2(c[1][2] + __uint_as_float(r1.z), c[1][3] + __uint_as_float(r1.w))); }
      if (more) {
      bar_arrive(3, 256);
      TR(8);
      #pragma unroll
      for (int i = NW0; i < 32; i++) { uint4 v = lds128(wb + R_WO + i * 512); A[i >> 4][i & 15][0] = v.x; A[i >> 4][i & 15][1] = v.y; A[i >> 4][i & 15][2] = v.z; A[i >> 4][i & 15][3] = v.w;
        if ((i % THR) == THR - 1) wb += v.x & zero; }
      TR(10);
      bar_sync(7, 256);
      TR(9);
      #pragma unroll
      for (int i = 0; i < 4; i++) { c[i][0] = c[i][1] = c[i][2] = c[i][3] = 0.f; }
      #pragma unroll
      for (int p = 0; p < 4; p++) {
        uint4 b = ldc(R_O + g * 256 + (p >> 1) * 128 + (fo ^ ((p & 1) << 6)));
        #pragma unroll
        for (int mt = 0; mt < 4; mt++) { const uint32_t* a = A[mt >> 1][(mt & 1) * 8 + 2 * p]; mma16(c[mt], a[0], a[1], a[2], a[3], b.x, b.y); }
        #pragma unroll
        for (int mt = 0; mt < 4; mt++) { const uint32_t* a = A[mt >> 1][(mt & 1) * 8 + 2 * p + 1]; mma16(c[mt], a[0], a[1], a[2], a[3], b.z, b.w); }
      }
      TR(6);
      float4* dst = &g_acc[s + 1][j][wv * 64 + lane];
      REDV4(dst, c[0][0], c[0][1], c[0][2]); REDV4(dst + 256, c[0][3], c[1][0], c[1][1]); REDV4(dst + 512, c[1][2], c[1][3], 0.f);
      REDV4(dst + 32, c[2][0], c[2][1], c[2][2]); REDV4(dst + 288, c[2][3], c[3][0], c[3][1]); REDV4(dst + 544, c[3][2], c[3][3], 0.f);
      bar_arrive(8, 352);
      TR(7);
      } else bar_sync(6, 256);
      { const int vt = tid - 256;
        if (j == 0) { const int r = vt >> 4, cc = vt & 15; uint4 v = lds128(sb + R_KT + (s & 1) * KT_SZ + (32 + r) * 256 + ((cc ^ swz(r)) << 4));
          __stcg((uint4*)(g_km + ((size_t)(s * 32 + h)) * 1024) + vt, v); }
        else { uint32_t vb = sb + R_VT + (s & 1) * VT_SZ + 32 * 272 + vt * 2; uint32_t e[8];
          #pragma unroll
          for (int k = 0; k < 8; k++) { unsigned short x; asm volatile("ld.shared.u16 %0, [%1];" : "=h"(x) : "r"(vb + k * 272) : "memory"); e[k] = x; }
          __stcg((uint4*)(g_vmT + ((size_t)(s * 32 + h)) * 1024) + vt, make_uint4(e[0] | (e[1] << 16), e[2] | (e[3] << 16), e[4] | (e[5] << 16), e[6] | (e[7] << 16))); }
        if (!more) { __syncwarp(); if (lane == 0) { __threadfence(); atomicAdd(&g_fl.prog[15][h], 1); } } }
      #pragma unroll
      for (int i = 0; i < 32; i++) { uint4 v = lds128(wb + R_WR + i * 512); A[i & 1][i >> 1][0] = v.x; A[i & 1][i >> 1][1] = v.y; A[i & 1][i >> 1][2] = v.z; A[i & 1][i >> 1][3] = v.w; }
    }
    return;
  }
  const float scale = 0.08838834764831845f, l2e = 1.4426950408889634f;
  auto prefetch = [&](int s) {
    const int vt = otid() - 160;
    if ((s & 3) == 0) { wait_flag(&g_fl.tile[s >> 2][h >> 1], 1); wait_flag(&g_fl.tile[s >> 2][16 + (h >> 1)], 1); }
    const int r = vt >> 4, c = vt & 15;
    const bf16* src = g_qkv + (size_t)(32 * s + r) * QW + h * 128 + c * 8;
    uint32_t kb = sb + R_KT + (s & 1) * KT_SZ + r * 256, vb = sb + R_VT + (s & 1) * VT_SZ + r * 272 + c * 16;
    #pragma unroll
    for (int i = 0; i < 8; i++) { cp16(kb + i * 1024 + ((c ^ swz(r + 4 * i)) << 4), src + (size_t)i * 4 * QW); cp16(vb + i * 1088, src + (size_t)i * 4 * QW + 4096); }
  };
  if (warp >= 4) {
  if (warp == 5 || warp == 6) prefetch(0);
  #pragma unroll 1
  for (int s = 0; s < NSTEP; s++) {
    TR(0); TR(1);
    const int tid = otid(), lane = tid & 31, warp = tid >> 5, g = lane >> 2, t = lane & 3;
    const uint32_t fo = (t ^ swz(g)) << 4;
    {
      if (tid == 0) mbar_expect(mQ, 4096);
      if (tid == 128) mbar_expect(mK, 4096);
      const float4* src = &g_acc[s][j][tid];
      uint4 v0, v1, v2; int it = 0;
      uint4 u0, u1, u2;
      LD3(v0, v1, v2);
      { long long t0 = clock64(); while (clock64() - t0 < PI); }
      while (true) {
        LD3(u0, u1, u2);
        if (OK3(v0, v1, v2)) break;
        LD3(v0, v1, v2);
        if (OK3(u0, u1, u2) || ++it >= SPIN_LIMIT) { v0 = u0; v1 = u1; v2 = u2; break; }
      }
      __syncwarp();
      stsm4t(sb + R_MEM + (lane & 7) * 16 + (4 * warp + (lane >> 3)) * 160,
        pack2(__uint_as_float(v0.x), __uint_as_float(v0.y)), pack2(__uint_as_float(v0.z), __uint_as_float(v1.x)),
        pack2(__uint_as_float(v1.y), __uint_as_float(v1.z)), pack2(__uint_as_float(v2.x), __uint_as_float(v2.y)));
    }
    TR(2);
    asm volatile("cp.async.wait_all;" ::: "memory");
    bar_sync(1, 256);
    { long long t0 = clock64(); while (clock64() - t0 < KD); }
    if (VP < 0) bar_arrive(4, 384);
    TR(3);
    float c[4][4];
    #pragma unroll
    for (int i = 0; i < 4; i++) { c[i][0] = c[i][1] = c[i][2] = c[i][3] = 0.f; }
    #pragma unroll
    for (int p = 0; p < 8; p++) {
      uint4 b = ldc(R_MEM + g * 16 + t * 160 + p * 640);
      mma16(c[0], A[0][2*p][0], A[0][2*p][1], A[0][2*p][2], A[0][2*p][3], b.x, b.y);
      mma16(c[1], A[1][2*p][0], A[1][2*p][1], A[1][2*p][2], A[1][2*p][3], b.x, b.y);
      mma16(c[2], A[0][2*p+1][0], A[0][2*p+1][1], A[0][2*p+1][2], A[0][2*p+1][3], b.z, b.w);
      mma16(c[3], A[1][2*p+1][0], A[1][2*p+1][1], A[1][2*p+1][2], A[1][2*p+1][3], b.z, b.w);
      if (p == VP) asm volatile("bar.arrive 4, 384;");
    }
    #pragma unroll
    for (int i = 0; i < 4; i++) { c[0][i] += c[2][i]; c[1][i] += c[3][i]; }
    const uint32_t rx = sb + R_RQK + (warp * 64 + lane) * 16;
    { uint32_t ra = mapa(rx, peer), rm = mapa(mK, peer);
      st_async_v4(ra, c[0][0], c[0][1], c[0][2], c[0][3], rm);
      st_async_v4(ra + 512, c[1][0], c[1][1], c[1][2], c[1][3], rm); }
    if (VP > 7) bar_arrive(4, 384);
    TR(4);
    const uint32_t so = (lane & 7) * 256 + (((4 * (warp & 3) + (lane >> 3)) ^ swz(lane & 7)) << 4);
    mbar_wait(mK, s & 1);
    TR(5);
    uint32_t m0, m1, m2, m3;
    { uint4 r0 = lds128(rx), r1 = lds128(rx + 512);
      m0 = pack2(c[0][0] + __uint_as_float(r0.x), c[0][1] + __uint_as_float(r0.y)); m1 = pack2(c[0][2] + __uint_as_float(r0.z), c[0][3] + __uint_as_float(r0.w));
      m2 = pack2(c[1][0] + __uint_as_float(r1.x), c[1][1] + __uint_as_float(r1.y)); m3 = pack2(c[1][2] + __uint_as_float(r1.z), c[1][3] + __uint_as_float(r1.w)); }
    stsm4t(sb + R_KT + (s & 1) * KT_SZ + 32 * 256 + so, m0, m1, m2, m3);
    if (s == NSTEP - 1) { bar_arrive(6, 256); break; }
    asm("movmatrix.sync.aligned.m8n8.trans.b16 %0, %0;" : "+r"(m0)); asm("movmatrix.sync.aligned.m8n8.trans.b16 %0, %0;" : "+r"(m1));
    asm("movmatrix.sync.aligned.m8n8.trans.b16 %0, %0;" : "+r"(m2)); asm("movmatrix.sync.aligned.m8n8.trans.b16 %0, %0;" : "+r"(m3));
    TR(8);
    bar_sync(9, 256);
    TR(9);
    { uint32_t qa[4]; ldsm4(qa, sb + R_Q + so);
      #pragma unroll
      for (int i = 0; i < 2; i++) { c[i][0] = c[i][1] = c[i][2] = c[i][3] = 0.f; }
      mma16(c[0], qa[0], 0, qa[1], 0, m0, m1); mma16(c[1], qa[2], 0, qa[3], 0, m2, m3);
      asm volatile("st.shared.v2.f32 [%0], {%1,%2};" ::"r"(sb + R_SM + (warp - 4) * 256 + lane * 8), "f"(c[0][0] + c[1][0]), "f"(c[0][1] + c[1][1]) : "memory"); }
    bar_arrive(2, 256);
    TR(10);
    if ((warp == 5 || warp == 6) && s < NSTEP - 2) prefetch(s + 1);
    TR(7);
    if (warp == 7) { if ((s & 3) == 1 && s > 1 && lane == 0) asm volatile("red.release.gpu.global.add.s32 [%0], 4;" ::"l"(&g_fl.prog[(s - 2) >> 2][h]) : "memory"); __syncwarp(); }
    else bar_sync(8, 352);
    { long long t0 = clock64(); while (clock64() - t0 < PDELAY); }
  }
  return;
  }
  #pragma unroll 1
  for (int s = 0; s < NSTEP; s++) {
    TR(0); TR(1);
    const int tid = otid(), lane = tid & 31, warp = tid >> 5, g = lane >> 2, t = lane & 3;
    const uint32_t fo = (t ^ swz(g)) << 4;
    {
      if (tid == 0) mbar_expect(mQ, 4096);
      if (tid == 128) mbar_expect(mK, 4096);
      const float4* src = &g_acc[s][j][tid];
      uint4 v0, v1, v2; int it = 0;
      uint4 u0, u1, u2;
      LD3(v0, v1, v2);
      { long long t0 = clock64(); while (clock64() - t0 < PI); }
      while (true) {
        LD3(u0, u1, u2);
        if (OK3(v0, v1, v2)) break;
        LD3(v0, v1, v2);
        if (OK3(u0, u1, u2) || ++it >= SPIN_LIMIT) { v0 = u0; v1 = u1; v2 = u2; break; }
      }
      __syncwarp();
      stsm4t(sb + R_MEM + (lane & 7) * 16 + (4 * warp + (lane >> 3)) * 160,
        pack2(__uint_as_float(v0.x), __uint_as_float(v0.y)), pack2(__uint_as_float(v0.z), __uint_as_float(v1.x)),
        pack2(__uint_as_float(v1.y), __uint_as_float(v1.z)), pack2(__uint_as_float(v2.x), __uint_as_float(v2.y)));
    }
    TR(2);

    bar_sync(1, 256);
    bar_arrive(4, 384);
    TR(3);
    float c[4][4];
    #pragma unroll
    for (int i = 0; i < 4; i++) { c[i][0] = c[i][1] = c[i][2] = c[i][3] = 0.f; }
    #pragma unroll
    for (int p = 0; p < 8; p++) {
      uint4 b = ldc(R_MEM + g * 16 + t * 160 + p * 640);
      mma16(c[0], A[0][2*p][0], A[0][2*p][1], A[0][2*p][2], A[0][2*p][3], b.x, b.y);
      mma16(c[1], A[1][2*p][0], A[1][2*p][1], A[1][2*p][2], A[1][2*p][3], b.x, b.y);
      mma16(c[2], A[0][2*p+1][0], A[0][2*p+1][1], A[0][2*p+1][2], A[0][2*p+1][3], b.z, b.w);
      mma16(c[3], A[1][2*p+1][0], A[1][2*p+1][1], A[1][2*p+1][2], A[1][2*p+1][3], b.z, b.w);
    }
    #pragma unroll
    for (int i = 0; i < 4; i++) { c[0][i] += c[2][i]; c[1][i] += c[3][i]; }
    const uint32_t rx = sb + R_RQK + (warp * 64 + lane) * 16;
    { uint32_t ra = mapa(rx, peer), rm = mapa(mQ, peer);
      st_async_v4(ra, c[0][0], c[0][1], c[0][2], c[0][3], rm);
      st_async_v4(ra + 512, c[1][0], c[1][1], c[1][2], c[1][3], rm); }
    TR(4);
    const uint32_t so = (lane & 7) * 256 + (((4 * (warp & 3) + (lane >> 3)) ^ swz(lane & 7)) << 4);
    if (s == NSTEP - 1) { mbar_wait(mQ, s & 1); break; }
    uint4 kf[4]; uint32_t vf[4][4];
    const uint32_t vb = sb + R_VT + (s & 1) * VT_SZ + (lane & 15) * 272 + (32 * warp + 8 * (lane >> 4)) * 2;
    #pragma unroll
    for (int p = 0; p < 4; p++) kf[p] = lds128(sb + R_KT + (s & 1) * KT_SZ + warp * 2048 + g * 256 + (p >> 1) * 128 + (fo ^ ((p & 1) << 6)));
    #pragma unroll
    for (int i = 0; i < 4; i++) ldsm4t(vf[i], vb + (i >> 1) * 16 * 272 + (i & 1) * 32);
    mbar_wait(mQ, s & 1);
    TR(5);
    uint32_t m0, m1, m2, m3;
    { uint4 r0 = lds128(rx), r1 = lds128(rx + 512);
      m0 = pack2(c[0][0] + __uint_as_float(r0.x), c[0][1] + __uint_as_float(r0.y)); m1 = pack2(c[0][2] + __uint_as_float(r0.z), c[0][3] + __uint_as_float(r0.w));
      m2 = pack2(c[1][0] + __uint_as_float(r1.x), c[1][1] + __uint_as_float(r1.y)); m3 = pack2(c[1][2] + __uint_as_float(r1.z), c[1][3] + __uint_as_float(r1.w)); }
    stsm4t(sb + R_Q + so, m0, m1, m2, m3);
    TR(8);
    bar_arrive(9, 256); bar_sync(5, 128);
    TR(9);
    {
      uint4 qa[4];
      #pragma unroll
      for (int p = 0; p < 4; p++) qa[p] = lds128(sb + R_Q + g * 256 + (p >> 1) * 128 + (fo ^ ((p & 1) << 6)));
      #pragma unroll
      for (int i = 0; i < 4; i++) { c[i][0] = c[i][1] = c[i][2] = c[i][3] = 0.f; }
      #pragma unroll
      for (int p = 0; p < 4; p++) { mma16(c[(p & 1) * 2], qa[p].x, 0, qa[p].y, 0, kf[p].x, kf[p].y); mma16(c[(p & 1) * 2 + 1], qa[p].z, 0, qa[p].w, 0, kf[p].z, kf[p].w); }
      float a = rbf(rbf((c[0][0] + c[1][0]) + (c[2][0] + c[3][0])) * scale) * l2e, b = rbf(rbf((c[0][1] + c[1][1]) + (c[2][1] + c[3][1])) * scale) * l2e;
      asm volatile("st.shared.v2.f32 [%0], {%1,%2};" ::"r"(sb + R_S + g * 160 + (8 * warp + 2 * t) * 4), "f"(a), "f"(b) : "memory");
    }
    TR(10);
    bar_sync(10, 128);
    float sv[8], pm[8];
    #pragma unroll
    for (int i = 0; i < 4; i++) asm volatile("ld.shared.v2.f32 {%0,%1}, [%2];" : "=f"(sv[2*i]), "=f"(sv[2*i+1]) : "r"(sb + R_S + g * 160 + (8 * i + 2 * t) * 4) : "memory");
    float mx = fmaxf(fmaxf(fmaxf(sv[0], sv[1]), fmaxf(sv[2], sv[3])), fmaxf(fmaxf(sv[4], sv[5]), fmaxf(sv[6], sv[7])));
    mx = fmaxf(mx, __shfl_xor_sync(~0u, mx, 1)); mx = fmaxf(mx, __shfl_xor_sync(~0u, mx, 2));
    uint32_t P[5];
    #pragma unroll
    for (int i = 0; i < 4; i++) P[i] = pack2(ex2(sv[2*i] - mx), ex2(sv[2*i+1] - mx));
    #pragma unroll
    for (int i = 0; i < 4; i++) { c[i][0] = c[i][1] = c[i][2] = c[i][3] = 0.f; }
    #pragma unroll
    for (int kk = 0; kk < 2; kk++) {
      mma16(c[0], P[2*kk], 0, P[2*kk+1], 0, vf[2*kk][0], vf[2*kk][1]); mma16(c[1], P[2*kk], 0, P[2*kk+1], 0, vf[2*kk][2], vf[2*kk][3]);
      mma16(c[2], P[2*kk], 0, P[2*kk+1], 0, vf[2*kk+1][0], vf[2*kk+1][1]); mma16(c[3], P[2*kk], 0, P[2*kk+1], 0, vf[2*kk+1][2], vf[2*kk+1][3]);
    }
    float sum = 0.f;
    #pragma unroll
    for (int i = 0; i < 4; i++) sum += __uint_as_float(P[i] << 16) + __uint_as_float(P[i] & 0xffff0000u);
    TR(11);
    bar_sync(2, 256);
    #pragma unroll
    for (int i = 0; i < 4; i++) asm volatile("ld.shared.v2.f32 {%0,%1}, [%2];" : "=f"(pm[2*i]), "=f"(pm[2*i+1]) : "r"(sb + R_SM + i * 256 + lane * 8) : "memory");
    const float s8 = rbf(rbf((pm[0] + pm[2]) + (pm[4] + pm[6])) * scale) * l2e, s9 = rbf(rbf((pm[1] + pm[3]) + (pm[5] + pm[7])) * scale) * l2e;
    float mg = fmaxf(mx, fmaxf(s8, s9));
    mg = fmaxf(mg, __shfl_xor_sync(~0u, mg, 1)); mg = fmaxf(mg, __shfl_xor_sync(~0u, mg, 2));
    const float fs = ex2(mx - mg);
    P[4] = pack2(ex2(s8 - mg), ex2(s9 - mg));
    #pragma unroll
    for (int i = 0; i < 4; i++) { c[i][0] *= fs; c[i][1] *= fs; }
    sum = fmaf(sum, fs, __uint_as_float(P[4] << 16) + __uint_as_float(P[4] & 0xffff0000u));
    sum += __shfl_xor_sync(~0u, sum, 1); sum += __shfl_xor_sync(~0u, sum, 2);
    float inv; asm("rcp.approx.ftz.f32 %0, %1;" : "=f"(inv) : "f"(sum));
    TR(6);
    bar_sync(3, 256);
    { uint32_t r[4]; ldsm4t(r, sb + R_VT + (s & 1) * VT_SZ + (32 + (lane & 7)) * 272 + (4 * warp + (lane >> 3)) * 16);
      #pragma unroll
      for (int i = 0; i < 4; i++) mma8(c[i], P[4], 0, r[i]); }
    asm volatile("stmatrix.sync.aligned.m8n8.x4.shared.b16 [%0], {%1,%2,%3,%4};" ::"r"(sb + R_O + so),
      "r"(pack2(c[0][0] * inv, c[0][1] * inv)), "r"(pack2(c[1][0] * inv, c[1][1] * inv)), "r"(pack2(c[2][0] * inv, c[2][1] * inv)), "r"(pack2(c[3][0] * inv, c[3][1] * inv)) : "memory");
    bar_arrive(7, 256);
    TR(7);
    bar_sync(8, 352);
    long long t0 = clock64();
    #pragma unroll
    for (int i = 0; i < 16; i++) { uint4 v = lds128(sb + R_WQ + ((warp * 16 + i) * 32 + lane) * 16); A[1][i][0] = v.x; A[1][i][1] = v.y; A[1][i][2] = v.z; A[1][i][3] = v.w; }
    while (clock64() - t0 < PDELAY);
  }
}

constexpr int I_M1 = 512, I_Q = 624, I_M2 = 880, I_AT = 1008, I_G = I_AT + 32, GSZ = 56, I_END = I_G + 15 * GSZ + 24;
constexpr int B_STG = 4 * 49152, B_BAR = B_STG + 8 * 2304;
struct Item { int type, rb, nt, ks; };
__device__ __forceinline__ Item decode(int it) {
  Item r; r.ks = 0;
  if (it < I_M1) { r.type = 0; r.rb = it >> 5; r.nt = it & 31; }
  else if (it < I_Q) { int i = it - I_M1; r.type = 1; r.rb = i / 7; r.nt = i % 7; }
  else if (it < I_M2) { int i = it - I_Q; r.type = 0; r.rb = i >> 4; r.nt = 32 + (i & 15); }
  else if (it < I_AT) { int i = it - I_M2; r.type = 2; r.rb = i >> 3; r.nt = (i >> 2) & 1; r.ks = i & 3; }
  else if (it < I_G) { r.type = 3; r.rb = 0; r.nt = it - I_AT; }
  else {
    int i = it - I_G, gi = i / GSZ, q = i % GSZ; if (gi == 15) q += 32;
    if (q < 32) { r.type = 3; r.rb = gi + 1; r.nt = q; }
    else if (q < 48) { r.type = 4; r.rb = gi; r.nt = (q - 32) >> 3; r.ks = (q - 32) & 7; }
    else { r.type = 5; r.rb = gi; r.nt = q - 48; } }
  return r;
}
__device__ __forceinline__ float gelu_t(float x) { float u = 0.7978845608028654f * (x + 0.044715f * x * x * x); float th; asm("tanh.approx.f32 %0, %1;" : "=f"(th) : "f"(u)); float hx = 0.5f * x; return fmaf(hx, th, hx); }

__device__ __forceinline__ void bulk(uint32_t sb, const Maps& mp, const bf16* __restrict__ x, const bf16* __restrict__ b1, const bf16* __restrict__ b2, bf16* __restrict__ out) {
  const int tid = threadIdx.x, warp = tid >> 5, lane = tid & 31, g = lane >> 2, t = lane & 3;
  const int bid = blockIdx.x - NREC;
  const uint32_t full = sb + B_BAR, empty = sb + B_BAR + 32, ifull = sb + B_BAR + 64, iempty = sb + B_BAR + 80;
  volatile int* ring = (volatile int*)(__cvta_shared_to_generic(sb + B_BAR + 96));
  if (warp >= 8) {
    asm volatile("setmaxnreg.dec.sync.aligned.u32 40;");
    if (tid == 256) {
      uint32_t st = 0, ph = 0;
      for (int n = 0;; n++) {
        int it = n == 0 ? bid : NBULK + atomicAdd(&g_fl.next, 1);
        Item I = decode(it);
        if (it < I_END) {
          if (I.type == 5) { wait_flag(&g_fl.s[I.rb][0], 16); wait_flag(&g_fl.z[I.rb][0], 8); }
          else if (I.type == 3) { wait_flag(&g_fl.prog[I.rb][I.nt], 8); wait_flag(&g_fl.tile[I.rb][I.nt >> 1], 1); wait_flag(&g_fl.tile[I.rb][16 + (I.nt >> 1)], 1); wait_flag(&g_fl.tile[I.rb][32 + (I.nt >> 1)], 1); fence_async(); }
          else if (I.type == 2) { wait_flag(&g_fl.hid[I.rb], 7); fence_async(); }
          else if (I.type == 4) { wait_flag(&g_fl.o[I.rb][I.ks], 4); fence_async(); }
        }
        mbar_wait(iempty + (n & 1) * 8, ((n >> 1) & 1) ^ 1);
        ring[n & 1] = it; mbar_arrive(ifull + (n & 1) * 8);
        if (it >= I_END) break;
        if (I.type == 5) continue;
        if (I.type == 3) {
          for (int m = 0; m < 3; m++) {
            mbar_wait(empty + st * 8, ph ^ 1);
            mbar_expect(full + st * 8, 32768);
            int col = (m == 0 ? 8192 : (m == 1 ? 0 : 4096)) + I.nt * 128;
            tma2d(sb + st * 49152, &mp.qkv, col, I.rb * 128, full + st * 8);
            tma2d(sb + st * 49152 + 16384, &mp.qkv, col + 64, I.rb * 128, full + st * 8);
            if (++st == 4) { st = 0; ph ^= 1; }
          }
          continue;
        }
        const CUtensorMap *ma, *mb; int nkb = 8, kb0 = 0, n0;
        if (I.type == 0) { ma = &mp.xn; mb = I.nt < 16 ? &mp.wk : (I.nt < 32 ? &mp.wv : &mp.wq); n0 = (I.nt & 15) * 256; }
        else if (I.type == 1) { ma = &mp.y; mb = &mp.w1; n0 = I.nt * 256; }
        else if (I.type == 2) { ma = &mp.hid; mb = &mp.w2; n0 = I.nt * 256; nkb = 7; kb0 = I.ks * 7; }
        else { ma = &mp.o; mb = &mp.wo; n0 = I.nt * 256; kb0 = I.ks * 8; }
        for (int kb = kb0; kb < kb0 + nkb; kb++) {
          mbar_wait(empty + st * 8, ph ^ 1);
          mbar_expect(full + st * 8, 49152);
          uint32_t sa = sb + st * 49152;
          tma2d(sa, ma, kb * 64, I.rb * 128, full + st * 8);
          #pragma unroll
          for (int q = 0; q < 4; q++) tma2d(sa + 16384 + q * 8192, mb, n0 + q * 64, kb * 64, full + st * 8);
          if (++st == 4) { st = 0; ph ^= 1; }
        }
      }
    } else if (warp == 9) {
      for (int n = 0;; n++) {
        mbar_wait(ifull + (n & 1) * 8, (n >> 1) & 1);
        int it = ring[n & 1];
        if (it >= I_END) break;
        Item I = decode(it);
        bar_sync(6 + (n & 1), 288);
        if (lane == 0) {
          if (I.type != 5) {
            fence_async(); __threadfence();
            int* f = I.type == 0 ? &g_fl.tile[I.rb][I.nt] : I.type == 1 ? &g_fl.hid[I.rb] : I.type == 2 ? &g_fl.z[I.rb][0] : I.type == 3 ? &g_fl.o[I.rb][I.nt >> 2] : &g_fl.s[I.rb][0];
            atomicAdd(f, 1);
          }
          mbar_arrive(iempty + (n & 1) * 8);
        }
      }
    }
    return;
  }
  asm volatile("setmaxnreg.inc.sync.aligned.u32 232;");
  const int wg = warp >> 2;
  const uint32_t stg = sb + B_STG + warp * 2304;
  const int lm = lane >> 3, lr = lane & 7;
  uint32_t st = 0, ph = 0;
  float d[128];
  #pragma unroll 1
  for (int n = 0;; n++) {
    mbar_wait(ifull + (n & 1) * 8, (n >> 1) & 1);
    const int it = ring[n & 1];
    __syncwarp(); if (lane == 0) mbar_arrive(iempty + (n & 1) * 8);
    if (it >= I_END) break;
    Item I = decode(it);
    const int row0 = I.rb * 128 + warp * 16;
    TB(0);
    if (I.type == 5) {
      #pragma unroll
      for (int i = 0; i < 4; i++) {
        size_t off = (size_t)(I.rb * 128 + I.nt * 16 + warp * 2 + (i >> 1)) * DM + (i & 1) * 256 + lane * 8;
        float4 s0 = __ldcg((const float4*)(g_s + off)), s1 = __ldcg((const float4*)(g_s + off + 4));
        float4 z0 = __ldcg((const float4*)(g_z + off)), z1 = __ldcg((const float4*)(g_z + off + 4));
        uint4 xv = *(const uint4*)(x + off), bv = *(const uint4*)(b2 + (i & 1) * 256 + lane * 8);
        float sa[8] = {s0.x, s0.y, s0.z, s0.w, s1.x, s1.y, s1.z, s1.w}, za[8] = {z0.x, z0.y, z0.z, z0.w, z1.x, z1.y, z1.z, z1.w}, r[8];
        #pragma unroll
        for (int e = 0; e < 8; e++) { float xx = __bfloat162float(((const bf16*)&xv)[e]), bb = __bfloat162float(((const bf16*)&bv)[e]);
          float u = rbf(rbf(za[e]) + bb); float gg = rbf(__fdividef(u, 1.f + __expf(-u))); r[e] = xx + rbf(rbf(sa[e]) * gg); }
        *(uint4*)(out + off) = make_uint4(pack2(r[0], r[1]), pack2(r[2], r[3]), pack2(r[4], r[5]), pack2(r[6], r[7]));
      }
      bar_arrive(6 + (n & 1), 288);
      continue;
    }
    if (I.type == 3) {
      const int h = I.nt, seg = warp >> 1, half = warp & 1, step = I.rb * 4 + seg;
      uint32_t kmr[16], vmr[16];
      { const uint32_t* km = (const uint32_t*)(g_km + ((size_t)(step * 32 + h)) * 1024) + g * 64 + t;
        const uint32_t* vm = (const uint32_t*)(g_vmT + ((size_t)(step * 32 + h)) * 1024) + g * 4 + t;
        #pragma unroll
        for (int i = 0; i < 16; i++) { kmr[i] = __ldcg(km + i * 4); vmr[i] = __ldcg(vm + i * 32); } }
      uint32_t sQ = sb + st * 49152; mbar_wait(full + st * 8, ph); uint32_t eQ = empty + st * 8; if (++st == 4) { st = 0; ph ^= 1; }
      uint32_t sK = sb + st * 49152; mbar_wait(full + st * 8, ph); uint32_t eK = empty + st * 8; if (++st == 4) { st = 0; ph ^= 1; }
      float sc[5][4];
      #pragma unroll
      for (int i = 0; i < 5; i++) { sc[i][0] = sc[i][1] = sc[i][2] = sc[i][3] = 0.f; }
      #pragma unroll
      for (int ks = 0; ks < 8; ks++) {
        uint32_t a[4]; { int r = warp * 16 + 8 * (lm & 1) + lr, c8 = 2 * ks + (lm >> 1); ldsm4(a, sQ + (c8 >> 3) * 16384 + r * 128 + (((c8 & 7) ^ (r & 7)) << 4)); }
        #pragma unroll
        for (int np = 0; np < 2; np++) {
          if (np == 1 && half == 0) continue;
          uint32_t b[4]; int r = seg * 32 + 16 * np + 8 * (lm >> 1) + lr, c8 = 2 * ks + (lm & 1);
          ldsm4(b, sK + (c8 >> 3) * 16384 + r * 128 + (((c8 & 7) ^ (r & 7)) << 4));
          mma16(sc[2*np], a[0], a[1], a[2], a[3], b[0], b[1]); mma16(sc[2*np+1], a[0], a[1], a[2], a[3], b[2], b[3]);
        }
        mma16(sc[4], a[0], a[1], a[2], a[3], kmr[2*ks], kmr[2*ks+1]);
      }
      __syncwarp(); if (lane == 0) { mbar_arrive(eQ); mbar_arrive(eK); }
      const float scale = 0.08838834764831845f;
      uint32_t P[5][2];
      #pragma unroll
      for (int rr = 0; rr < 2; rr++) {
        const int qi = 16 * half + g + 8 * rr;
        float mx = -3.0e38f;
        #pragma unroll
        for (int i = 0; i < 5; i++)
          #pragma unroll
          for (int e = 0; e < 2; e++) { float v = rbf(rbf(sc[i][2*rr+e]) * scale); if (i < 4 && 8 * i + 2 * t + e > qi) v = -1.0e9f; sc[i][2*rr+e] = v; mx = fmaxf(mx, v); }
        mx = fmaxf(mx, __shfl_xor_sync(~0u, mx, 1)); mx = fmaxf(mx, __shfl_xor_sync(~0u, mx, 2));
        float sum = 0;
        #pragma unroll
        for (int i = 0; i < 5; i++)
          #pragma unroll
          for (int e = 0; e < 2; e++) { float v = __expf(sc[i][2*rr+e] - mx); sc[i][2*rr+e] = v; sum += v; }
        sum += __shfl_xor_sync(~0u, sum, 1); sum += __shfl_xor_sync(~0u, sum, 2);
        float inv = __fdividef(1.f, sum);
        #pragma unroll
        for (int i = 0; i < 5; i++) P[i][rr] = pack2(sc[i][2*rr] * inv, sc[i][2*rr+1] * inv);
      }
      uint32_t sV = sb + st * 49152; mbar_wait(full + st * 8, ph); uint32_t eV = empty + st * 8; if (++st == 4) { st = 0; ph ^= 1; }
      #pragma unroll
      for (int i = 0; i < 64; i++) d[i] = 0.f;
      #pragma unroll
      for (int n2 = 0; n2 < 8; n2++) {
        #pragma unroll
        for (int kk = 0; kk < 2; kk++) {
          if (kk == 1 && half == 0) continue;
          uint32_t b[4]; int r = seg * 32 + 16 * kk + 8 * (lm & 1) + lr, c8 = 2 * n2 + (lm >> 1);
          ldsm4t(b, sV + (c8 >> 3) * 16384 + r * 128 + (((c8 & 7) ^ (r & 7)) << 4));
          mma16(d + 8 * n2, P[2*kk][0], P[2*kk][1], P[2*kk+1][0], P[2*kk+1][1], b[0], b[1]);
          mma16(d + 8 * n2 + 4, P[2*kk][0], P[2*kk][1], P[2*kk+1][0], P[2*kk+1][1], b[2], b[3]);
        }
        mma8(d + 8 * n2, P[4][0], P[4][1], vmr[2*n2]); mma8(d + 8 * n2 + 4, P[4][0], P[4][1], vmr[2*n2+1]);
      }
      __syncwarp(); if (lane == 0) mbar_arrive(eV);
      #pragma unroll
      for (int ch = 0; ch < 2; ch++) {
        #pragma unroll
        for (int i = 0; i < 8; i++) { const float* a = d + ch * 32 + i * 4;
          sts32(stg + g * 144 + i * 16 + t * 4, pack2(a[0], a[1])); sts32(stg + (g + 8) * 144 + i * 16 + t * 4, pack2(a[2], a[3])); }
        __syncwarp();
        #pragma unroll
        for (int i = 0; i < 4; i++) { int r = i * 4 + lm; uint4 v = lds128(stg + r * 144 + lr * 16);
          *(uint4*)(g_o + (size_t)(row0 + r) * 4096 + h * 128 + ch * 64 + lr * 8) = v; }
        __syncwarp();
      }
      bar_arrive(6 + (n & 1), 288);
      continue;
    }
    const int nkb = I.type == 2 ? 7 : 8;
    uint32_t prev = 0;
    for (int kb = 0; kb < nkb; kb++) {
      mbar_wait(full + st * 8, ph);
      uint32_t sa = sb + st * 49152;
      asm volatile("wgmma.fence.sync.aligned;" ::: "memory");
      #pragma unroll
      for (int k = 0; k < 4; k++)
        wgmma256(d, mkdesc(sa + wg * 8192 + k * 32, 16, 1024), mkdesc(sa + 16384 + k * 2048, 8192, 1024), (kb | k) != 0);
      asm volatile("wgmma.commit_group.sync.aligned;" ::: "memory");
      if (kb > 0) { asm volatile("wgmma.wait_group.sync.aligned 1;" ::: "memory"); if (lane == 0) mbar_arrive(prev); }
      prev = empty + st * 8;
      if (++st == 4) { st = 0; ph ^= 1; }
    }
    asm volatile("wgmma.wait_group.sync.aligned 0;" ::: "memory");
    if (lane == 0) mbar_arrive(prev);
    TB(1);
    if (I.type <= 1) {
      bf16* dst; int ld;
      if (I.type == 0) { dst = g_qkv + (size_t)row0 * QW + I.nt * 256; ld = QW; } else { dst = g_hid + (size_t)row0 * FF + I.nt * 256; ld = FF; }
      #pragma unroll
      for (int ch = 0; ch < 4; ch++) {
        #pragma unroll
        for (int i = 0; i < 8; i++) { float* a = d + ch * 32 + i * 4;
          if (I.type == 1) { float2 bb = __bfloat1622float2(*(const __nv_bfloat162*)(b1 + I.nt * 256 + ch * 64 + i * 8 + 2 * t));
            a[0] = gelu_t(rbf(rbf(a[0]) + bb.x)); a[1] = gelu_t(rbf(rbf(a[1]) + bb.y)); a[2] = gelu_t(rbf(rbf(a[2]) + bb.x)); a[3] = gelu_t(rbf(rbf(a[3]) + bb.y)); }
          sts32(stg + g * 144 + i * 16 + t * 4, pack2(a[0], a[1])); sts32(stg + (g + 8) * 144 + i * 16 + t * 4, pack2(a[2], a[3])); }
        __syncwarp();
        #pragma unroll
        for (int i = 0; i < 4; i++) { int r = i * 4 + lm; uint4 v = lds128(stg + r * 144 + lr * 16); *(uint4*)(dst + (size_t)r * ld + ch * 64 + lr * 8) = v; }
        __syncwarp();
      }
    } else {
      float* dst = (I.type == 2 ? g_z : g_s) + (size_t)(row0 + g) * DM + I.nt * 256 + 2 * t;
      #pragma unroll
      for (int i = 0; i < 32; i++) {
        asm volatile("red.relaxed.gpu.global.add.v2.f32 [%0], {%1,%2};" ::"l"(dst + i * 8), "f"(d[4*i]), "f"(d[4*i+1]) : "memory");
        asm volatile("red.relaxed.gpu.global.add.v2.f32 [%0], {%1,%2};" ::"l"(dst + 8 * DM + i * 8), "f"(d[4*i+2]), "f"(d[4*i+3]) : "memory");
      }
    }
    bar_arrive(6 + (n & 1), 288);
  }
}

__global__ void __cluster_dims__(2, 1, 1) __launch_bounds__(384, 1)
main_kernel(const __grid_constant__ Maps mp, const bf16* x, const bf16* Wq, const bf16* Wk, const bf16* Wv, const bf16* Wo, const bf16* b1, const bf16* b2, bf16* out) {
  const uint32_t sb = smem_u32(smem_raw);
  if (sb & 1023) __trap();
  if (threadIdx.x == 0) {
    if (blockIdx.x < NREC) { mbar_init(sb + R_BAR, 1); mbar_init(sb + R_BAR + 8, 1); mbar_init(sb + R_BAR + 16, 1); }
    else { for (int i = 0; i < 4; i++) { mbar_init(sb + B_BAR + i * 8, 1); mbar_init(sb + B_BAR + 32 + i * 8, 8); }
      for (int i = 0; i < 2; i++) { mbar_init(sb + B_BAR + 64 + i * 8, 1); mbar_init(sb + B_BAR + 80 + i * 8, 9); } }
    asm volatile("fence.mbarrier_init.release.cluster;" ::: "memory");
  }
  asm volatile("barrier.cluster.arrive.release.aligned; barrier.cluster.wait.acquire.aligned;" ::: "memory");
  if (blockIdx.x < NREC) recurrence(sb, Wq, Wk, Wv, Wo);
  else bulk(sb, mp, x, b1, b2, out);
}

typedef CUresult (*EncFn)(CUtensorMap*, CUtensorMapDataType, cuuint32_t, void*, const cuuint64_t*, const cuuint64_t*, const cuuint32_t*, const cuuint32_t*, CUtensorMapInterleave, CUtensorMapSwizzle, CUtensorMapL2promotion, CUtensorMapFloatOOBfill);
static void mk(EncFn f, CUtensorMap* m, const void* p, uint64_t rows, uint64_t cols, uint32_t boxr) {
  cuuint64_t dims[2] = {cols, rows}, str[1] = {cols * 2}; cuuint32_t box[2] = {64, boxr}, es[2] = {1, 1};
  f(m, CU_TENSOR_MAP_DATA_TYPE_BFLOAT16, 2, (void*)p, dims, str, box, es, CU_TENSOR_MAP_INTERLEAVE_NONE, CU_TENSOR_MAP_SWIZZLE_128B, CU_TENSOR_MAP_L2_PROMOTION_L2_256B, CU_TENSOR_MAP_FLOAT_OOB_FILL_NONE);
}
extern "C" void kernel_launch(void* const* d_in, const int* in_sizes, int n_in, void* d_out, int out_size) {
  const bf16 *x = (const bf16*)d_in[0], *mem0 = (const bf16*)d_in[1], *Wq = (const bf16*)d_in[2], *Wk = (const bf16*)d_in[3], *Wv = (const bf16*)d_in[4], *Wo = (const bf16*)d_in[5];
  const bf16 *w1 = (const bf16*)d_in[8], *b1 = (const bf16*)d_in[9], *w2 = (const bf16*)d_in[10], *b2 = (const bf16*)d_in[11];
  void* fn = nullptr; cudaDriverEntryPointQueryResult qr;
  cudaGetDriverEntryPoint("cuTensorMapEncodeTiled", &fn, cudaEnableDefault, &qr);
  EncFn f = (EncFn)fn;
  void *pxn, *py, *ph, *po, *pq;
  cudaGetSymbolAddress(&pxn, g_xn); cudaGetSymbolAddress(&py, g_y); cudaGetSymbolAddress(&ph, g_hid); cudaGetSymbolAddress(&po, g_o); cudaGetSymbolAddress(&pq, g_qkv);
  Maps mp;
  mk(f, &mp.xn, pxn, SEQ, DM, 128); mk(f, &mp.y, py, SEQ, DM, 128); mk(f, &mp.hid, ph, SEQ, FF, 128); mk(f, &mp.o, po, SEQ, 4096, 128); mk(f, &mp.qkv, pq, SEQ, QW, 128);
  mk(f, &mp.wk, Wk, DM, 4096, 64); mk(f, &mp.wv, Wv, DM, 4096, 64); mk(f, &mp.wq, Wq, DM, 4096, 64);
  mk(f, &mp.w1, w1, DM, FF, 64); mk(f, &mp.w2, w2, FF, DM, 64); mk(f, &mp.wo, Wo, 4096, DM, 64);
  cudaFuncSetAttribute(main_kernel, cudaFuncAttributeMaxDynamicSharedMemorySize, SMEM_BYTES);
  prologue_kernel<<<256, 256, 0, cudaStreamPerThread>>>(x, mem0);
  main_kernel<<<NCTA, 384, SMEM_BYTES, cudaStreamPerThread>>>(mp, x, Wq, Wk, Wv, Wo, b1, b2, (bf16*)d_out);
}
```

```cpp
#include <cuda_runtime.h>
#include <cuda_bf16.h>
#include <cuda.h>
#include <stdint.h>

typedef __nv_bfloat16 bf16;
constexpr int SEQ = 2048, DM = 512, FF = 1792, QW = 12288, NSTEP = 64;
constexpr int NREC = 64, NBULK = 68, NCTA = 132;
constexpr int SPIN_LIMIT = 1 << 22;
#define THR 4
#define PDELAY 500

__device__ bf16 g_xn[SEQ * DM];
__device__ bf16 g_y[SEQ * DM];
__device__ bf16 g_qkv[(size_t)SEQ * QW];
__device__ bf16 g_hid[SEQ * FF];
__device__ bf16 g_o[(size_t)SEQ * 4096];
__device__ float g_z[SEQ * DM];
__device__ float g_s[SEQ * DM];
__device__ float4 g_acc[NSTEP][2][768];
__device__ bf16 g_km[NSTEP * 32 * 8 * 128];
__device__ bf16 g_vmT[NSTEP * 32 * 128 * 8];
struct Flags { int tile[16][48]; int hid[16]; int z[16][2]; int o[16][8]; int s[16][2]; int prog[16][32]; int next; };
__device__ Flags g_fl;

#define TR(i)
#define TB(i)
#define TI(i)
struct Maps { CUtensorMap xn, y, hid, o, qkv, wk, wv, wq, w1, w2, wo; };

extern __shared__ __align__(1024) uint8_t smem_raw[];
__device__ __forceinline__ uint4 ldc(uint32_t off) { return *(const uint4*)(smem_raw + off); }
__device__ __forceinline__ uint32_t smem_u32(const void* p) { return (uint32_t)__cvta_generic_to_shared(p); }
__device__ __forceinline__ int otid() { int t; asm volatile("mov.u32 %0, %%tid.x;" : "=r"(t)); return t; }
__device__ __forceinline__ uint32_t mapa(uint32_t a, uint32_t r) { uint32_t o; asm volatile("mapa.shared::cluster.u32 %0, %1, %2;" : "=r"(o) : "r"(a), "r"(r)); return o; }
__device__ __forceinline__ void st_async_v4(uint32_t addr, float a, float b, float c, float d, uint32_t mbar) {
  asm volatile("st.async.weak.shared::cluster.mbarrier::complete_tx::bytes.v4.b32 [%0], {%1,%2,%3,%4}, [%5];" ::"r"(addr), "r"(__float_as_uint(a)), "r"(__float_as_uint(b)), "r"(__float_as_uint(c)), "r"(__float_as_uint(d)), "r"(mbar) : "memory"); }
__device__ __forceinline__ void mbar_init(uint32_t m, int c) { asm volatile("mbarrier.init.shared::cta.b64 [%0], %1;" ::"r"(m), "r"(c) : "memory"); }
__device__ __forceinline__ void mbar_expect(uint32_t m, int bytes) { asm volatile("mbarrier.arrive.expect_tx.shared::cta.b64 _, [%0], %1;" ::"r"(m), "r"(bytes) : "memory"); }
__device__ __forceinline__ void mbar_arrive(uint32_t m) { asm volatile("mbarrier.arrive.shared::cta.b64 _, [%0];" ::"r"(m) : "memory"); }
__device__ __forceinline__ void mbar_wait(uint32_t m, uint32_t parity) {
  uint32_t ok; int it = 0;
  do { asm volatile("{.reg .pred p; mbarrier.try_wait.parity.shared::cta.b64 p, [%1], %2; selp.u32 %0,1,0,p;}" : "=r"(ok) : "r"(m), "r"(parity) : "memory"); } while (!ok && ++it < SPIN_LIMIT); }
__device__ __forceinline__ void mbar_spin(uint32_t m, uint32_t parity) {
  uint32_t ok; int it = 0;
  do { asm volatile("{.reg .pred p; mbarrier.test_wait.parity.shared::cta.b64 p, [%1], %2; selp.u32 %0,1,0,p;}" : "=r"(ok) : "r"(m), "r"(parity) : "memory"); } while (!ok && ++it < SPIN_LIMIT); }
__device__ __forceinline__ void bar_sync(int id, int n) { asm volatile("bar.sync %0, %1;" ::"r"(id), "r"(n) : "memory"); }
__device__ __forceinline__ void bar_arrive(int id, int n) { asm volatile("bar.arrive %0, %1;" ::"r"(id), "r"(n) : "memory"); }
__device__ __forceinline__ int ld_acq(const int* p) { int v; asm volatile("ld.acquire.gpu.global.s32 %0, [%1];" : "=r"(v) : "l"(p) : "memory"); return v; }
__device__ __forceinline__ void wait_flag(const int* p, int target) { int it = 0; while (ld_acq(p) < target && ++it < SPIN_LIMIT) { __nanosleep(40); } }
__device__ __forceinline__ void fence_async() { asm volatile("fence.proxy.async.global;" ::: "memory"); }
__device__ __forceinline__ uint4 lds128(uint32_t a) { uint4 v; asm volatile("ld.shared.v4.u32 {%0,%1,%2,%3}, [%4];" : "=r"(v.x), "=r"(v.y), "=r"(v.z), "=r"(v.w) : "r"(a) : "memory"); return v; }
__device__ __forceinline__ void sts128(uint32_t a, uint4 v) { asm volatile("st.shared.v4.u32 [%0], {%1,%2,%3,%4};" ::"r"(a), "r"(v.x), "r"(v.y), "r"(v.z), "r"(v.w) : "memory"); }
__device__ __forceinline__ void sts32(uint32_t a, uint32_t v) { asm volatile("st.shared.u32 [%0], %1;" ::"r"(a), "r"(v) : "memory"); }
__device__ __forceinline__ void sts16(uint32_t a, float f) { unsigned short h = __bfloat16_as_ushort(__float2bfloat16(f)); asm volatile("st.shared.u16 [%0], %1;" ::"r"(a), "h"(h) : "memory"); }
__device__ __forceinline__ void ldsm4(uint32_t* r, uint32_t a) { asm volatile("ldmatrix.sync.aligned.m8n8.x4.shared.b16 {%0,%1,%2,%3}, [%4];" : "=r"(r[0]), "=r"(r[1]), "=r"(r[2]), "=r"(r[3]) : "r"(a) : "memory"); }
__device__ __forceinline__ void ldsm4t(uint32_t* r, uint32_t a) { asm volatile("ldmatrix.sync.aligned.m8n8.x4.trans.shared.b16 {%0,%1,%2,%3}, [%4];" : "=r"(r[0]), "=r"(r[1]), "=r"(r[2]), "=r"(r[3]) : "r"(a) : "memory"); }
__device__ __forceinline__ void mma16(float* c, uint32_t a0, uint32_t a1, uint32_t a2, uint32_t a3, uint32_t b0, uint32_t b1) {
  asm("mma.sync.aligned.m16n8k16.row.col.f32.bf16.bf16.f32 {%0,%1,%2,%3}, {%4,%5,%6,%7}, {%8,%9}, {%0,%1,%2,%3};" : "+f"(c[0]), "+f"(c[1]), "+f"(c[2]), "+f"(c[3]) : "r"(a0), "r"(a1), "r"(a2), "r"(a3), "r"(b0), "r"(b1)); }
__device__ __forceinline__ void mma8(float* c, uint32_t a0, uint32_t a1, uint32_t b0) {
  asm("mma.sync.aligned.m16n8k8.row.col.f32.bf16.bf16.f32 {%0,%1,%2,%3}, {%4,%5}, {%6}, {%0,%1,%2,%3};" : "+f"(c[0]), "+f"(c[1]), "+f"(c[2]), "+f"(c[3]) : "r"(a0), "r"(a1), "r"(b0)); }
__device__ __forceinline__ uint32_t pack2(float a, float b) { __nv_bfloat162 h = __floats2bfloat162_rn(a, b); return *(uint32_t*)&h; }
__device__ __forceinline__ float rbf(float x) { uint32_t r; asm("cvt.rn.bf16x2.f32 %0, %1, %2;" : "=r"(r) : "f"(x), "f"(0.f)); return __uint_as_float(r); }
__device__ __forceinline__ void cp16(uint32_t d, const void* s) { asm volatile("cp.async.cg.shared.global [%0], [%1], 16;" ::"r"(d), "l"(s) : "memory"); }
__device__ __forceinline__ void tma2d(uint32_t dst, const CUtensorMap* m, int c0, int c1, uint32_t mbar) {
  asm volatile("cp.async.bulk.tensor.2d.shared::cluster.global.mbarrier::complete_tx::bytes [%0], [%1, {%2,%3}], [%4];" ::"r"(dst), "l"(m), "r"(c0), "r"(c1), "r"(mbar) : "memory"); }
__device__ __forceinline__ uint64_t mkdesc(uint32_t addr, uint32_t lbo, uint32_t sbo) {
  return (uint64_t)((addr & 0x3FFFF) >> 4) | ((uint64_t)(lbo >> 4) << 16) | ((uint64_t)(sbo >> 4) << 32) | (1ull << 62); }

#define R8(i) "+f"(d[i]), "+f"(d[i+1]), "+f"(d[i+2]), "+f"(d[i+3]), "+f"(d[i+4]), "+f"(d[i+5]), "+f"(d[i+6]), "+f"(d[i+7])
__device__ __forceinline__ void wgmma256(float* d, uint64_t da, uint64_t db, int acc) {
  asm volatile("{.reg .pred p; setp.ne.b32 p, %130, 0;\n"
    "wgmma.mma_async.sync.aligned.m64n256k16.f32.bf16.bf16 {"
    "%0,%1,%2,%3,%4,%5,%6,%7,%8,%9,%10,%11,%12,%13,%14,%15,%16,%17,%18,%19,%20,%21,%22,%23,%24,%25,%26,%27,%28,%29,%30,%31,"
    "%32,%33,%34,%35,%36,%37,%38,%39,%40,%41,%42,%43,%44,%45,%46,%47,%48,%49,%50,%51,%52,%53,%54,%55,%56,%57,%58,%59,%60,%61,%62,%63,"
    "%64,%65,%66,%67,%68,%69,%70,%71,%72,%73,%74,%75,%76,%77,%78,%79,%80,%81,%82,%83,%84,%85,%86,%87,%88,%89,%90,%91,%92,%93,%94,%95,"
    "%96,%97,%98,%99,%100,%101,%102,%103,%104,%105,%106,%107,%108,%109,%110,%111,%112,%113,%114,%115,%116,%117,%118,%119,%120,%121,%122,%123,%124,%125,%126,%127"
    "}, %128, %129, p, 1, 1, 0, 1;}"
    : R8(0), R8(8), R8(16), R8(24), R8(32), R8(40), R8(48), R8(56), R8(64), R8(72), R8(80), R8(88), R8(96), R8(104), R8(112), R8(120)
    : "l"(da), "l"(db), "r"(acc)); }

__global__ void __launch_bounds__(256) prologue_kernel(const bf16* __restrict__ x, const bf16* __restrict__ mem0, const bf16* Wq, const bf16* Wk, const bf16* Wv, const bf16* Wo) {
  int tid = threadIdx.x, lane = tid & 31, warp = tid >> 5;
  { const int gt = blockIdx.x * 256 + tid; const size_t o = (size_t)(gt & 32767) * 64;
    asm volatile("prefetch.global.L2 [%0];" ::"l"((gt < 32768 ? Wk : Wv) + o));
    asm volatile("prefetch.global.L2 [%0];" ::"l"((gt < 32768 ? Wq : Wo) + o)); }
  int row = blockIdx.x * 8 + warp;
  {
    const uint4* src = (const uint4*)(x + (size_t)row * DM);
    uint4 u[2] = { src[lane], src[lane + 32] };
    float v[16];
    #pragma unroll
    for (int i = 0; i < 2; i++) { const __nv_bfloat162* h = (const __nv_bfloat162*)&u[i];
      #pragma unroll
      for (int k = 0; k < 4; k++) { float2 f = __bfloat1622float2(h[k]); v[i * 8 + 2 * k] = f.x; v[i * 8 + 2 * k + 1] = f.y; } }
    #pragma unroll
    for (int pass = 0; pass < 2; pass++) {
      float s = 0;
      #pragma unroll
      for (int i = 0; i < 16; i++) s += v[i];
      #pragma unroll
      for (int o = 16; o; o >>= 1) s += __shfl_xor_sync(~0u, s, o);
      float mf = s * (1.f / DM);
      float q = 0;
      #pragma unroll
      for (int i = 0; i < 16; i++) { float dd = v[i] - mf; q += dd * dd; }
      #pragma unroll
      for (int o = 16; o; o >>= 1) q += __shfl_xor_sync(~0u, q, o);
      float m = rbf(mf), var = rbf(q * (1.f / DM));
      float den = rbf(sqrtf(rbf(var + 1e-5f)));
      #pragma unroll
      for (int i = 0; i < 16; i++) v[i] = rbf(rbf(v[i] - m) / den);
      uint4 o4[2];
      #pragma unroll
      for (int i = 0; i < 2; i++) { o4[i].x = pack2(v[i*8], v[i*8+1]); o4[i].y = pack2(v[i*8+2], v[i*8+3]); o4[i].z = pack2(v[i*8+4], v[i*8+5]); o4[i].w = pack2(v[i*8+6], v[i*8+7]); }
      uint4* dst = (uint4*)((pass ? g_y : g_xn) + (size_t)row * DM);
      dst[lane] = o4[0]; dst[lane + 32] = o4[1];
    }
  }
  int gt = blockIdx.x * 256 + tid;
  float4 z4 = make_float4(0, 0, 0, 0);
  #pragma unroll
  for (int i = 0; i < 4; i++) { ((float4*)g_z)[gt + i * 65536] = z4; ((float4*)g_s)[gt + i * 65536] = z4; }
  for (int i = gt; i < NSTEP * 1536; i += 65536) {
    float4 val = z4;
    if (i < 1536) {
      int j = i / 768, c = i % 768, ci = c >> 8, w = (c & 255) >> 5, l = c & 31, g = l >> 2, t = l & 3;
      float e3[3];
      #pragma unroll
      for (int k = 0; k < 3; k++) { int e = ci * 3 + k; int mt = e >> 2, cc = e & 3;
        e3[k] = e < 8 ? __bfloat162float(mem0[(2 * t + (cc & 1)) * DM + 256 * j + 32 * w + 16 * mt + g + 8 * (cc >> 1)]) : 0.f; }
      val = make_float4(e3[0], e3[1], e3[2], 32.f);
    }
    (&g_acc[0][0][0])[i] = val;
  }
  if (gt < (int)(sizeof(Flags) / 4)) ((int*)&g_fl)[gt] = 0;
}

constexpr int R_WR = 0, R_WO = 65536, R_KT = 131072, KT_SZ = 40 * 256, R_VT = R_KT + 2 * KT_SZ, VT_SZ = 40 * 272,
              R_MEM = R_VT + 2 * VT_SZ, R_Q = R_MEM + 32 * 160, R_O = R_Q + 8 * 256, R_S = R_O + 8 * 256,
              R_SM = R_S + 8 * 40 * 4, R_RQK = R_SM + 1024, R_RV = R_RQK + 8192, R_WQ = R_RV + 4096, R_BAR = 232448 - 64, R_END = R_BAR + 64;
static_assert(R_WQ + 32768 <= R_BAR, "smem");
#define PI 0
#define LD1(v, p) asm volatile("ld.relaxed.gpu.global.v4.u32 {%0,%1,%2,%3}, [%4];" : "=r"(v.x), "=r"(v.y), "=r"(v.z), "=r"(v.w) : "l"(p) : "memory")
#define LD3(a, b, c) do { LD1(a, src + ((EXP & 2) ? 256 * (h % 3) : 0)); if (EXP & 2) { b = a; c = a; } else { LD1(b, src + 256); LD1(c, src + 512); } } while (0)
#define OK3(a, b, c) __all_sync(~0u, (a.w == 0x42000000u) && (b.w == 0x42000000u) && (c.w == 0x42000000u))
#define W7D 1100
#define NW0 8
#define VD 0
#define KD 150
#define VCH 2
#define VP 3
__device__ __forceinline__ void wgmma8(float* d, uint64_t da, uint64_t db, int acc) {
  asm volatile("{.reg .pred p; setp.ne.b32 p, %6, 0;\n wgmma.mma_async.sync.aligned.m64n8k16.f32.bf16.bf16 {%0,%1,%2,%3}, %4, %5, p, 1, 1, 0, 0;}"
    : "+f"(d[0]), "+f"(d[1]), "+f"(d[2]), "+f"(d[3]) : "l"(da), "l"(db), "r"(acc)); }
__device__ __forceinline__ void stsm4(uint32_t a, uint32_t r0, uint32_t r1, uint32_t r2, uint32_t r3) { asm volatile("stmatrix.sync.aligned.m8n8.x4.shared.b16 [%0], {%1,%2,%3,%4};" ::"r"(a), "r"(r0), "r"(r1), "r"(r2), "r"(r3) : "memory"); }
__device__ __forceinline__ uint32_t swz(uint32_t r) { return ((r & 1) << 2) | ((r >> 1) & 3); }
__device__ __forceinline__ void stsm4t(uint32_t a, uint32_t r0, uint32_t r1, uint32_t r2, uint32_t r3) { asm volatile("stmatrix.sync.aligned.m8n8.x4.trans.shared.b16 [%0], {%1,%2,%3,%4};" ::"r"(a), "r"(r0), "r"(r1), "r"(r2), "r"(r3) : "memory"); }
__device__ __forceinline__ void stsm2(uint32_t a, uint32_t r0, uint32_t r1) { asm volatile("stmatrix.sync.aligned.m8n8.x2.shared.b16 [%0], {%1,%2};" ::"r"(a), "r"(r0), "r"(r1) : "memory"); }
__device__ __forceinline__ float ex2(float x) { float r; asm("ex2.approx.ftz.f32 %0, %1;" : "=f"(r) : "f"(x)); return r; }
#define REDV4(p, a, b, c) asm volatile("red.relaxed.gpu.global.add.v4.f32 [%0], {%1,%2,%3,%4};" ::"l"(p), "f"(a), "f"(b), "f"(c), "f"(RCNT) : "memory")
#define EXP 0
#define RCNT ((EXP & 1) ? 4.0f : 1.0f)
constexpr int SMEM_BYTES = 232448;
static_assert(R_END <= SMEM_BYTES, "smem");

__device__ __forceinline__ void recurrence(uint32_t sb, const bf16* __restrict__ Wq, const bf16* __restrict__ Wk, const bf16* __restrict__ Wv, const bf16* __restrict__ Wo) {
  const int tid = threadIdx.x, warp = tid >> 5, lane = tid & 31, g = lane >> 2, t = lane & 3;
  const int h = blockIdx.x >> 1, j = blockIdx.x & 1;
  const uint32_t peer = j ^ 1;
  const uint32_t mQ = sb + R_BAR, mV = sb + R_BAR + 8, mK = sb + R_BAR + 16;
  uint32_t A[2][16][4];
  TI(1);
  const int lm = lane >> 3, lr = lane & 7;
  for (int i = tid; i < 256 * 16; i += 384) { const int r = i >> 4, c = i & 15; const size_t o = ((size_t)(256 * j + r)) * 4096 + h * 128 + c * 8;
    const uint32_t d = sb + r * 256 + ((c ^ ((r & 1) | ((r >> 2) & 6))) << 4);
    cp16(d + 131072, Wq + o); cp16(d + 65536, Wk + o); cp16(d, Wv + o); }
  auto ldwo = [&](int half, uint32_t st) {
    for (int i = tid; i < 64 * 32; i += 384) { const int r = i >> 5, c = i & 31;
      cp16(st + r * 512 + ((c ^ ((r & 1) | ((r >> 2) & 6))) << 4), Wo + ((size_t)(h * 128 + 64 * half + r)) * DM + 256 * j + c * 8); } };
  auto cvwo = [&](int half, uint32_t st) {
    if (warp < 8) {
      #pragma unroll
      for (int i = 0; i < 8; i++) { const int wv = warp >> 1, mt = warp & 1, kq = i & 3, hi = i >> 2;
        const int k = 32 * (kq >> 1) + 8 * (lr >> 1) + (lr & 1) + 4 * (kq & 1) + 2 * (lm >> 1); uint32_t r[4];
        ldsm4t(r, st + k * 512 + (((8 * wv + 4 * mt + 2 * hi + (lm & 1)) ^ lr) << 4));
        sts128(sb + R_WO + ((wv * 32 + mt * 16 + hi * 8 + half * 4 + kq) * 32 + lane) * 16, make_uint4(r[0], r[1], r[2], r[3])); }
    } };
  ldwo(0, sb + 196608);
  asm volatile("cp.async.wait_all;" ::: "memory"); __syncthreads();
  TI(2);
  { const uint32_t st = sb + (2 - (warp >> 2)) * 65536;
    #pragma unroll
    for (int mt = 0; mt < 2; mt++)
      #pragma unroll
      for (int ks = 0; ks < 16; ks++) {
        const int k = 32 * (ks >> 1) + 8 * (lr >> 1) + (lr & 1) + 4 * (ks & 1) + 2 * (lm >> 1);
        ldsm4t(A[mt][ks], st + k * 256 + (((4 * (warp & 3) + 2 * mt + (lm & 1)) ^ lr) << 4));
      } }
  __syncthreads();
  TI(3);
  ldwo(1, sb + 131072);
  cvwo(0, sb + 196608);
  if (warp >= 8) {
    #pragma unroll
    for (int i = 0; i < 32; i++) sts128(sb + R_WR + (((warp - 8) * 32 + i) * 32 + lane) * 16, make_uint4(A[i & 1][i >> 1][0], A[i & 1][i >> 1][1], A[i & 1][i >> 1][2], A[i & 1][i >> 1][3]));
  }
  asm volatile("cp.async.wait_all;" ::: "memory"); __syncthreads();
  TI(4);
  cvwo(1, sb + 131072);
  if (warp < 4) {
    #pragma unroll
    for (int i = 0; i < 16; i++) sts128(sb + R_WQ + ((warp * 16 + i) * 32 + lane) * 16, make_uint4(A[1][i][0], A[1][i][1], A[1][i][2], A[1][i][3]));
  }
  __syncthreads();
  if (warp >= 8) {
    const uint32_t zero = blockIdx.y;
    #pragma unroll 1
    for (int s = 0; s < NSTEP; s++) {
      const int tid = otid(), lane = tid & 31, wv = (tid >> 5) - 8, g = lane >> 2, t = lane & 3;
      if (tid == 256) mbar_expect(mV, 4096);
      const uint32_t fo = (t ^ swz(g)) << 4;
      TR(1);
      bar_sync(4, 384);
      if (VD) { long long t0 = clock64(); while (clock64() - t0 < VD); }
      TR(2);
      float c[4][4];
      #pragma unroll
      for (int i = 0; i < 4; i++) { c[i][0] = c[i][1] = c[i][2] = c[i][3] = 0.f; }
      #pragma unroll
      for (int p = 0; p < 8; p++) {
        uint4 b = ldc(R_MEM + g * 16 + t * 160 + p * 640);
        mma16(c[0], A[0][2*p][0], A[0][2*p][1], A[0][2*p][2], A[0][2*p][3], b.x, b.y);
        mma16(c[1], A[1][2*p][0], A[1][2*p][1], A[1][2*p][2], A[1][2*p][3], b.x, b.y);
        mma16(c[2], A[0][2*p+1][0], A[0][2*p+1][1], A[0][2*p+1][2], A[0][2*p+1][3], b.z, b.w);
        mma16(c[3], A[1][2*p+1][0], A[1][2*p+1][1], A[1][2*p+1][2], A[1][2*p+1][3], b.z, b.w);
      }
      #pragma unroll
      for (int i = 0; i < 4; i++) { c[0][i] += c[2][i]; c[1][i] += c[3][i]; }
      const uint32_t rx = sb + R_RV + (wv * 64 + lane) * 16;
      { uint32_t ra = mapa(rx, peer), rm = mapa(mV, peer);
        st_async_v4(ra, c[0][0], c[0][1], c[0][2], c[0][3], rm);
        st_async_v4(ra + 512, c[1][0], c[1][1], c[1][2], c[1][3], rm); }
      TR(4);
      const bool more = s < NSTEP - 1;
      uint32_t wb = sb + (wv * 1024 + lane) * 16;
      #pragma unroll
      for (int i = 0; i < NW0; i++) { uint4 v = lds128(wb + R_WO + i * 512); A[i >> 4][i & 15][0] = v.x; A[i >> 4][i & 15][1] = v.y; A[i >> 4][i & 15][2] = v.z; A[i >> 4][i & 15][3] = v.w; }
      TR(3);
      mbar_wait(mV, s & 1);
      TR(5);
      { uint4 r0 = lds128(rx), r1 = lds128(rx + 512);
        stsm4t(sb + R_VT + (s & 1) * VT_SZ + (32 + (lane & 7)) * 272 + (4 * wv + (lane >> 3)) * 16,
          pack2(c[0][0] + __uint_as_float(r0.x), c[0][1] + __uint_as_float(r0.y)), pack2(c[0][2] + __uint_as_float(r0.z), c[0][3] + __uint_as_float(r0.w)),
          pack2(c[1][0] + __uint_as_float(r1.x), c[1][1] + __uint_as_float(r1.y)), pack2(c[1][2] + __uint_as_float(r1.z), c[1][3] + __uint_as_float(r1.w))); }
      if (more) {
      bar_arrive(3, 256);
      TR(8);
      #pragma unroll
      for (int i = NW0; i < 32; i++) { uint4 v = lds128(wb + R_WO + i * 512); A[i >> 4][i & 15][0] = v.x; A[i >> 4][i & 15][1] = v.y; A[i >> 4][i & 15][2] = v.z; A[i >> 4][i & 15][3] = v.w;
        if ((i % THR) == THR - 1) wb += v.x & zero; }
      TR(10);
      bar_sync(7, 256);
      TR(9);
      #pragma unroll
      for (int i = 0; i < 4; i++) { c[i][0] = c[i][1] = c[i][2] = c[i][3] = 0.f; }
      #pragma unroll
      for (int p = 0; p < 4; p++) {
        uint4 b = ldc(R_O + g * 256 + (p >> 1) * 128 + (fo ^ ((p & 1) << 6)));
        #pragma unroll
        for (int mt = 0; mt < 4; mt++) { const uint32_t* a = A[mt >> 1][(mt & 1) * 8 + 2 * p]; mma16(c[mt], a[0], a[1], a[2], a[3], b.x, b.y); }
        #pragma unroll
        for (int mt = 0; mt < 4; mt++) { const uint32_t* a = A[mt >> 1][(mt & 1) * 8 + 2 * p + 1]; mma16(c[mt], a[0], a[1], a[2], a[3], b.z, b.w); }
      }
      TR(6);
      float4* dst = &g_acc[s + 1][j][wv * 64 + lane];
      if (!(EXP & 1) || (h & 3) == wv) {
      REDV4(dst, c[0][0], c[0][1], c[0][2]); REDV4(dst + 256, c[0][3], c[1][0], c[1][1]); REDV4(dst + 512, c[1][2], c[1][3], 0.f);
      REDV4(dst + 32, c[2][0], c[2][1], c[2][2]); REDV4(dst + 288, c[2][3], c[3][0], c[3][1]); REDV4(dst + 544, c[3][2], c[3][3], 0.f); }
      bar_arrive(8, 352);
      TR(7);
      } else bar_sync(6, 256);
      { const int vt = tid - 256;
        if (j == 0) { const int r = vt >> 4, cc = vt & 15; uint4 v = lds128(sb + R_KT + (s & 1) * KT_SZ + (32 + r) * 256 + ((cc ^ swz(r)) << 4));
          __stcg((uint4*)(g_km + ((size_t)(s * 32 + h)) * 1024) + vt, v); }
        else { uint32_t vb = sb + R_VT + (s & 1) * VT_SZ + 32 * 272 + vt * 2; uint32_t e[8];
          #pragma unroll
          for (int k = 0; k < 8; k++) { unsigned short x; asm volatile("ld.shared.u16 %0, [%1];" : "=h"(x) : "r"(vb + k * 272) : "memory"); e[k] = x; }
          __stcg((uint4*)(g_vmT + ((size_t)(s * 32 + h)) * 1024) + vt, make_uint4(e[0] | (e[1] << 16), e[2] | (e[3] << 16), e[4] | (e[5] << 16), e[6] | (e[7] << 16))); }
        if (!more) { __syncwarp(); if (lane == 0) { __threadfence(); atomicAdd(&g_fl.prog[15][h], 1); } } }
      #pragma unroll
      for (int i = 0; i < 32; i++) { uint4 v = lds128(wb + R_WR + i * 512); A[i & 1][i >> 1][0] = v.x; A[i & 1][i >> 1][1] = v.y; A[i & 1][i >> 1][2] = v.z; A[i & 1][i >> 1][3] = v.w; }
    }
    return;
  }
  const float scale = 0.08838834764831845f, l2e = 1.4426950408889634f;
  auto prefetch = [&](int s) {
    const int vt = otid() - 160;
    if ((s & 3) == 0) { wait_flag(&g_fl.tile[s >> 2][h >> 1], 1); wait_flag(&g_fl.tile[s >> 2][16 + (h >> 1)], 1); }
    const int r = vt >> 4, c = vt & 15;
    const bf16* src = g_qkv + (size_t)(32 * s + r) * QW + h * 128 + c * 8;
    uint32_t kb = sb + R_KT + (s & 1) * KT_SZ + r * 256, vb = sb + R_VT + (s & 1) * VT_SZ + r * 272 + c * 16;
    #pragma unroll
    for (int i = 0; i < 8; i++) { cp16(kb + i * 1024 + ((c ^ swz(r + 4 * i)) << 4), src + (size_t)i * 4 * QW); cp16(vb + i * 1088, src + (size_t)i * 4 * QW + 4096); }
  };
  if (warp >= 4) {
  if (warp == 5 || warp == 6) prefetch(0);
  #pragma unroll 1
  for (int s = 0; s < NSTEP; s++) {
    TR(0); TR(1);
    const int tid = otid(), lane = tid & 31, warp = tid >> 5, g = lane >> 2, t = lane & 3;
    const uint32_t fo = (t ^ swz(g)) << 4;
    {
      if (tid == 0) mbar_expect(mQ, 4096);
      if (tid == 128) mbar_expect(mK, 4096);
      const float4* src = &g_acc[s][j][tid];
      uint4 v0, v1, v2; int it = 0;
      do { LD3(v0, v1, v2); } while (!OK3(v0, v1, v2) && ++it < SPIN_LIMIT);
      __syncwarp();
      stsm4t(sb + R_MEM + (lane & 7) * 16 + (4 * warp + (lane >> 3)) * 160,
        pack2(__uint_as_float(v0.x), __uint_as_float(v0.y)), pack2(__uint_as_float(v0.z), __uint_as_float(v1.x)),
        pack2(__uint_as_float(v1.y), __uint_as_float(v1.z)), pack2(__uint_as_float(v2.x), __uint_as_float(v2.y)));
    }
    TR(2);
    asm volatile("cp.async.wait_all;" ::: "memory");
    bar_sync(1, 256);
    { long long t0 = clock64(); while (clock64() - t0 < KD); }
    if (VP < 0) bar_arrive(4, 384);
    TR(3);
    float c[4][4];
    #pragma unroll
    for (int i = 0; i < 4; i++) { c[i][0] = c[i][1] = c[i][2] = c[i][3] = 0.f; }
    #pragma unroll
    for (int p = 0; p < 8; p++) {
      uint4 b = ldc(R_MEM + g * 16 + t * 160 + p * 640);
      mma16(c[0], A[0][2*p][0], A[0][2*p][1], A[0][2*p][2], A[0][2*p][3], b.x, b.y);
      mma16(c[1], A[1][2*p][0], A[1][2*p][1], A[1][2*p][2], A[1][2*p][3], b.x, b.y);
      mma16(c[2], A[0][2*p+1][0], A[0][2*p+1][1], A[0][2*p+1][2], A[0][2*p+1][3], b.z, b.w);
      mma16(c[3], A[1][2*p+1][0], A[1][2*p+1][1], A[1][2*p+1][2], A[1][2*p+1][3], b.z, b.w);
      if (p == VP) asm volatile("bar.arrive 4, 384;");
    }
    #pragma unroll
    for (int i = 0; i < 4; i++) { c[0][i] += c[2][i]; c[1][i] += c[3][i]; }
    const uint32_t rx = sb + R_RQK + (warp * 64 + lane) * 16;
    { uint32_t ra = mapa(rx, peer), rm = mapa(mK, peer);
      st_async_v4(ra, c[0][0], c[0][1], c[0][2], c[0][3], rm);
      st_async_v4(ra + 512, c[1][0], c[1][1], c[1][2], c[1][3], rm); }
    if (VP > 7) bar_arrive(4, 384);
    TR(4);
    const uint32_t so = (lane & 7) * 256 + (((4 * (warp & 3) + (lane >> 3)) ^ swz(lane & 7)) << 4);
    mbar_wait(mK, s & 1);
    TR(5);
    uint32_t m0, m1, m2, m3;
    { uint4 r0 = lds128(rx), r1 = lds128(rx + 512);
      m0 = pack2(c[0][0] + __uint_as_float(r0.x), c[0][1] + __uint_as_float(r0.y)); m1 = pack2(c[0][2] + __uint_as_float(r0.z), c[0][3] + __uint_as_float(r0.w));
      m2 = pack2(c[1][0] + __uint_as_float(r1.x), c[1][1] + __uint_as_float(r1.y)); m3 = pack2(c[1][2] + __uint_as_float(r1.z), c[1][3] + __uint_as_float(r1.w)); }
    stsm4t(sb + R_KT + (s & 1) * KT_SZ + 32 * 256 + so, m0, m1, m2, m3);
    if (s == NSTEP - 1) { bar_arrive(6, 256); break; }
    asm("movmatrix.sync.aligned.m8n8.trans.b16 %0, %0;" : "+r"(m0)); asm("movmatrix.sync.aligned.m8n8.trans.b16 %0, %0;" : "+r"(m1));
    asm("movmatrix.sync.aligned.m8n8.trans.b16 %0, %0;" : "+r"(m2)); asm("movmatrix.sync.aligned.m8n8.trans.b16 %0, %0;" : "+r"(m3));
    TR(8);
    bar_sync(9, 256);
    TR(9);
    { uint32_t qa[4]; ldsm4(qa, sb + R_Q + so);
      #pragma unroll
      for (int i = 0; i < 2; i++) { c[i][0] = c[i][1] = c[i][2] = c[i][3] = 0.f; }
      mma16(c[0], qa[0], 0, qa[1], 0, m0, m1); mma16(c[1], qa[2], 0, qa[3], 0, m2, m3);
      asm volatile("st.shared.v2.f32 [%0], {%1,%2};" ::"r"(sb + R_SM + (warp - 4) * 256 + lane * 8), "f"(c[0][0] + c[1][0]), "f"(c[0][1] + c[1][1]) : "memory"); }
    bar_arrive(2, 256);
    TR(10);
    if ((warp == 5 || warp == 6) && s < NSTEP - 2) prefetch(s + 1);
    TR(7);
    if (warp == 7) { if ((s & 3) == 1 && s > 1 && lane == 0) asm volatile("red.release.gpu.global.add.s32 [%0], 4;" ::"l"(&g_fl.prog[(s - 2) >> 2][h]) : "memory"); __syncwarp();
      long long t0 = clock64(); while (clock64() - t0 < W7D); }
    else bar_sync(8, 352);
    { long long t0 = clock64(); while (clock64() - t0 < PDELAY); }
  }
  return;
  }
  #pragma unroll 1
  for (int s = 0; s < NSTEP; s++) {
    TR(0); TR(1);
    const int tid = otid(), lane = tid & 31, warp = tid >> 5, g = lane >> 2, t = lane & 3;
    const uint32_t fo = (t ^ swz(g)) << 4;
    {
      if (tid == 0) mbar_expect(mQ, 4096);
      if (tid == 128) mbar_expect(mK, 4096);
      const float4* src = &g_acc[s][j][tid];
      uint4 v0, v1, v2; int it = 0;
      do { LD3(v0, v1, v2); } while (!OK3(v0, v1, v2) && ++it < SPIN_LIMIT);
      __syncwarp();
      stsm4t(sb + R_MEM + (lane & 7) * 16 + (4 * warp + (lane >> 3)) * 160,
        pack2(__uint_as_float(v0.x), __uint_as_float(v0.y)), pack2(__uint_as_float(v0.z), __uint_as_float(v1.x)),
        pack2(__uint_as_float(v1.y), __uint_as_float(v1.z)), pack2(__uint_as_float(v2.x), __uint_as_float(v2.y)));
    }
    TR(2);

    bar_sync(1, 256);
    bar_arrive(4, 384);
    TR(3);
    float c[4][4];
    #pragma unroll
    for (int i = 0; i < 4; i++) { c[i][0] = c[i][1] = c[i][2] = c[i][3] = 0.f; }
    #pragma unroll
    for (int p = 0; p < 8; p++) {
      uint4 b = ldc(R_MEM + g * 16 + t * 160 + p * 640);
      mma16(c[0], A[0][2*p][0], A[0][2*p][1], A[0][2*p][2], A[0][2*p][3], b.x, b.y);
      mma16(c[1], A[1][2*p][0], A[1][2*p][1], A[1][2*p][2], A[1][2*p][3], b.x, b.y);
      mma16(c[2], A[0][2*p+1][0], A[0][2*p+1][1], A[0][2*p+1][2], A[0][2*p+1][3], b.z, b.w);
      mma16(c[3], A[1][2*p+1][0], A[1][2*p+1][1], A[1][2*p+1][2], A[1][2*p+1][3], b.z, b.w);
    }
    #pragma unroll
    for (int i = 0; i < 4; i++) { c[0][i] += c[2][i]; c[1][i] += c[3][i]; }
    const uint32_t rx = sb + R_RQK + (warp * 64 + lane) * 16;
    { uint32_t ra = mapa(rx, peer), rm = mapa(mQ, peer);
      st_async_v4(ra, c[0][0], c[0][1], c[0][2], c[0][3], rm);
      st_async_v4(ra + 512, c[1][0], c[1][1], c[1][2], c[1][3], rm); }
    TR(4);
    const uint32_t so = (lane & 7) * 256 + (((4 * (warp & 3) + (lane >> 3)) ^ swz(lane & 7)) << 4);
    if (s == NSTEP - 1) { mbar_wait(mQ, s & 1); break; }
    uint4 kf[4]; uint32_t vf[4][4];
    const uint32_t vb = sb + R_VT + (s & 1) * VT_SZ + (lane & 15) * 272 + (32 * warp + 8 * (lane >> 4)) * 2;
    #pragma unroll
    for (int p = 0; p < 4; p++) kf[p] = lds128(sb + R_KT + (s & 1) * KT_SZ + warp * 2048 + g * 256 + (p >> 1) * 128 + (fo ^ ((p & 1) << 6)));
    #pragma unroll
    for (int i = 0; i < 4; i++) ldsm4t(vf[i], vb + (i >> 1) * 16 * 272 + (i & 1) * 32);
    mbar_wait(mQ, s & 1);
    TR(5);
    uint32_t m0, m1, m2, m3;
    { uint4 r0 = lds128(rx), r1 = lds128(rx + 512);
      m0 = pack2(c[0][0] + __uint_as_float(r0.x), c[0][1] + __uint_as_float(r0.y)); m1 = pack2(c[0][2] + __uint_as_float(r0.z), c[0][3] + __uint_as_float(r0.w));
      m2 = pack2(c[1][0] + __uint_as_float(r1.x), c[1][1] + __uint_as_float(r1.y)); m3 = pack2(c[1][2] + __uint_as_float(r1.z), c[1][3] + __uint_as_float(r1.w)); }
    stsm4t(sb + R_Q + so, m0, m1, m2, m3);
    TR(8);
    bar_arrive(9, 256); bar_sync(5, 128);
    TR(9);
    {
      uint4 qa[4];
      #pragma unroll
      for (int p = 0; p < 4; p++) qa[p] = lds128(sb + R_Q + g * 256 + (p >> 1) * 128 + (fo ^ ((p & 1) << 6)));
      #pragma unroll
      for (int i = 0; i < 4; i++) { c[i][0] = c[i][1] = c[i][2] = c[i][3] = 0.f; }
      #pragma unroll
      for (int p = 0; p < 4; p++) { mma16(c[(p & 1) * 2], qa[p].x, 0, qa[p].y, 0, kf[p].x, kf[p].y); mma16(c[(p & 1) * 2 + 1], qa[p].z, 0, qa[p].w, 0, kf[p].z, kf[p].w); }
      float a = rbf(rbf((c[0][0] + c[1][0]) + (c[2][0] + c[3][0])) * scale) * l2e, b = rbf(rbf((c[0][1] + c[1][1]) + (c[2][1] + c[3][1])) * scale) * l2e;
      asm volatile("st.shared.v2.f32 [%0], {%1,%2};" ::"r"(sb + R_S + g * 160 + (8 * warp + 2 * t) * 4), "f"(a), "f"(b) : "memory");
    }
    TR(10);
    bar_sync(10, 128);
    float sv[8], pm[8];
    #pragma unroll
    for (int i = 0; i < 4; i++) asm volatile("ld.shared.v2.f32 {%0,%1}, [%2];" : "=f"(sv[2*i]), "=f"(sv[2*i+1]) : "r"(sb + R_S + g * 160 + (8 * i + 2 * t) * 4) : "memory");
    float mx = fmaxf(fmaxf(fmaxf(sv[0], sv[1]), fmaxf(sv[2], sv[3])), fmaxf(fmaxf(sv[4], sv[5]), fmaxf(sv[6], sv[7])));
    mx = fmaxf(mx, __shfl_xor_sync(~0u, mx, 1)); mx = fmaxf(mx, __shfl_xor_sync(~0u, mx, 2));
    uint32_t P[5];
    #pragma unroll
    for (int i = 0; i < 4; i++) P[i] = pack2(ex2(sv[2*i] - mx), ex2(sv[2*i+1] - mx));
    #pragma unroll
    for (int i = 0; i < 4; i++) { c[i][0] = c[i][1] = c[i][2] = c[i][3] = 0.f; }
    #pragma unroll
    for (int kk = 0; kk < 2; kk++) {
      mma16(c[0], P[2*kk], 0, P[2*kk+1], 0, vf[2*kk][0], vf[2*kk][1]); mma16(c[1], P[2*kk], 0, P[2*kk+1], 0, vf[2*kk][2], vf[2*kk][3]);
      mma16(c[2], P[2*kk], 0, P[2*kk+1], 0, vf[2*kk+1][0], vf[2*kk+1][1]); mma16(c[3], P[2*kk], 0, P[2*kk+1], 0, vf[2*kk+1][2], vf[2*kk+1][3]);
    }
    float sum = 0.f;
    #pragma unroll
    for (int i = 0; i < 4; i++) sum += __uint_as_float(P[i] << 16) + __uint_as_float(P[i] & 0xffff0000u);
    TR(11);
    bar_sync(2, 256);
    #pragma unroll
    for (int i = 0; i < 4; i++) asm volatile("ld.shared.v2.f32 {%0,%1}, [%2];" : "=f"(pm[2*i]), "=f"(pm[2*i+1]) : "r"(sb + R_SM + i * 256 + lane * 8) : "memory");
    const float s8 = rbf(rbf((pm[0] + pm[2]) + (pm[4] + pm[6])) * scale) * l2e, s9 = rbf(rbf((pm[1] + pm[3]) + (pm[5] + pm[7])) * scale) * l2e;
    float mg = fmaxf(mx, fmaxf(s8, s9));
    mg = fmaxf(mg, __shfl_xor_sync(~0u, mg, 1)); mg = fmaxf(mg, __shfl_xor_sync(~0u, mg, 2));
    const float fs = ex2(mx - mg);
    P[4] = pack2(ex2(s8 - mg), ex2(s9 - mg));
    #pragma unroll
    for (int i = 0; i < 4; i++) { c[i][0] *= fs; c[i][1] *= fs; }
    sum = fmaf(sum, fs, __uint_as_float(P[4] << 16) + __uint_as_float(P[4] & 0xffff0000u));
    sum += __shfl_xor_sync(~0u, sum, 1); sum += __shfl_xor_sync(~0u, sum, 2);
    float inv; asm("rcp.approx.ftz.f32 %0, %1;" : "=f"(inv) : "f"(sum));
    TR(6);
    bar_sync(3, 256);
    { uint32_t r[4]; ldsm4t(r, sb + R_VT + (s & 1) * VT_SZ + (32 + (lane & 7)) * 272 + (4 * warp + (lane >> 3)) * 16);
      #pragma unroll
      for (int i = 0; i < 4; i++) mma8(c[i], P[4], 0, r[i]); }
    asm volatile("stmatrix.sync.aligned.m8n8.x4.shared.b16 [%0], {%1,%2,%3,%4};" ::"r"(sb + R_O + so),
      "r"(pack2(c[0][0] * inv, c[0][1] * inv)), "r"(pack2(c[1][0] * inv, c[1][1] * inv)), "r"(pack2(c[2][0] * inv, c[2][1] * inv)), "r"(pack2(c[3][0] * inv, c[3][1] * inv)) : "memory");
    bar_arrive(7, 256);
    TR(7);
    bar_sync(8, 352);
    long long t0 = clock64();
    #pragma unroll
    for (int i = 0; i < 16; i++) { uint4 v = lds128(sb + R_WQ + ((warp * 16 + i) * 32 + lane) * 16); A[1][i][0] = v.x; A[1][i][1] = v.y; A[1][i][2] = v.z; A[1][i][3] = v.w; }
    while (clock64() - t0 < PDELAY);
  }
}

constexpr int I_M1 = 512, I_Q = 624, I_M2 = 880, I_AT = 1008, I_G = I_AT + 32, GSZ = 56, I_END = I_G + 15 * GSZ + 24;
constexpr int B_STG = 4 * 49152, B_BAR = B_STG + 8 * 2304;
struct Item { int type, rb, nt, ks; };
__device__ __forceinline__ Item decode(int it) {
  Item r; r.ks = 0;
  if (it < I_M1) { r.type = 0; r.rb = it >> 5; r.nt = it & 31; }
  else if (it < I_Q) { int i = it - I_M1; r.type = 1; r.rb = i / 7; r.nt = i % 7; }
  else if (it < I_M2) { int i = it - I_Q; r.type = 0; r.rb = i >> 4; r.nt = 32 + (i & 15); }
  else if (it < I_AT) { int i = it - I_M2; r.type = 2; r.rb = i >> 3; r.nt = (i >> 2) & 1; r.ks = i & 3; }
  else if (it < I_G) { r.type = 3; r.rb = 0; r.nt = it - I_AT; }
  else {
    int i = it - I_G, gi = i / GSZ, q = i % GSZ; if (gi == 15) q += 32;
    if (q < 32) { r.type = 3; r.rb = gi + 1; r.nt = q; }
    else if (q < 48) { r.type = 4; r.rb = gi; r.nt = (q - 32) >> 3; r.ks = (q - 32) & 7; }
    else { r.type = 5; r.rb = gi; r.nt = q - 48; } }
  return r;
}
__device__ __forceinline__ float gelu_t(float x) { float u = 0.7978845608028654f * (x + 0.044715f * x * x * x); float th; asm("tanh.approx.f32 %0, %1;" : "=f"(th) : "f"(u)); float hx = 0.5f * x; return fmaf(hx, th, hx); }

__device__ __forceinline__ void bulk(uint32_t sb, const Maps& mp, const bf16* __restrict__ x, const bf16* __restrict__ b1, const bf16* __restrict__ b2, bf16* __restrict__ out) {
  const int tid = threadIdx.x, warp = tid >> 5, lane = tid & 31, g = lane >> 2, t = lane & 3;
  const int bid = blockIdx.x - NREC;
  const uint32_t full = sb + B_BAR, empty = sb + B_BAR + 32, ifull = sb + B_BAR + 64, iempty = sb + B_BAR + 80;
  volatile int* ring = (volatile int*)(__cvta_shared_to_generic(sb + B_BAR + 96));
  if (warp >= 8) {
    asm volatile("setmaxnreg.dec.sync.aligned.u32 40;");
    if (tid == 256) {
      uint32_t st = 0, ph = 0;
      for (int n = 0;; n++) {
        int it = n == 0 ? bid : NBULK + atomicAdd(&g_fl.next, 1);
        Item I = decode(it);
        if (it < I_END) {
          if (I.type == 5) { wait_flag(&g_fl.s[I.rb][0], 16); wait_flag(&g_fl.z[I.rb][0], 8); }
          else if (I.type == 3) { wait_flag(&g_fl.prog[I.rb][I.nt], 8); wait_flag(&g_fl.tile[I.rb][I.nt >> 1], 1); wait_flag(&g_fl.tile[I.rb][16 + (I.nt >> 1)], 1); wait_flag(&g_fl.tile[I.rb][32 + (I.nt >> 1)], 1); fence_async(); }
          else if (I.type == 2) { wait_flag(&g_fl.hid[I.rb], 7); fence_async(); }
          else if (I.type == 4) { wait_flag(&g_fl.o[I.rb][I.ks], 4); fence_async(); }
        }
        mbar_wait(iempty + (n & 1) * 8, ((n >> 1) & 1) ^ 1);
        ring[n & 1] = it; mbar_arrive(ifull + (n & 1) * 8);
        if (it >= I_END) break;
        if (I.type == 5) continue;
        if (I.type == 3) {
          for (int m = 0; m < 3; m++) {
            mbar_wait(empty + st * 8, ph ^ 1);
            mbar_expect(full + st * 8, 32768);
            int col = (m == 0 ? 8192 : (m == 1 ? 0 : 4096)) + I.nt * 128;
            tma2d(sb + st * 49152, &mp.qkv, col, I.rb * 128, full + st * 8);
            tma2d(sb + st * 49152 + 16384, &mp.qkv, col + 64, I.rb * 128, full + st * 8);
            if (++st == 4) { st = 0; ph ^= 1; }
          }
          continue;
        }
        const CUtensorMap *ma, *mb; int nkb = 8, kb0 = 0, n0;
        if (I.type == 0) { ma = &mp.xn; mb = I.nt < 16 ? &mp.wk : (I.nt < 32 ? &mp.wv : &mp.wq); n0 = (I.nt & 15) * 256; }
        else if (I.type == 1) { ma = &mp.y; mb = &mp.w1; n0 = I.nt * 256; }
        else if (I.type == 2) { ma = &mp.hid; mb = &mp.w2; n0 = I.nt * 256; nkb = 7; kb0 = I.ks * 7; }
        else { ma = &mp.o; mb = &mp.wo; n0 = I.nt * 256; kb0 = I.ks * 8; }
        for (int kb = kb0; kb < kb0 + nkb; kb++) {
          mbar_wait(empty + st * 8, ph ^ 1);
          mbar_expect(full + st * 8, 49152);
          uint32_t sa = sb + st * 49152;
          tma2d(sa, ma, kb * 64, I.rb * 128, full + st * 8);
          #pragma unroll
          for (int q = 0; q < 4; q++) tma2d(sa + 16384 + q * 8192, mb, n0 + q * 64, kb * 64, full + st * 8);
          if (++st == 4) { st = 0; ph ^= 1; }
        }
      }
    } else if (warp == 9) {
      for (int n = 0;; n++) {
        mbar_wait(ifull + (n & 1) * 8, (n >> 1) & 1);
        int it = ring[n & 1];
        if (it >= I_END) break;
        Item I = decode(it);
        bar_sync(6 + (n & 1), 288);
        if (lane == 0) {
          if (I.type != 5) {
            fence_async(); __threadfence();
            int* f = I.type == 0 ? &g_fl.tile[I.rb][I.nt] : I.type == 1 ? &g_fl.hid[I.rb] : I.type == 2 ? &g_fl.z[I.rb][0] : I.type == 3 ? &g_fl.o[I.rb][I.nt >> 2] : &g_fl.s[I.rb][0];
            atomicAdd(f, 1);
          }
          mbar_arrive(iempty + (n & 1) * 8);
        }
      }
    }
    return;
  }
  asm volatile("setmaxnreg.inc.sync.aligned.u32 232;");
  const int wg = warp >> 2;
  const uint32_t stg = sb + B_STG + warp * 2304;
  const int lm = lane >> 3, lr = lane & 7;
  uint32_t st = 0, ph = 0;
  float d[128];
  #pragma unroll 1
  for (int n = 0;; n++) {
    mbar_wait(ifull + (n & 1) * 8, (n >> 1) & 1);
    const int it = ring[n & 1];
    __syncwarp(); if (lane == 0) mbar_arrive(iempty + (n & 1) * 8);
    if (it >= I_END) break;
    Item I = decode(it);
    const int row0 = I.rb * 128 + warp * 16;
    TB(0);
    if (I.type == 5) {
      #pragma unroll
      for (int i = 0; i < 4; i++) {
        size_t off = (size_t)(I.rb * 128 + I.nt * 16 + warp * 2 + (i >> 1)) * DM + (i & 1) * 256 + lane * 8;
        float4 s0 = __ldcg((const float4*)(g_s + off)), s1 = __ldcg((const float4*)(g_s + off + 4));
        float4 z0 = __ldcg((const float4*)(g_z + off)), z1 = __ldcg((const float4*)(g_z + off + 4));
        uint4 xv = *(const uint4*)(x + off), bv = *(const uint4*)(b2 + (i & 1) * 256 + lane * 8);
        float sa[8] = {s0.x, s0.y, s0.z, s0.w, s1.x, s1.y, s1.z, s1.w}, za[8] = {z0.x, z0.y, z0.z, z0.w, z1.x, z1.y, z1.z, z1.w}, r[8];
        #pragma unroll
        for (int e = 0; e < 8; e++) { float xx = __bfloat162float(((const bf16*)&xv)[e]), bb = __bfloat162float(((const bf16*)&bv)[e]);
          float u = rbf(rbf(za[e]) + bb); float gg = rbf(__fdividef(u, 1.f + __expf(-u))); r[e] = xx + rbf(rbf(sa[e]) * gg); }
        *(uint4*)(out + off) = make_uint4(pack2(r[0], r[1]), pack2(r[2], r[3]), pack2(r[4], r[5]), pack2(r[6], r[7]));
      }
      bar_arrive(6 + (n & 1), 288);
      continue;
    }
    if (I.type == 3) {
      const int h = I.nt, seg = warp >> 1, half = warp & 1, step = I.rb * 4 + seg;
      uint32_t kmr[16], vmr[16];
      { const uint32_t* km = (const uint32_t*)(g_km + ((size_t)(step * 32 + h)) * 1024) + g * 64 + t;
        const uint32_t* vm = (const uint32_t*)(g_vmT + ((size_t)(step * 32 + h)) * 1024) + g * 4 + t;
        #pragma unroll
        for (int i = 0; i < 16; i++) { kmr[i] = __ldcg(km + i * 4); vmr[i] = __ldcg(vm + i * 32); } }
      uint32_t sQ = sb + st * 49152; mbar_wait(full + st * 8, ph); uint32_t eQ = empty + st * 8; if (++st == 4) { st = 0; ph ^= 1; }
      uint32_t sK = sb + st * 49152; mbar_wait(full + st * 8, ph); uint32_t eK = empty + st * 8; if (++st == 4) { st = 0; ph ^= 1; }
      float sc[5][4];
      #pragma unroll
      for (int i = 0; i < 5; i++) { sc[i][0] = sc[i][1] = sc[i][2] = sc[i][3] = 0.f; }
      #pragma unroll
      for (int ks = 0; ks < 8; ks++) {
        uint32_t a[4]; { int r = warp * 16 + 8 * (lm & 1) + lr, c8 = 2 * ks + (lm >> 1); ldsm4(a, sQ + (c8 >> 3) * 16384 + r * 128 + (((c8 & 7) ^ (r & 7)) << 4)); }
        #pragma unroll
        for (int np = 0; np < 2; np++) {
          if (np == 1 && half == 0) continue;
          uint32_t b[4]; int r = seg * 32 + 16 * np + 8 * (lm >> 1) + lr, c8 = 2 * ks + (lm & 1);
          ldsm4(b, sK + (c8 >> 3) * 16384 + r * 128 + (((c8 & 7) ^ (r & 7)) << 4));
          mma16(sc[2*np], a[0], a[1], a[2], a[3], b[0], b[1]); mma16(sc[2*np+1], a[0], a[1], a[2], a[3], b[2], b[3]);
        }
        mma16(sc[4], a[0], a[1], a[2], a[3], kmr[2*ks], kmr[2*ks+1]);
      }
      __syncwarp(); if (lane == 0) { mbar_arrive(eQ); mbar_arrive(eK); }
      const float scale = 0.08838834764831845f;
      uint32_t P[5][2];
      #pragma unroll
      for (int rr = 0; rr < 2; rr++) {
        const int qi = 16 * half + g + 8 * rr;
        float mx = -3.0e38f;
        #pragma unroll
        for (int i = 0; i < 5; i++)
          #pragma unroll
          for (int e = 0; e < 2; e++) { float v = rbf(rbf(sc[i][2*rr+e]) * scale); if (i < 4 && 8 * i + 2 * t + e > qi) v = -1.0e9f; sc[i][2*rr+e] = v; mx = fmaxf(mx, v); }
        mx = fmaxf(mx, __shfl_xor_sync(~0u, mx, 1)); mx = fmaxf(mx, __shfl_xor_sync(~0u, mx, 2));
        float sum = 0;
        #pragma unroll
        for (int i = 0; i < 5; i++)
          #pragma unroll
          for (int e = 0; e < 2; e++) { float v = __expf(sc[i][2*rr+e] - mx); sc[i][2*rr+e] = v; sum += v; }
        sum += __shfl_xor_sync(~0u, sum, 1); sum += __shfl_xor_sync(~0u, sum, 2);
        float inv = __fdividef(1.f, sum);
        #pragma unroll
        for (int i = 0; i < 5; i++) P[i][rr] = pack2(sc[i][2*rr] * inv, sc[i][2*rr+1] * inv);
      }
      uint32_t sV = sb + st * 49152; mbar_wait(full + st * 8, ph); uint32_t eV = empty + st * 8; if (++st == 4) { st = 0; ph ^= 1; }
      #pragma unroll
      for (int i = 0; i < 64; i++) d[i] = 0.f;
      #pragma unroll
      for (int n2 = 0; n2 < 8; n2++) {
        #pragma unroll
        for (int kk = 0; kk < 2; kk++) {
          if (kk == 1 && half == 0) continue;
          uint32_t b[4]; int r = seg * 32 + 16 * kk + 8 * (lm & 1) + lr, c8 = 2 * n2 + (lm >> 1);
          ldsm4t(b, sV + (c8 >> 3) * 16384 + r * 128 + (((c8 & 7) ^ (r & 7)) << 4));
          mma16(d + 8 * n2, P[2*kk][0], P[2*kk][1], P[2*kk+1][0], P[2*kk+1][1], b[0], b[1]);
          mma16(d + 8 * n2 + 4, P[2*kk][0], P[2*kk][1], P[2*kk+1][0], P[2*kk+1][1], b[2], b[3]);
        }
        mma8(d + 8 * n2, P[4][0], P[4][1], vmr[2*n2]); mma8(d + 8 * n2 + 4, P[4][0], P[4][1], vmr[2*n2+1]);
      }
      __syncwarp(); if (lane == 0) mbar_arrive(eV);
      #pragma unroll
      for (int ch = 0; ch < 2; ch++) {
        #pragma unroll
        for (int i = 0; i < 8; i++) { const float* a = d + ch * 32 + i * 4;
          sts32(stg + g * 144 + i * 16 + t * 4, pack2(a[0], a[1])); sts32(stg + (g + 8) * 144 + i * 16 + t * 4, pack2(a[2], a[3])); }
        __syncwarp();
        #pragma unroll
        for (int i = 0; i < 4; i++) { int r = i * 4 + lm; uint4 v = lds128(stg + r * 144 + lr * 16);
          *(uint4*)(g_o + (size_t)(row0 + r) * 4096 + h * 128 + ch * 64 + lr * 8) = v; }
        __syncwarp();
      }
      bar_arrive(6 + (n & 1), 288);
      continue;
    }
    const int nkb = I.type == 2 ? 7 : 8;
    uint32_t prev = 0;
    for (int kb = 0; kb < nkb; kb++) {
      mbar_wait(full + st * 8, ph);
      uint32_t sa = sb + st * 49152;
      asm volatile("wgmma.fence.sync.aligned;" ::: "memory");
      #pragma unroll
      for (int k = 0; k < 4; k++)
        wgmma256(d, mkdesc(sa + wg * 8192 + k * 32, 16, 1024), mkdesc(sa + 16384 + k * 2048, 8192, 1024), (kb | k) != 0);
      asm volatile("wgmma.commit_group.sync.aligned;" ::: "memory");
      if (kb > 0) { asm volatile("wgmma.wait_group.sync.aligned 1;" ::: "memory"); if (lane == 0) mbar_arrive(prev); }
      prev = empty + st * 8;
      if (++st == 4) { st = 0; ph ^= 1; }
    }
    asm volatile("wgmma.wait_group.sync.aligned 0;" ::: "memory");
    if (lane == 0) mbar_arrive(prev);
    TB(1);
    if (I.type <= 1) {
      bf16* dst; int ld;
      if (I.type == 0) { dst = g_qkv + (size_t)row0 * QW + I.nt * 256; ld = QW; } else { dst = g_hid + (size_t)row0 * FF + I.nt * 256; ld = FF; }
      #pragma unroll
      for (int ch = 0; ch < 4; ch++) {
        #pragma unroll
        for (int i = 0; i < 8; i++) { float* a = d + ch * 32 + i * 4;
          if (I.type == 1) { float2 bb = __bfloat1622float2(*(const __nv_bfloat162*)(b1 + I.nt * 256 + ch * 64 + i * 8 + 2 * t));
            a[0] = gelu_t(rbf(rbf(a[0]) + bb.x)); a[1] = gelu_t(rbf(rbf(a[1]) + bb.y)); a[2] = gelu_t(rbf(rbf(a[2]) + bb.x)); a[3] = gelu_t(rbf(rbf(a[3]) + bb.y)); }
          sts32(stg + g * 144 + i * 16 + t * 4, pack2(a[0], a[1])); sts32(stg + (g + 8) * 144 + i * 16 + t * 4, pack2(a[2], a[3])); }
        __syncwarp();
        #pragma unroll
        for (int i = 0; i < 4; i++) { int r = i * 4 + lm; uint4 v = lds128(stg + r * 144 + lr * 16); *(uint4*)(dst + (size_t)r * ld + ch * 64 + lr * 8) = v; }
        __syncwarp();
      }
    } else {
      float* dst = (I.type == 2 ? g_z : g_s) + (size_t)(row0 + g) * DM + I.nt * 256 + 2 * t;
      #pragma unroll
      for (int i = 0; i < 32; i++) {
        asm volatile("red.relaxed.gpu.global.add.v2.f32 [%0], {%1,%2};" ::"l"(dst + i * 8), "f"(d[4*i]), "f"(d[4*i+1]) : "memory");
        asm volatile("red.relaxed.gpu.global.add.v2.f32 [%0], {%1,%2};" ::"l"(dst + 8 * DM + i * 8), "f"(d[4*i+2]), "f"(d[4*i+3]) : "memory");
      }
    }
    bar_arrive(6 + (n & 1), 288);
  }
}

__global__ void __cluster_dims__(2, 1, 1) __launch_bounds__(384, 1)
main_kernel(const __grid_constant__ Maps mp, const bf16* x, const bf16* Wq, const bf16* Wk, const bf16* Wv, const bf16* Wo, const bf16* b1, const bf16* b2, bf16* out) {
  const uint32_t sb = smem_u32(smem_raw);
  if (sb & 1023) __trap();
  if (threadIdx.x == 0) {
    if (blockIdx.x < NREC) { mbar_init(sb + R_BAR, 1); mbar_init(sb + R_BAR + 8, 1); mbar_init(sb + R_BAR + 16, 1); }
    else { for (int i = 0; i < 4; i++) { mbar_init(sb + B_BAR + i * 8, 1); mbar_init(sb + B_BAR + 32 + i * 8, 8); }
      for (int i = 0; i < 2; i++) { mbar_init(sb + B_BAR + 64 + i * 8, 1); mbar_init(sb + B_BAR + 80 + i * 8, 9); } }
    asm volatile("fence.mbarrier_init.release.cluster;" ::: "memory");
  }
  asm volatile("barrier.cluster.arrive.release.aligned; barrier.cluster.wait.acquire.aligned;" ::: "memory");
  if (blockIdx.x < NREC) recurrence(sb, Wq, Wk, Wv, Wo);
  else bulk(sb, mp, x, b1, b2, out);
}

typedef CUresult (*EncFn)(CUtensorMap*, CUtensorMapDataType, cuuint32_t, void*, const cuuint64_t*, const cuuint64_t*, const cuuint32_t*, const cuuint32_t*, CUtensorMapInterleave, CUtensorMapSwizzle, CUtensorMapL2promotion, CUtensorMapFloatOOBfill);
static void mk(EncFn f, CUtensorMap* m, const void* p, uint64_t rows, uint64_t cols, uint32_t boxr) {
  cuuint64_t dims[2] = {cols, rows}, str[1] = {cols * 2}; cuuint32_t box[2] = {64, boxr}, es[2] = {1, 1};
  f(m, CU_TENSOR_MAP_DATA_TYPE_BFLOAT16, 2, (void*)p, dims, str, box, es, CU_TENSOR_MAP_INTERLEAVE_NONE, CU_TENSOR_MAP_SWIZZLE_128B, CU_TENSOR_MAP_L2_PROMOTION_L2_256B, CU_TENSOR_MAP_FLOAT_OOB_FILL_NONE);
}
extern "C" void kernel_launch(void* const* d_in, const int* in_sizes, int n_in, void* d_out, int out_size) {
  const bf16 *x = (const bf16*)d_in[0], *mem0 = (const bf16*)d_in[1], *Wq = (const bf16*)d_in[2], *Wk = (const bf16*)d_in[3], *Wv = (const bf16*)d_in[4], *Wo = (const bf16*)d_in[5];
  const bf16 *w1 = (const bf16*)d_in[8], *b1 = (const bf16*)d_in[9], *w2 = (const bf16*)d_in[10], *b2 = (const bf16*)d_in[11];
  void* fn = nullptr; cudaDriverEntryPointQueryResult qr;
  cudaGetDriverEntryPoint("cuTensorMapEncodeTiled", &fn, cudaEnableDefault, &qr);
  EncFn f = (EncFn)fn;
  void *pxn, *py, *ph, *po, *pq;
  cudaGetSymbolAddress(&pxn, g_xn); cudaGetSymbolAddress(&py, g_y); cudaGetSymbolAddress(&ph, g_hid); cudaGetSymbolAddress(&po, g_o); cudaGetSymbolAddress(&pq, g_qkv);
  Maps mp;
  mk(f, &mp.xn, pxn, SEQ, DM, 128); mk(f, &mp.y, py, SEQ, DM, 128); mk(f, &mp.hid, ph, SEQ, FF, 128); mk(f, &mp.o, po, SEQ, 4096, 128); mk(f, &mp.qkv, pq, SEQ, QW, 128);
  mk(f, &mp.wk, Wk, DM, 4096, 64); mk(f, &mp.wv, Wv, DM, 4096, 64); mk(f, &mp.wq, Wq, DM, 4096, 64);
  mk(f, &mp.w1, w1, DM, FF, 64); mk(f, &mp.w2, w2, FF, DM, 64); mk(f, &mp.wo, Wo, 4096, DM, 64);
  cudaFuncSetAttribute(main_kernel, cudaFuncAttributeMaxDynamicSharedMemorySize, SMEM_BYTES);
  prologue_kernel<<<256, 256, 0, cudaStreamPerThread>>>(x, mem0, Wq, Wk, Wv, Wo);
  main_kernel<<<NCTA, 384, SMEM_BYTES, cudaStreamPerThread>>>(mp, x, Wq, Wk, Wv, Wo, b1, b2, (bf16*)d_out);
}
```

```cpp
#include <cuda_runtime.h>
#include <cuda_bf16.h>
#include <cuda.h>
#include <stdint.h>

typedef __nv_bfloat16 bf16;
constexpr int SEQ = 2048, DM = 512, FF = 1792, QW = 12288, NSTEP = 64;
constexpr int NREC = 64, NBULK = 68, NCTA = 132;
constexpr int SPIN_LIMIT = 1 << 22;
#define THR 4
#define PDELAY 500

__device__ bf16 g_xn[SEQ * DM];
__device__ bf16 g_y[SEQ * DM];
__device__ bf16 g_qkv[(size_t)SEQ * QW];
__device__ bf16 g_hid[SEQ * FF];
__device__ bf16 g_o[(size_t)SEQ * 4096];
#define NFULL 13
__device__ bf16 g_g[SEQ * DM];
__device__ float g_sp[(16 - NFULL) * 8 * 128 * DM];
__device__ float4 g_acc[NSTEP][2][768];
__device__ bf16 g_km[NSTEP * 32 * 8 * 128];
__device__ bf16 g_vmT[NSTEP * 32 * 128 * 8];
struct Flags { int tile[16][48]; int hid[16]; int z[16][2]; int o[16][8]; int s[16][2]; int prog[16][32]; int next; };
__device__ Flags g_fl;

#define TR(i)
#define TB(i)
#define TI(i)
struct Maps { CUtensorMap xn, y, hid, o, qkv, wk, wv, wq, w1, w2, wo; };

extern __shared__ __align__(1024) uint8_t smem_raw[];
__device__ __forceinline__ uint4 ldc(uint32_t off) { return *(const uint4*)(smem_raw + off); }
__device__ __forceinline__ uint32_t smem_u32(const void* p) { return (uint32_t)__cvta_generic_to_shared(p); }
__device__ __forceinline__ int otid() { int t; asm volatile("mov.u32 %0, %%tid.x;" : "=r"(t)); return t; }
__device__ __forceinline__ uint32_t mapa(uint32_t a, uint32_t r) { uint32_t o; asm volatile("mapa.shared::cluster.u32 %0, %1, %2;" : "=r"(o) : "r"(a), "r"(r)); return o; }
__device__ __forceinline__ void st_async_v4(uint32_t addr, float a, float b, float c, float d, uint32_t mbar) {
  asm volatile("st.async.weak.shared::cluster.mbarrier::complete_tx::bytes.v4.b32 [%0], {%1,%2,%3,%4}, [%5];" ::"r"(addr), "r"(__float_as_uint(a)), "r"(__float_as_uint(b)), "r"(__float_as_uint(c)), "r"(__float_as_uint(d)), "r"(mbar) : "memory"); }
__device__ __forceinline__ void mbar_init(uint32_t m, int c) { asm volatile("mbarrier.init.shared::cta.b64 [%0], %1;" ::"r"(m), "r"(c) : "memory"); }
__device__ __forceinline__ void mbar_expect(uint32_t m, int bytes) { asm volatile("mbarrier.arrive.expect_tx.shared::cta.b64 _, [%0], %1;" ::"r"(m), "r"(bytes) : "memory"); }
__device__ __forceinline__ void mbar_arrive(uint32_t m) { asm volatile("mbarrier.arrive.shared::cta.b64 _, [%0];" ::"r"(m) : "memory"); }
__device__ __forceinline__ void mbar_wait(uint32_t m, uint32_t parity) {
  uint32_t ok; int it = 0;
  do { asm volatile("{.reg .pred p; mbarrier.try_wait.parity.shared::cta.b64 p, [%1], %2; selp.u32 %0,1,0,p;}" : "=r"(ok) : "r"(m), "r"(parity) : "memory"); } while (!ok && ++it < SPIN_LIMIT); }
__device__ __forceinline__ void mbar_spin(uint32_t m, uint32_t parity) {
  uint32_t ok; int it = 0;
  do { asm volatile("{.reg .pred p; mbarrier.test_wait.parity.shared::cta.b64 p, [%1], %2; selp.u32 %0,1,0,p;}" : "=r"(ok) : "r"(m), "r"(parity) : "memory"); } while (!ok && ++it < SPIN_LIMIT); }
__device__ __forceinline__ void bar_sync(int id, int n) { asm volatile("bar.sync %0, %1;" ::"r"(id), "r"(n) : "memory"); }
__device__ __forceinline__ void bar_arrive(int id, int n) { asm volatile("bar.arrive %0, %1;" ::"r"(id), "r"(n) : "memory"); }
__device__ __forceinline__ int ld_acq(const int* p) { int v; asm volatile("ld.acquire.gpu.global.s32 %0, [%1];" : "=r"(v) : "l"(p) : "memory"); return v; }
__device__ __forceinline__ void wait_flag(const int* p, int target) { int it = 0; while (ld_acq(p) < target && ++it < SPIN_LIMIT) { __nanosleep(40); } }
__device__ __forceinline__ void fence_async() { asm volatile("fence.proxy.async.global;" ::: "memory"); }
__device__ __forceinline__ uint4 lds128(uint32_t a) { uint4 v; asm volatile("ld.shared.v4.u32 {%0,%1,%2,%3}, [%4];" : "=r"(v.x), "=r"(v.y), "=r"(v.z), "=r"(v.w) : "r"(a) : "memory"); return v; }
__device__ __forceinline__ void sts128(uint32_t a, uint4 v) { asm volatile("st.shared.v4.u32 [%0], {%1,%2,%3,%4};" ::"r"(a), "r"(v.x), "r"(v.y), "r"(v.z), "r"(v.w) : "memory"); }
__device__ __forceinline__ void sts32(uint32_t a, uint32_t v) { asm volatile("st.shared.u32 [%0], %1;" ::"r"(a), "r"(v) : "memory"); }
__device__ __forceinline__ void sts16(uint32_t a, float f) { unsigned short h = __bfloat16_as_ushort(__float2bfloat16(f)); asm volatile("st.shared.u16 [%0], %1;" ::"r"(a), "h"(h) : "memory"); }
__device__ __forceinline__ void ldsm4(uint32_t* r, uint32_t a) { asm volatile("ldmatrix.sync.aligned.m8n8.x4.shared.b16 {%0,%1,%2,%3}, [%4];" : "=r"(r[0]), "=r"(r[1]), "=r"(r[2]), "=r"(r[3]) : "r"(a) : "memory"); }
__device__ __forceinline__ void ldsm4t(uint32_t* r, uint32_t a) { asm volatile("ldmatrix.sync.aligned.m8n8.x4.trans.shared.b16 {%0,%1,%2,%3}, [%4];" : "=r"(r[0]), "=r"(r[1]), "=r"(r[2]), "=r"(r[3]) : "r"(a) : "memory"); }
__device__ __forceinline__ void mma16(float* c, uint32_t a0, uint32_t a1, uint32_t a2, uint32_t a3, uint32_t b0, uint32_t b1) {
  asm("mma.sync.aligned.m16n8k16.row.col.f32.bf16.bf16.f32 {%0,%1,%2,%3}, {%4,%5,%6,%7}, {%8,%9}, {%0,%1,%2,%3};" : "+f"(c[0]), "+f"(c[1]), "+f"(c[2]), "+f"(c[3]) : "r"(a0), "r"(a1), "r"(a2), "r"(a3), "r"(b0), "r"(b1)); }
__device__ __forceinline__ void mma8(float* c, uint32_t a0, uint32_t a1, uint32_t b0) {
  asm("mma.sync.aligned.m16n8k8.row.col.f32.bf16.bf16.f32 {%0,%1,%2,%3}, {%4,%5}, {%6}, {%0,%1,%2,%3};" : "+f"(c[0]), "+f"(c[1]), "+f"(c[2]), "+f"(c[3]) : "r"(a0), "r"(a1), "r"(b0)); }
__device__ __forceinline__ uint32_t pack2(float a, float b) { __nv_bfloat162 h = __floats2bfloat162_rn(a, b); return *(uint32_t*)&h; }
__device__ __forceinline__ float rbf(float x) { uint32_t r; asm("cvt.rn.bf16x2.f32 %0, %1, %2;" : "=r"(r) : "f"(x), "f"(0.f)); return __uint_as_float(r); }
__device__ __forceinline__ void cp16(uint32_t d, const void* s) { asm volatile("cp.async.cg.shared.global [%0], [%1], 16;" ::"r"(d), "l"(s) : "memory"); }
__device__ __forceinline__ void tma2d(uint32_t dst, const CUtensorMap* m, int c0, int c1, uint32_t mbar) {
  asm volatile("cp.async.bulk.tensor.2d.shared::cluster.global.mbarrier::complete_tx::bytes [%0], [%1, {%2,%3}], [%4];" ::"r"(dst), "l"(m), "r"(c0), "r"(c1), "r"(mbar) : "memory"); }
__device__ __forceinline__ uint64_t mkdesc(uint32_t addr, uint32_t lbo, uint32_t sbo) {
  return (uint64_t)((addr & 0x3FFFF) >> 4) | ((uint64_t)(lbo >> 4) << 16) | ((uint64_t)(sbo >> 4) << 32) | (1ull << 62); }

#define R8(i) "+f"(d[i]), "+f"(d[i+1]), "+f"(d[i+2]), "+f"(d[i+3]), "+f"(d[i+4]), "+f"(d[i+5]), "+f"(d[i+6]), "+f"(d[i+7])
__device__ __forceinline__ void wgmma256(float* d, uint64_t da, uint64_t db, int acc) {
  asm volatile("{.reg .pred p; setp.ne.b32 p, %130, 0;\n"
    "wgmma.mma_async.sync.aligned.m64n256k16.f32.bf16.bf16 {"
    "%0,%1,%2,%3,%4,%5,%6,%7,%8,%9,%10,%11,%12,%13,%14,%15,%16,%17,%18,%19,%20,%21,%22,%23,%24,%25,%26,%27,%28,%29,%30,%31,"
    "%32,%33,%34,%35,%36,%37,%38,%39,%40,%41,%42,%43,%44,%45,%46,%47,%48,%49,%50,%51,%52,%53,%54,%55,%56,%57,%58,%59,%60,%61,%62,%63,"
    "%64,%65,%66,%67,%68,%69,%70,%71,%72,%73,%74,%75,%76,%77,%78,%79,%80,%81,%82,%83,%84,%85,%86,%87,%88,%89,%90,%91,%92,%93,%94,%95,"
    "%96,%97,%98,%99,%100,%101,%102,%103,%104,%105,%106,%107,%108,%109,%110,%111,%112,%113,%114,%115,%116,%117,%118,%119,%120,%121,%122,%123,%124,%125,%126,%127"
    "}, %128, %129, p, 1, 1, 0, 1;}"
    : R8(0), R8(8), R8(16), R8(24), R8(32), R8(40), R8(48), R8(56), R8(64), R8(72), R8(80), R8(88), R8(96), R8(104), R8(112), R8(120)
    : "l"(da), "l"(db), "r"(acc)); }

__global__ void __launch_bounds__(256) prologue_kernel(const bf16* __restrict__ x, const bf16* __restrict__ mem0, const bf16* Wq, const bf16* Wk, const bf16* Wv, const bf16* Wo) {
  int tid = threadIdx.x, lane = tid & 31, warp = tid >> 5;
  { const int gt = blockIdx.x * 256 + tid; const size_t o = (size_t)(gt & 32767) * 64;
    asm volatile("prefetch.global.L2 [%0];" ::"l"((gt < 32768 ? Wk : Wv) + o));
    asm volatile("prefetch.global.L2 [%0];" ::"l"((gt < 32768 ? Wq : Wo) + o)); }
  int row = blockIdx.x * 8 + warp;
  {
    const uint4* src = (const uint4*)(x + (size_t)row * DM);
    uint4 u[2] = { src[lane], src[lane + 32] };
    float v[16];
    #pragma unroll
    for (int i = 0; i < 2; i++) { const __nv_bfloat162* h = (const __nv_bfloat162*)&u[i];
      #pragma unroll
      for (int k = 0; k < 4; k++) { float2 f = __bfloat1622float2(h[k]); v[i * 8 + 2 * k] = f.x; v[i * 8 + 2 * k + 1] = f.y; } }
    #pragma unroll
    for (int pass = 0; pass < 2; pass++) {
      float s = 0;
      #pragma unroll
      for (int i = 0; i < 16; i++) s += v[i];
      #pragma unroll
      for (int o = 16; o; o >>= 1) s += __shfl_xor_sync(~0u, s, o);
      float mf = s * (1.f / DM);
      float q = 0;
      #pragma unroll
      for (int i = 0; i < 16; i++) { float dd = v[i] - mf; q += dd * dd; }
      #pragma unroll
      for (int o = 16; o; o >>= 1) q += __shfl_xor_sync(~0u, q, o);
      float m = rbf(mf), var = rbf(q * (1.f / DM));
      float den = rbf(sqrtf(rbf(var + 1e-5f)));
      #pragma unroll
      for (int i = 0; i < 16; i++) v[i] = rbf(rbf(v[i] - m) / den);
      uint4 o4[2];
      #pragma unroll
      for (int i = 0; i < 2; i++) { o4[i].x = pack2(v[i*8], v[i*8+1]); o4[i].y = pack2(v[i*8+2], v[i*8+3]); o4[i].z = pack2(v[i*8+4], v[i*8+5]); o4[i].w = pack2(v[i*8+6], v[i*8+7]); }
      uint4* dst = (uint4*)((pass ? g_y : g_xn) + (size_t)row * DM);
      dst[lane] = o4[0]; dst[lane + 32] = o4[1];
    }
  }
  int gt = blockIdx.x * 256 + tid;
  float4 z4 = make_float4(0, 0, 0, 0);
  for (int i = gt; i < NSTEP * 1536; i += 65536) {
    float4 val = z4;
    if (i < 1536) {
      int j = i / 768, c = i % 768, ci = c >> 8, w = (c & 255) >> 5, l = c & 31, g = l >> 2, t = l & 3;
      float e3[3];
      #pragma unroll
      for (int k = 0; k < 3; k++) { int e = ci * 3 + k; int mt = e >> 2, cc = e & 3;
        e3[k] = e < 8 ? __bfloat162float(mem0[(2 * t + (cc & 1)) * DM + 256 * j + 32 * w + 16 * mt + g + 8 * (cc >> 1)]) : 0.f; }
      val = make_float4(e3[0], e3[1], e3[2], 32.f);
    }
    (&g_acc[0][0][0])[i] = val;
  }
  if (gt < (int)(sizeof(Flags) / 4)) ((int*)&g_fl)[gt] = 0;
}

constexpr int R_WR = 0, R_WO = 65536, R_KT = 131072, KT_SZ = 40 * 256, R_VT = R_KT + 2 * KT_SZ, VT_SZ = 40 * 272,
              R_MEM = R_VT + 2 * VT_SZ, R_Q = R_MEM + 32 * 160, R_O = R_Q + 8 * 256, R_S = R_O + 8 * 256,
              R_SM = R_S + 8 * 40 * 4, R_RQK = R_SM + 1024, R_RV = R_RQK + 8192, R_WQ = R_RV + 4096, R_BAR = 232448 - 64, R_END = R_BAR + 64;
static_assert(R_WQ + 32768 <= R_BAR, "smem");
#define PI 0
#define LD1(v, p) asm volatile("ld.relaxed.gpu.global.v4.u32 {%0,%1,%2,%3}, [%4];" : "=r"(v.x), "=r"(v.y), "=r"(v.z), "=r"(v.w) : "l"(p) : "memory")
#define LD3(a, b, c) do { LD1(a, src + ((EXP & 2) ? 256 * (h % 3) : 0)); if (EXP & 2) { b = a; c = a; } else { LD1(b, src + 256); LD1(c, src + 512); } } while (0)
#define OK3(a, b, c) __all_sync(~0u, (a.w == 0x42000000u) && (b.w == 0x42000000u) && (c.w == 0x42000000u))
#define W7D 1100
#define NW0 8
#define VD 0
#define KD 150
#define VCH 2
#define VP 3
__device__ __forceinline__ void wgmma8(float* d, uint64_t da, uint64_t db, int acc) {
  asm volatile("{.reg .pred p; setp.ne.b32 p, %6, 0;\n wgmma.mma_async.sync.aligned.m64n8k16.f32.bf16.bf16 {%0,%1,%2,%3}, %4, %5, p, 1, 1, 0, 0;}"
    : "+f"(d[0]), "+f"(d[1]), "+f"(d[2]), "+f"(d[3]) : "l"(da), "l"(db), "r"(acc)); }
__device__ __forceinline__ void stsm4(uint32_t a, uint32_t r0, uint32_t r1, uint32_t r2, uint32_t r3) { asm volatile("stmatrix.sync.aligned.m8n8.x4.shared.b16 [%0], {%1,%2,%3,%4};" ::"r"(a), "r"(r0), "r"(r1), "r"(r2), "r"(r3) : "memory"); }
__device__ __forceinline__ uint32_t swz(uint32_t r) { return ((r & 1) << 2) | ((r >> 1) & 3); }
__device__ __forceinline__ void stsm4t(uint32_t a, uint32_t r0, uint32_t r1, uint32_t r2, uint32_t r3) { asm volatile("stmatrix.sync.aligned.m8n8.x4.trans.shared.b16 [%0], {%1,%2,%3,%4};" ::"r"(a), "r"(r0), "r"(r1), "r"(r2), "r"(r3) : "memory"); }
__device__ __forceinline__ void stsm2(uint32_t a, uint32_t r0, uint32_t r1) { asm volatile("stmatrix.sync.aligned.m8n8.x2.shared.b16 [%0], {%1,%2};" ::"r"(a), "r"(r0), "r"(r1) : "memory"); }
__device__ __forceinline__ float ex2(float x) { float r; asm("ex2.approx.ftz.f32 %0, %1;" : "=f"(r) : "f"(x)); return r; }
#define REDV4(p, a, b, c) asm volatile("red.relaxed.gpu.global.add.v4.f32 [%0], {%1,%2,%3,%4};" ::"l"(p), "f"(a), "f"(b), "f"(c), "f"(RCNT) : "memory")
#define EXP 0
#define RCNT ((EXP & 1) ? 4.0f : 1.0f)
constexpr int SMEM_BYTES = 232448;
static_assert(R_END <= SMEM_BYTES, "smem");

__device__ __forceinline__ void recurrence(uint32_t sb, const bf16* __restrict__ Wq, const bf16* __restrict__ Wk, const bf16* __restrict__ Wv, const bf16* __restrict__ Wo) {
  const int tid = threadIdx.x, warp = tid >> 5, lane = tid & 31, g = lane >> 2, t = lane & 3;
  const int h = blockIdx.x >> 1, j = blockIdx.x & 1;
  const uint32_t peer = j ^ 1;
  const uint32_t mQ = sb + R_BAR, mV = sb + R_BAR + 8, mK = sb + R_BAR + 16;
  uint32_t A[2][16][4];
  TI(1);
  const int lm = lane >> 3, lr = lane & 7;
  for (int i = tid; i < 256 * 16; i += 384) { const int r = i >> 4, c = i & 15; const size_t o = ((size_t)(256 * j + r)) * 4096 + h * 128 + c * 8;
    const uint32_t d = sb + r * 256 + ((c ^ ((r & 1) | ((r >> 2) & 6))) << 4);
    cp16(d + 131072, Wq + o); cp16(d + 65536, Wk + o); cp16(d, Wv + o); }
  auto ldwo = [&](int half, uint32_t st) {
    for (int i = tid; i < 64 * 32; i += 384) { const int r = i >> 5, c = i & 31;
      cp16(st + r * 512 + ((c ^ ((r & 1) | ((r >> 2) & 6))) << 4), Wo + ((size_t)(h * 128 + 64 * half + r)) * DM + 256 * j + c * 8); } };
  auto cvwo = [&](int half, uint32_t st) {
    if (warp < 8) {
      #pragma unroll
      for (int i = 0; i < 8; i++) { const int wv = warp >> 1, mt = warp & 1, kq = i & 3, hi = i >> 2;
        const int k = 32 * (kq >> 1) + 8 * (lr >> 1) + (lr & 1) + 4 * (kq & 1) + 2 * (lm >> 1); uint32_t r[4];
        ldsm4t(r, st + k * 512 + (((8 * wv + 4 * mt + 2 * hi + (lm & 1)) ^ lr) << 4));
        sts128(sb + R_WO + ((wv * 32 + mt * 16 + hi * 8 + half * 4 + kq) * 32 + lane) * 16, make_uint4(r[0], r[1], r[2], r[3])); }
    } };
  ldwo(0, sb + 196608);
  asm volatile("cp.async.wait_all;" ::: "memory"); __syncthreads();
  TI(2);
  { const uint32_t st = sb + (2 - (warp >> 2)) * 65536;
    #pragma unroll
    for (int mt = 0; mt < 2; mt++)
      #pragma unroll
      for (int ks = 0; ks < 16; ks++) {
        const int k = 32 * (ks >> 1) + 8 * (lr >> 1) + (lr & 1) + 4 * (ks & 1) + 2 * (lm >> 1);
        ldsm4t(A[mt][ks], st + k * 256 + (((4 * (warp & 3) + 2 * mt + (lm & 1)) ^ lr) << 4));
      } }
  __syncthreads();
  TI(3);
  ldwo(1, sb + 131072);
  cvwo(0, sb + 196608);
  if (warp >= 8) {
    #pragma unroll
    for (int i = 0; i < 32; i++) sts128(sb + R_WR + (((warp - 8) * 32 + i) * 32 + lane) * 16, make_uint4(A[i & 1][i >> 1][0], A[i & 1][i >> 1][1], A[i & 1][i >> 1][2], A[i & 1][i >> 1][3]));
  }
  asm volatile("cp.async.wait_all;" ::: "memory"); __syncthreads();
  TI(4);
  cvwo(1, sb + 131072);
  if (warp < 4) {
    #pragma unroll
    for (int i = 0; i < 16; i++) sts128(sb + R_WQ + ((warp * 16 + i) * 32 + lane) * 16, make_uint4(A[1][i][0], A[1][i][1], A[1][i][2], A[1][i][3]));
  }
  __syncthreads();
  if (warp >= 8) {
    const uint32_t zero = blockIdx.y;
    #pragma unroll 1
    for (int s = 0; s < NSTEP; s++) {
      const int tid = otid(), lane = tid & 31, wv = (tid >> 5) - 8, g = lane >> 2, t = lane & 3;
      if (tid == 256) mbar_expect(mV, 4096);
      const uint32_t fo = (t ^ swz(g)) << 4;
      TR(1);
      bar_sync(4, 384);
      if (VD) { long long t0 = clock64(); while (clock64() - t0 < VD); }
      TR(2);
      float c[4][4];
      #pragma unroll
      for (int i = 0; i < 4; i++) { c[i][0] = c[i][1] = c[i][2] = c[i][3] = 0.f; }
      #pragma unroll
      for (int p = 0; p < 8; p++) {
        uint4 b = ldc(R_MEM + g * 16 + t * 160 + p * 640);
        mma16(c[0], A[0][2*p][0], A[0][2*p][1], A[0][2*p][2], A[0][2*p][3], b.x, b.y);
        mma16(c[1], A[1][2*p][0], A[1][2*p][1], A[1][2*p][2], A[1][2*p][3], b.x, b.y);
        mma16(c[2], A[0][2*p+1][0], A[0][2*p+1][1], A[0][2*p+1][2], A[0][2*p+1][3], b.z, b.w);
        mma16(c[3], A[1][2*p+1][0], A[1][2*p+1][1], A[1][2*p+1][2], A[1][2*p+1][3], b.z, b.w);
      }
      #pragma unroll
      for (int i = 0; i < 4; i++) { c[0][i] += c[2][i]; c[1][i] += c[3][i]; }
      const uint32_t rx = sb + R_RV + (wv * 64 + lane) * 16;
      { uint32_t ra = mapa(rx, peer), rm = mapa(mV, peer);
        st_async_v4(ra, c[0][0], c[0][1], c[0][2], c[0][3], rm);
        st_async_v4(ra + 512, c[1][0], c[1][1], c[1][2], c[1][3], rm); }
      TR(4);
      const bool more = s < NSTEP - 1;
      uint32_t wb = sb + (wv * 1024 + lane) * 16;
      #pragma unroll
      for (int i = 0; i < NW0; i++) { uint4 v = lds128(wb + R_WO + i * 512); A[i >> 4][i & 15][0] = v.x; A[i >> 4][i & 15][1] = v.y; A[i >> 4][i & 15][2] = v.z; A[i >> 4][i & 15][3] = v.w; }
      TR(3);
      mbar_wait(mV, s & 1);
      TR(5);
      { uint4 r0 = lds128(rx), r1 = lds128(rx + 512);
        stsm4t(sb + R_VT + (s & 1) * VT_SZ + (32 + (lane & 7)) * 272 + (4 * wv + (lane >> 3)) * 16,
          pack2(c[0][0] + __uint_as_float(r0.x), c[0][1] + __uint_as_float(r0.y)), pack2(c[0][2] + __uint_as_float(r0.z), c[0][3] + __uint_as_float(r0.w)),
          pack2(c[1][0] + __uint_as_float(r1.x), c[1][1] + __uint_as_float(r1.y)), pack2(c[1][2] + __uint_as_float(r1.z), c[1][3] + __uint_as_float(r1.w))); }
      if (more) {
      bar_arrive(3, 256);
      TR(8);
      #pragma unroll
      for (int i = NW0; i < 32; i++) { uint4 v = lds128(wb + R_WO + i * 512); A[i >> 4][i & 15][0] = v.x; A[i >> 4][i & 15][1] = v.y; A[i >> 4][i & 15][2] = v.z; A[i >> 4][i & 15][3] = v.w;
        if ((i % THR) == THR - 1) wb += v.x & zero; }
      TR(10);
      bar_sync(7, 256);
      TR(9);
      #pragma unroll
      for (int i = 0; i < 4; i++) { c[i][0] = c[i][1] = c[i][2] = c[i][3] = 0.f; }
      #pragma unroll
      for (int p = 0; p < 4; p++) {
        uint4 b = ldc(R_O + g * 256 + (p >> 1) * 128 + (fo ^ ((p & 1) << 6)));
        #pragma unroll
        for (int mt = 0; mt < 4; mt++) { const uint32_t* a = A[mt >> 1][(mt & 1) * 8 + 2 * p]; mma16(c[mt], a[0], a[1], a[2], a[3], b.x, b.y); }
        #pragma unroll
        for (int mt = 0; mt < 4; mt++) { const uint32_t* a = A[mt >> 1][(mt & 1) * 8 + 2 * p + 1]; mma16(c[mt], a[0], a[1], a[2], a[3], b.z, b.w); }
      }
      TR(6);
      float4* dst = &g_acc[s + 1][j][wv * 64 + lane];
      if (!(EXP & 1) || (h & 3) == wv) {
      REDV4(dst, c[0][0], c[0][1], c[0][2]); REDV4(dst + 256, c[0][3], c[1][0], c[1][1]); REDV4(dst + 512, c[1][2], c[1][3], 0.f);
      REDV4(dst + 32, c[2][0], c[2][1], c[2][2]); REDV4(dst + 288, c[2][3], c[3][0], c[3][1]); REDV4(dst + 544, c[3][2], c[3][3], 0.f); }
      bar_arrive(8, 352);
      TR(7);
      } else bar_sync(6, 256);
      { const int vt = tid - 256;
        if (j == 0) { const int r = vt >> 4, cc = vt & 15; uint4 v = lds128(sb + R_KT + (s & 1) * KT_SZ + (32 + r) * 256 + ((cc ^ swz(r)) << 4));
          __stcg((uint4*)(g_km + ((size_t)(s * 32 + h)) * 1024) + vt, v); }
        else { uint32_t vb = sb + R_VT + (s & 1) * VT_SZ + 32 * 272 + vt * 2; uint32_t e[8];
          #pragma unroll
          for (int k = 0; k < 8; k++) { unsigned short x; asm volatile("ld.shared.u16 %0, [%1];" : "=h"(x) : "r"(vb + k * 272) : "memory"); e[k] = x; }
          __stcg((uint4*)(g_vmT + ((size_t)(s * 32 + h)) * 1024) + vt, make_uint4(e[0] | (e[1] << 16), e[2] | (e[3] << 16), e[4] | (e[5] << 16), e[6] | (e[7] << 16))); }
        if (!more) { __syncwarp(); if (lane == 0) { __threadfence(); atomicAdd(&g_fl.prog[15][h], 1); } } }
      #pragma unroll
      for (int i = 0; i < 32; i++) { uint4 v = lds128(wb + R_WR + i * 512); A[i & 1][i >> 1][0] = v.x; A[i & 1][i >> 1][1] = v.y; A[i & 1][i >> 1][2] = v.z; A[i & 1][i >> 1][3] = v.w; }
    }
    return;
  }
  const float scale = 0.08838834764831845f, l2e = 1.4426950408889634f;
  auto prefetch = [&](int s) {
    const int vt = otid() - 160;
    if ((s & 3) == 0) { wait_flag(&g_fl.tile[s >> 2][h >> 1], 1); wait_flag(&g_fl.tile[s >> 2][16 + (h >> 1)], 1); }
    const int r = vt >> 4, c = vt & 15;
    const bf16* src = g_qkv + (size_t)(32 * s + r) * QW + h * 128 + c * 8;
    uint32_t kb = sb + R_KT + (s & 1) * KT_SZ + r * 256, vb = sb + R_VT + (s & 1) * VT_SZ + r * 272 + c * 16;
    #pragma unroll
    for (int i = 0; i < 8; i++) { cp16(kb + i * 1024 + ((c ^ swz(r + 4 * i)) << 4), src + (size_t)i * 4 * QW); cp16(vb + i * 1088, src + (size_t)i * 4 * QW + 4096); }
  };
  if (warp >= 4) {
  if (warp == 5 || warp == 6) prefetch(0);
  #pragma unroll 1
  for (int s = 0; s < NSTEP; s++) {
    TR(0); TR(1);
    const int tid = otid(), lane = tid & 31, warp = tid >> 5, g = lane >> 2, t = lane & 3;
    const uint32_t fo = (t ^ swz(g)) << 4;
    {
      if (tid == 0) mbar_expect(mQ, 4096);
      if (tid == 128) mbar_expect(mK, 4096);
      const float4* src = &g_acc[s][j][tid];
      uint4 v0, v1, v2; int it = 0;
      do { LD3(v0, v1, v2); } while (!OK3(v0, v1, v2) && ++it < SPIN_LIMIT);
      __syncwarp();
      stsm4t(sb + R_MEM + (lane & 7) * 16 + (4 * warp + (lane >> 3)) * 160,
        pack2(__uint_as_float(v0.x), __uint_as_float(v0.y)), pack2(__uint_as_float(v0.z), __uint_as_float(v1.x)),
        pack2(__uint_as_float(v1.y), __uint_as_float(v1.z)), pack2(__uint_as_float(v2.x), __uint_as_float(v2.y)));
    }
    TR(2);
    asm volatile("cp.async.wait_all;" ::: "memory");
    bar_sync(1, 256);
    { long long t0 = clock64(); while (clock64() - t0 < KD); }
    if (VP < 0) bar_arrive(4, 384);
    TR(3);
    float c[4][4];
    #pragma unroll
    for (int i = 0; i < 4; i++) { c[i][0] = c[i][1] = c[i][2] = c[i][3] = 0.f; }
    #pragma unroll
    for (int p = 0; p < 8; p++) {
      uint4 b = ldc(R_MEM + g * 16 + t * 160 + p * 640);
      mma16(c[0], A[0][2*p][0], A[0][2*p][1], A[0][2*p][2], A[0][2*p][3], b.x, b.y);
      mma16(c[1], A[1][2*p][0], A[1][2*p][1], A[1][2*p][2], A[1][2*p][3], b.x, b.y);
      mma16(c[2], A[0][2*p+1][0], A[0][2*p+1][1], A[0][2*p+1][2], A[0][2*p+1][3], b.z, b.w);
      mma16(c[3], A[1][2*p+1][0], A[1][2*p+1][1], A[1][2*p+1][2], A[1][2*p+1][3], b.z, b.w);
      if (p == VP) asm volatile("bar.arrive 4, 384;");
    }
    #pragma unroll
    for (int i = 0; i < 4; i++) { c[0][i] += c[2][i]; c[1][i] += c[3][i]; }
    const uint32_t rx = sb + R_RQK + (warp * 64 + lane) * 16;
    { uint32_t ra = mapa(rx, peer), rm = mapa(mK, peer);
      st_async_v4(ra, c[0][0], c[0][1], c[0][2], c[0][3], rm);
      st_async_v4(ra + 512, c[1][0], c[1][1], c[1][2], c[1][3], rm); }
    if (VP > 7) bar_arrive(4, 384);
    TR(4);
    const uint32_t so = (lane & 7) * 256 + (((4 * (warp & 3) + (lane >> 3)) ^ swz(lane & 7)) << 4);
    mbar_wait(mK, s & 1);
    TR(5);
    uint32_t m0, m1, m2, m3;
    { uint4 r0 = lds128(rx), r1 = lds128(rx + 512);
      m0 = pack2(c[0][0] + __uint_as_float(r0.x), c[0][1] + __uint_as_float(r0.y)); m1 = pack2(c[0][2] + __uint_as_float(r0.z), c[0][3] + __uint_as_float(r0.w));
      m2 = pack2(c[1][0] + __uint_as_float(r1.x), c[1][1] + __uint_as_float(r1.y)); m3 = pack2(c[1][2] + __uint_as_float(r1.z), c[1][3] + __uint_as_float(r1.w)); }
    stsm4t(sb + R_KT + (s & 1) * KT_SZ + 32 * 256 + so, m0, m1, m2, m3);
    if (s == NSTEP - 1) { bar_arrive(6, 256); break; }
    asm("movmatrix.sync.aligned.m8n8.trans.b16 %0, %0;" : "+r"(m0)); asm("movmatrix.sync.aligned.m8n8.trans.b16 %0, %0;" : "+r"(m1));
    asm("movmatrix.sync.aligned.m8n8.trans.b16 %0, %0;" : "+r"(m2)); asm("movmatrix.sync.aligned.m8n8.trans.b16 %0, %0;" : "+r"(m3));
    TR(8);
    bar_sync(9, 256);
    TR(9);
    { uint32_t qa[4]; ldsm4(qa, sb + R_Q + so);
      #pragma unroll
      for (int i = 0; i < 2; i++) { c[i][0] = c[i][1] = c[i][2] = c[i][3] = 0.f; }
      mma16(c[0], qa[0], 0, qa[1], 0, m0, m1); mma16(c[1], qa[2], 0, qa[3], 0, m2, m3);
      asm volatile("st.shared.v2.f32 [%0], {%1,%2};" ::"r"(sb + R_SM + (warp - 4) * 256 + lane * 8), "f"(c[0][0] + c[1][0]), "f"(c[0][1] + c[1][1]) : "memory"); }
    bar_arrive(2, 256);
    TR(10);
    if ((warp == 5 || warp == 6) && s < NSTEP - 2) prefetch(s + 1);
    TR(7);
    if (warp == 7) { if ((s & 3) == 1 && s > 1 && lane == 0) asm volatile("red.release.gpu.global.add.s32 [%0], 4;" ::"l"(&g_fl.prog[(s - 2) >> 2][h]) : "memory"); __syncwarp();
      long long t0 = clock64(); while (clock64() - t0 < W7D); }
    else bar_sync(8, 352);
    { long long t0 = clock64(); while (clock64() - t0 < PDELAY); }
  }
  return;
  }
  #pragma unroll 1
  for (int s = 0; s < NSTEP; s++) {
    TR(0); TR(1);
    const int tid = otid(), lane = tid & 31, warp = tid >> 5, g = lane >> 2, t = lane & 3;
    const uint32_t fo = (t ^ swz(g)) << 4;
    {
      if (tid == 0) mbar_expect(mQ, 4096);
      if (tid == 128) mbar_expect(mK, 4096);
      const float4* src = &g_acc[s][j][tid];
      uint4 v0, v1, v2; int it = 0;
      do { LD3(v0, v1, v2); } while (!OK3(v0, v1, v2) && ++it < SPIN_LIMIT);
      __syncwarp();
      stsm4t(sb + R_MEM + (lane & 7) * 16 + (4 * warp + (lane >> 3)) * 160,
        pack2(__uint_as_float(v0.x), __uint_as_float(v0.y)), pack2(__uint_as_float(v0.z), __uint_as_float(v1.x)),
        pack2(__uint_as_float(v1.y), __uint_as_float(v1.z)), pack2(__uint_as_float(v2.x), __uint_as_float(v2.y)));
    }
    TR(2);

    bar_sync(1, 256);
    bar_arrive(4, 384);
    TR(3);
    float c[4][4];
    #pragma unroll
    for (int i = 0; i < 4; i++) { c[i][0] = c[i][1] = c[i][2] = c[i][3] = 0.f; }
    #pragma unroll
    for (int p = 0; p < 8; p++) {
      uint4 b = ldc(R_MEM + g * 16 + t * 160 + p * 640);
      mma16(c[0], A[0][2*p][0], A[0][2*p][1], A[0][2*p][2], A[0][2*p][3], b.x, b.y);
      mma16(c[1], A[1][2*p][0], A[1][2*p][1], A[1][2*p][2], A[1][2*p][3], b.x, b.y);
      mma16(c[2], A[0][2*p+1][0], A[0][2*p+1][1], A[0][2*p+1][2], A[0][2*p+1][3], b.z, b.w);
      mma16(c[3], A[1][2*p+1][0], A[1][2*p+1][1], A[1][2*p+1][2], A[1][2*p+1][3], b.z, b.w);
    }
    #pragma unroll
    for (int i = 0; i < 4; i++) { c[0][i] += c[2][i]; c[1][i] += c[3][i]; }
    const uint32_t rx = sb + R_RQK + (warp * 64 + lane) * 16;
    { uint32_t ra = mapa(rx, peer), rm = mapa(mQ, peer);
      st_async_v4(ra, c[0][0], c[0][1], c[0][2], c[0][3], rm);
      st_async_v4(ra + 512, c[1][0], c[1][1], c[1][2], c[1][3], rm); }
    TR(4);
    const uint32_t so = (lane & 7) * 256 + (((4 * (warp & 3) + (lane >> 3)) ^ swz(lane & 7)) << 4);
    if (s == NSTEP - 1) { mbar_wait(mQ, s & 1); break; }
    uint4 kf[4]; uint32_t vf[4][4];
    const uint32_t vb = sb + R_VT + (s & 1) * VT_SZ + (lane & 15) * 272 + (32 * warp + 8 * (lane >> 4)) * 2;
    #pragma unroll
    for (int p = 0; p < 4; p++) kf[p] = lds128(sb + R_KT + (s & 1) * KT_SZ + warp * 2048 + g * 256 + (p >> 1) * 128 + (fo ^ ((p & 1) << 6)));
    #pragma unroll
    for (int i = 0; i < 4; i++) ldsm4t(vf[i], vb + (i >> 1) * 16 * 272 + (i & 1) * 32);
    mbar_wait(mQ, s & 1);
    TR(5);
    uint32_t m0, m1, m2, m3;
    { uint4 r0 = lds128(rx), r1 = lds128(rx + 512);
      m0 = pack2(c[0][0] + __uint_as_float(r0.x), c[0][1] + __uint_as_float(r0.y)); m1 = pack2(c[0][2] + __uint_as_float(r0.z), c[0][3] + __uint_as_float(r0.w));
      m2 = pack2(c[1][0] + __uint_as_float(r1.x), c[1][1] + __uint_as_float(r1.y)); m3 = pack2(c[1][2] + __uint_as_float(r1.z), c[1][3] + __uint_as_float(r1.w)); }
    stsm4t(sb + R_Q + so, m0, m1, m2, m3);
    TR(8);
    bar_arrive(9, 256); bar_sync(5, 128);
    TR(9);
    {
      uint4 qa[4];
      #pragma unroll
      for (int p = 0; p < 4; p++) qa[p] = lds128(sb + R_Q + g * 256 + (p >> 1) * 128 + (fo ^ ((p & 1) << 6)));
      #pragma unroll
      for (int i = 0; i < 4; i++) { c[i][0] = c[i][1] = c[i][2] = c[i][3] = 0.f; }
      #pragma unroll
      for (int p = 0; p < 4; p++) { mma16(c[(p & 1) * 2], qa[p].x, 0, qa[p].y, 0, kf[p].x, kf[p].y); mma16(c[(p & 1) * 2 + 1], qa[p].z, 0, qa[p].w, 0, kf[p].z, kf[p].w); }
      float a = rbf(rbf((c[0][0] + c[1][0]) + (c[2][0] + c[3][0])) * scale) * l2e, b = rbf(rbf((c[0][1] + c[1][1]) + (c[2][1] + c[3][1])) * scale) * l2e;
      asm volatile("st.shared.v2.f32 [%0], {%1,%2};" ::"r"(sb + R_S + g * 160 + (8 * warp + 2 * t) * 4), "f"(a), "f"(b) : "memory");
    }
    TR(10);
    bar_sync(10, 128);
    float sv[8], pm[8];
    #pragma unroll
    for (int i = 0; i < 4; i++) asm volatile("ld.shared.v2.f32 {%0,%1}, [%2];" : "=f"(sv[2*i]), "=f"(sv[2*i+1]) : "r"(sb + R_S + g * 160 + (8 * i + 2 * t) * 4) : "memory");
    float mx = fmaxf(fmaxf(fmaxf(sv[0], sv[1]), fmaxf(sv[2], sv[3])), fmaxf(fmaxf(sv[4], sv[5]), fmaxf(sv[6], sv[7])));
    mx = fmaxf(mx, __shfl_xor_sync(~0u, mx, 1)); mx = fmaxf(mx, __shfl_xor_sync(~0u, mx, 2));
    uint32_t P[5];
    #pragma unroll
    for (int i = 0; i < 4; i++) P[i] = pack2(ex2(sv[2*i] - mx), ex2(sv[2*i+1] - mx));
    #pragma unroll
    for (int i = 0; i < 4; i++) { c[i][0] = c[i][1] = c[i][2] = c[i][3] = 0.f; }
    #pragma unroll
    for (int kk = 0; kk < 2; kk++) {
      mma16(c[0], P[2*kk], 0, P[2*kk+1], 0, vf[2*kk][0], vf[2*kk][1]); mma16(c[1], P[2*kk], 0, P[2*kk+1], 0, vf[2*kk][2], vf[2*kk][3]);
      mma16(c[2], P[2*kk], 0, P[2*kk+1], 0, vf[2*kk+1][0], vf[2*kk+1][1]); mma16(c[3], P[2*kk], 0, P[2*kk+1], 0, vf[2*kk+1][2], vf[2*kk+1][3]);
    }
    float sum = 0.f;
    #pragma unroll
    for (int i = 0; i < 4; i++) sum += __uint_as_float(P[i] << 16) + __uint_as_float(P[i] & 0xffff0000u);
    TR(11);
    bar_sync(2, 256);
    #pragma unroll
    for (int i = 0; i < 4; i++) asm volatile("ld.shared.v2.f32 {%0,%1}, [%2];" : "=f"(pm[2*i]), "=f"(pm[2*i+1]) : "r"(sb + R_SM + i * 256 + lane * 8) : "memory");
    const float s8 = rbf(rbf((pm[0] + pm[2]) + (pm[4] + pm[6])) * scale) * l2e, s9 = rbf(rbf((pm[1] + pm[3]) + (pm[5] + pm[7])) * scale) * l2e;
    float mg = fmaxf(mx, fmaxf(s8, s9));
    mg = fmaxf(mg, __shfl_xor_sync(~0u, mg, 1)); mg = fmaxf(mg, __shfl_xor_sync(~0u, mg, 2));
    const float fs = ex2(mx - mg);
    P[4] = pack2(ex2(s8 - mg), ex2(s9 - mg));
    #pragma unroll
    for (int i = 0; i < 4; i++) { c[i][0] *= fs; c[i][1] *= fs; }
    sum = fmaf(sum, fs, __uint_as_float(P[4] << 16) + __uint_as_float(P[4] & 0xffff0000u));
    sum += __shfl_xor_sync(~0u, sum, 1); sum += __shfl_xor_sync(~0u, sum, 2);
    float inv; asm("rcp.approx.ftz.f32 %0, %1;" : "=f"(inv) : "f"(sum));
    TR(6);
    bar_sync(3, 256);
    { uint32_t r[4]; ldsm4t(r, sb + R_VT + (s & 1) * VT_SZ + (32 + (lane & 7)) * 272 + (4 * warp + (lane >> 3)) * 16);
      #pragma unroll
      for (int i = 0; i < 4; i++) mma8(c[i], P[4], 0, r[i]); }
    asm volatile("stmatrix.sync.aligned.m8n8.x4.shared.b16 [%0], {%1,%2,%3,%4};" ::"r"(sb + R_O + so),
      "r"(pack2(c[0][0] * inv, c[0][1] * inv)), "r"(pack2(c[1][0] * inv, c[1][1] * inv)), "r"(pack2(c[2][0] * inv, c[2][1] * inv)), "r"(pack2(c[3][0] * inv, c[3][1] * inv)) : "memory");
    bar_arrive(7, 256);
    TR(7);
    bar_sync(8, 352);
    long long t0 = clock64();
    #pragma unroll
    for (int i = 0; i < 16; i++) { uint4 v = lds128(sb + R_WQ + ((warp * 16 + i) * 32 + lane) * 16); A[1][i][0] = v.x; A[1][i][1] = v.y; A[1][i][2] = v.z; A[1][i][3] = v.w; }
    while (clock64() - t0 < PDELAY);
  }
}

constexpr int I_M1 = 512, I_Q = 624, I_M2 = 688, I_Q2 = 720, I_G = 912, I_S = I_G + NFULL * 34, I_END = I_S + (16 - NFULL) * 56;
constexpr int B_STG = 4 * 49152, B_BAR = B_STG + 8 * 2304;
struct Item { int type, rb, nt, ks; };
__device__ __forceinline__ Item decode(int it) {
  Item r; r.ks = 0;
  if (it < I_M1) { r.type = 0; r.rb = it >> 5; r.nt = it & 31; }
  else if (it < I_Q) { int i = it - I_M1; r.type = 1; r.rb = i / 7; r.nt = i % 7; }
  else if (it < I_M2) { int i = it - I_Q; r.type = 0; r.rb = i >> 4; r.nt = 32 + (i & 15); }
  else if (it < I_Q2) { int i = it - I_M2; r.type = 2; r.rb = i >> 1; r.nt = i & 1; }
  else if (it < I_G) { int i = it - I_Q2 + 64; r.type = 0; r.rb = i >> 4; r.nt = 32 + (i & 15); }
  else if (it < I_S) { int i = it - I_G, q = i % 34; r.rb = i / 34; if (q < 32) { r.type = 3; r.nt = q; } else { r.type = 4; r.nt = q - 32; } }
  else { int i = it - I_S, q = i % 56; r.rb = NFULL + i / 56;
    if (q < 32) { r.type = 3; r.nt = q; }
    else if (q < 48) { r.type = 6; r.nt = (q - 32) >> 3; r.ks = (q - 32) & 7; }
    else { r.type = 5; r.nt = q - 48; } }
  return r;
}
__device__ __forceinline__ float gelu_t(float x) { float u = 0.7978845608028654f * (x + 0.044715f * x * x * x); float th; asm("tanh.approx.f32 %0, %1;" : "=f"(th) : "f"(u)); float hx = 0.5f * x; return fmaf(hx, th, hx); }

__device__ __forceinline__ void bulk(uint32_t sb, const Maps& mp, const bf16* __restrict__ x, const bf16* __restrict__ b1, const bf16* __restrict__ b2, bf16* __restrict__ out) {
  const int tid = threadIdx.x, warp = tid >> 5, lane = tid & 31, g = lane >> 2, t = lane & 3;
  const int bid = blockIdx.x - NREC;
  const uint32_t full = sb + B_BAR, empty = sb + B_BAR + 32, ifull = sb + B_BAR + 64, iempty = sb + B_BAR + 80;
  volatile int* ring = (volatile int*)(__cvta_shared_to_generic(sb + B_BAR + 96));
  if (warp >= 8) {
    asm volatile("setmaxnreg.dec.sync.aligned.u32 40;");
    if (tid == 256) {
      uint32_t st = 0, ph = 0;
      for (int n = 0;; n++) {
        int it = n == 0 ? bid : NBULK + atomicAdd(&g_fl.next, 1);
        Item I = decode(it);
        if (it < I_END) {
          if (I.type == 5) { wait_flag(&g_fl.s[I.rb][0], 16); wait_flag(&g_fl.z[I.rb][0], 1); wait_flag(&g_fl.z[I.rb][1], 1); }
          else if (I.type == 3) { wait_flag(&g_fl.tile[I.rb][I.nt >> 1], 1); wait_flag(&g_fl.tile[I.rb][16 + (I.nt >> 1)], 1); wait_flag(&g_fl.tile[I.rb][32 + (I.nt >> 1)], 1); fence_async();
            for (int m = 0; m < 3; m++) {
              mbar_wait(empty + st * 8, ph ^ 1);
              mbar_expect(full + st * 8, 32768);
              int col = (m == 0 ? 8192 : (m == 1 ? 0 : 4096)) + I.nt * 128;
              tma2d(sb + st * 49152, &mp.qkv, col, I.rb * 128, full + st * 8);
              tma2d(sb + st * 49152 + 16384, &mp.qkv, col + 64, I.rb * 128, full + st * 8);
              if (++st == 4) { st = 0; ph ^= 1; }
            }
            wait_flag(&g_fl.prog[I.rb][I.nt], 8); }
          else if (I.type == 2) { wait_flag(&g_fl.hid[I.rb], 7); fence_async(); }
          else if (I.type == 4) { wait_flag(&g_fl.z[I.rb][I.nt], 1); wait_flag(&g_fl.o[I.rb][0], 4); fence_async(); }
          else if (I.type == 6) { wait_flag(&g_fl.o[I.rb][I.ks], 4); fence_async(); }
        }
        mbar_wait(iempty + (n & 1) * 8, ((n >> 1) & 1) ^ 1);
        ring[n & 1] = it; mbar_arrive(ifull + (n & 1) * 8);
        if (it >= I_END) break;
        if (I.type == 5 || I.type == 3) continue;
        const CUtensorMap *ma, *mb; int nkb = 8, kb0 = 0, n0;
        if (I.type == 0) { ma = &mp.xn; mb = I.nt < 16 ? &mp.wk : (I.nt < 32 ? &mp.wv : &mp.wq); n0 = (I.nt & 15) * 256; }
        else if (I.type == 1) { ma = &mp.y; mb = &mp.w1; n0 = I.nt * 256; }
        else if (I.type == 2) { ma = &mp.hid; mb = &mp.w2; n0 = I.nt * 256; nkb = 28; }
        else { ma = &mp.o; mb = &mp.wo; n0 = I.nt * 256; kb0 = I.ks * 8; if (I.type == 4) nkb = 64; }
        for (int kb = kb0; kb < kb0 + nkb; kb++) {
          if (I.type == 4 && kb && !(kb & 7)) { wait_flag(&g_fl.o[I.rb][kb >> 3], 4); fence_async(); }
          mbar_wait(empty + st * 8, ph ^ 1);
          mbar_expect(full + st * 8, 49152);
          uint32_t sa = sb + st * 49152;
          tma2d(sa, ma, kb * 64, I.rb * 128, full + st * 8);
          #pragma unroll
          for (int q = 0; q < 4; q++) tma2d(sa + 16384 + q * 8192, mb, n0 + q * 64, kb * 64, full + st * 8);
          if (++st == 4) { st = 0; ph ^= 1; }
        }
      }
    } else if (warp == 9) {
      for (int n = 0;; n++) {
        mbar_wait(ifull + (n & 1) * 8, (n >> 1) & 1);
        int it = ring[n & 1];
        if (it >= I_END) break;
        Item I = decode(it);
        bar_sync(6 + (n & 1), 288);
        if (lane == 0) {
          if (I.type != 5 && I.type != 4) {
            fence_async(); __threadfence();
            int* f = I.type == 0 ? &g_fl.tile[I.rb][I.nt] : I.type == 1 ? &g_fl.hid[I.rb] : I.type == 2 ? &g_fl.z[I.rb][I.nt] : I.type == 3 ? &g_fl.o[I.rb][I.nt >> 2] : &g_fl.s[I.rb][0];
            atomicAdd(f, 1);
          }
          mbar_arrive(iempty + (n & 1) * 8);
        }
      }
    }
    return;
  }
  asm volatile("setmaxnreg.inc.sync.aligned.u32 232;");
  const int wg = warp >> 2;
  const uint32_t stg = sb + B_STG + warp * 2304;
  const int lm = lane >> 3, lr = lane & 7;
  uint32_t st = 0, ph = 0;
  float d[128];
  #pragma unroll 1
  for (int n = 0;; n++) {
    mbar_wait(ifull + (n & 1) * 8, (n >> 1) & 1);
    const int it = ring[n & 1];
    __syncwarp(); if (lane == 0) mbar_arrive(iempty + (n & 1) * 8);
    if (it >= I_END) break;
    Item I = decode(it);
    const int row0 = I.rb * 128 + warp * 16;
    TB(0);
    if (I.type == 5) {
      #pragma unroll
      for (int i = 0; i < 4; i++) {
        size_t off = (size_t)(I.rb * 128 + I.nt * 16 + warp * 2 + (i >> 1)) * DM + (i & 1) * 256 + lane * 8;
        const float* sp = g_sp + off + (size_t)(I.rb - NFULL) * 7 * 128 * DM - (size_t)NFULL * 128 * DM;
        float4 s0 = __ldcg((const float4*)sp), s1 = __ldcg((const float4*)(sp + 4));
        #pragma unroll
        for (int k = 1; k < 8; k++) { float4 a = __ldcg((const float4*)(sp + k * 128 * DM)), b = __ldcg((const float4*)(sp + k * 128 * DM + 4));
          s0.x += a.x; s0.y += a.y; s0.z += a.z; s0.w += a.w; s1.x += b.x; s1.y += b.y; s1.z += b.z; s1.w += b.w; }
        uint4 xv = *(const uint4*)(x + off), gv = __ldcg((const uint4*)(g_g + off));
        float sa[8] = {s0.x, s0.y, s0.z, s0.w, s1.x, s1.y, s1.z, s1.w}, r[8];
        #pragma unroll
        for (int e = 0; e < 8; e++) r[e] = __bfloat162float(((const bf16*)&xv)[e]) + rbf(rbf(sa[e]) * __bfloat162float(((const bf16*)&gv)[e]));
        *(uint4*)(out + off) = make_uint4(pack2(r[0], r[1]), pack2(r[2], r[3]), pack2(r[4], r[5]), pack2(r[6], r[7]));
      }
      bar_arrive(6 + (n & 1), 288);
      continue;
    }
    if (I.type == 3) {
      const int h = I.nt, seg = warp >> 1, half = warp & 1, step = I.rb * 4 + seg;
      uint32_t kmr[16], vmr[16];
      { const uint32_t* km = (const uint32_t*)(g_km + ((size_t)(step * 32 + h)) * 1024) + g * 64 + t;
        const uint32_t* vm = (const uint32_t*)(g_vmT + ((size_t)(step * 32 + h)) * 1024) + g * 4 + t;
        #pragma unroll
        for (int i = 0; i < 16; i++) { kmr[i] = __ldcg(km + i * 4); vmr[i] = __ldcg(vm + i * 32); } }
      uint32_t sQ = sb + st * 49152; mbar_wait(full + st * 8, ph); uint32_t eQ = empty + st * 8; if (++st == 4) { st = 0; ph ^= 1; }
      uint32_t sK = sb + st * 49152; mbar_wait(full + st * 8, ph); uint32_t eK = empty + st * 8; if (++st == 4) { st = 0; ph ^= 1; }
      float sc[5][4];
      #pragma unroll
      for (int i = 0; i < 5; i++) { sc[i][0] = sc[i][1] = sc[i][2] = sc[i][3] = 0.f; }
      #pragma unroll
      for (int ks = 0; ks < 8; ks++) {
        uint32_t a[4]; { int r = warp * 16 + 8 * (lm & 1) + lr, c8 = 2 * ks + (lm >> 1); ldsm4(a, sQ + (c8 >> 3) * 16384 + r * 128 + (((c8 & 7) ^ (r & 7)) << 4)); }
        #pragma unroll
        for (int np = 0; np < 2; np++) {
          if (np == 1 && half == 0) continue;
          uint32_t b[4]; int r = seg * 32 + 16 * np + 8 * (lm >> 1) + lr, c8 = 2 * ks + (lm & 1);
          ldsm4(b, sK + (c8 >> 3) * 16384 + r * 128 + (((c8 & 7) ^ (r & 7)) << 4));
          mma16(sc[2*np], a[0], a[1], a[2], a[3], b[0], b[1]); mma16(sc[2*np+1], a[0], a[1], a[2], a[3], b[2], b[3]);
        }
        mma16(sc[4], a[0], a[1], a[2], a[3], kmr[2*ks], kmr[2*ks+1]);
      }
      __syncwarp(); if (lane == 0) { mbar_arrive(eQ); mbar_arrive(eK); }
      const float scale = 0.08838834764831845f;
      uint32_t P[5][2];
      #pragma unroll
      for (int rr = 0; rr < 2; rr++) {
        const int qi = 16 * half + g + 8 * rr;
        float mx = -3.0e38f;
        #pragma unroll
        for (int i = 0; i < 5; i++)
          #pragma unroll
          for (int e = 0; e < 2; e++) { float v = rbf(rbf(sc[i][2*rr+e]) * scale); if (i < 4 && 8 * i + 2 * t + e > qi) v = -1.0e9f; sc[i][2*rr+e] = v; mx = fmaxf(mx, v); }
        mx = fmaxf(mx, __shfl_xor_sync(~0u, mx, 1)); mx = fmaxf(mx, __shfl_xor_sync(~0u, mx, 2));
        float sum = 0;
        #pragma unroll
        for (int i = 0; i < 5; i++)
          #pragma unroll
          for (int e = 0; e < 2; e++) { float v = __expf(sc[i][2*rr+e] - mx); sc[i][2*rr+e] = v; sum += v; }
        sum += __shfl_xor_sync(~0u, sum, 1); sum += __shfl_xor_sync(~0u, sum, 2);
        float inv = __fdividef(1.f, sum);
        #pragma unroll
        for (int i = 0; i < 5; i++) P[i][rr] = pack2(sc[i][2*rr] * inv, sc[i][2*rr+1] * inv);
      }
      uint32_t sV = sb + st * 49152; mbar_wait(full + st * 8, ph); uint32_t eV = empty + st * 8; if (++st == 4) { st = 0; ph ^= 1; }
      #pragma unroll
      for (int i = 0; i < 64; i++) d[i] = 0.f;
      #pragma unroll
      for (int n2 = 0; n2 < 8; n2++) {
        #pragma unroll
        for (int kk = 0; kk < 2; kk++) {
          if (kk == 1 && half == 0) continue;
          uint32_t b[4]; int r = seg * 32 + 16 * kk + 8 * (lm & 1) + lr, c8 = 2 * n2 + (lm >> 1);
          ldsm4t(b, sV + (c8 >> 3) * 16384 + r * 128 + (((c8 & 7) ^ (r & 7)) << 4));
          mma16(d + 8 * n2, P[2*kk][0], P[2*kk][1], P[2*kk+1][0], P[2*kk+1][1], b[0], b[1]);
          mma16(d + 8 * n2 + 4, P[2*kk][0], P[2*kk][1], P[2*kk+1][0], P[2*kk+1][1], b[2], b[3]);
        }
        mma8(d + 8 * n2, P[4][0], P[4][1], vmr[2*n2]); mma8(d + 8 * n2 + 4, P[4][0], P[4][1], vmr[2*n2+1]);
      }
      __syncwarp(); if (lane == 0) mbar_arrive(eV);
      #pragma unroll
      for (int ch = 0; ch < 2; ch++) {
        #pragma unroll
        for (int i = 0; i < 8; i++) { const float* a = d + ch * 32 + i * 4;
          sts32(stg + g * 144 + i * 16 + t * 4, pack2(a[0], a[1])); sts32(stg + (g + 8) * 144 + i * 16 + t * 4, pack2(a[2], a[3])); }
        __syncwarp();
        #pragma unroll
        for (int i = 0; i < 4; i++) { int r = i * 4 + lm; uint4 v = lds128(stg + r * 144 + lr * 16);
          *(uint4*)(g_o + (size_t)(row0 + r) * 4096 + h * 128 + ch * 64 + lr * 8) = v; }
        __syncwarp();
      }
      bar_arrive(6 + (n & 1), 288);
      continue;
    }
    const int nkb = I.type == 2 ? 28 : I.type == 4 ? 64 : 8;
    uint32_t prev = 0;
    for (int kb = 0; kb < nkb; kb++) {
      mbar_wait(full + st * 8, ph);
      uint32_t sa = sb + st * 49152;
      asm volatile("wgmma.fence.sync.aligned;" ::: "memory");
      #pragma unroll
      for (int k = 0; k < 4; k++)
        wgmma256(d, mkdesc(sa + wg * 8192 + k * 32, 16, 1024), mkdesc(sa + 16384 + k * 2048, 8192, 1024), (kb | k) != 0);
      asm volatile("wgmma.commit_group.sync.aligned;" ::: "memory");
      if (kb > 0) { asm volatile("wgmma.wait_group.sync.aligned 1;" ::: "memory"); if (lane == 0) mbar_arrive(prev); }
      prev = empty + st * 8;
      if (++st == 4) { st = 0; ph ^= 1; }
    }
    asm volatile("wgmma.wait_group.sync.aligned 0;" ::: "memory");
    if (lane == 0) mbar_arrive(prev);
    TB(1);
    if (I.type != 6) {
      bf16* dst; int ld;
      if (I.type == 0) { dst = g_qkv + (size_t)row0 * QW + I.nt * 256; ld = QW; } else if (I.type == 1) { dst = g_hid + (size_t)row0 * FF + I.nt * 256; ld = FF; }
      else { dst = (I.type == 2 ? g_g : out) + (size_t)row0 * DM + I.nt * 256; ld = DM; }
      #pragma unroll
      for (int ch = 0; ch < 4; ch++) {
        #pragma unroll
        for (int i = 0; i < 8; i++) { float* a = d + ch * 32 + i * 4;
          if (I.type == 1) { float2 bb = __bfloat1622float2(*(const __nv_bfloat162*)(b1 + I.nt * 256 + ch * 64 + i * 8 + 2 * t));
            a[0] = gelu_t(rbf(rbf(a[0]) + bb.x)); a[1] = gelu_t(rbf(rbf(a[1]) + bb.y)); a[2] = gelu_t(rbf(rbf(a[2]) + bb.x)); a[3] = gelu_t(rbf(rbf(a[3]) + bb.y)); }
          if (I.type == 2) { float2 bb = __bfloat1622float2(*(const __nv_bfloat162*)(b2 + I.nt * 256 + ch * 64 + i * 8 + 2 * t));
            #pragma unroll
            for (int e = 0; e < 4; e++) { float u = rbf(rbf(a[e]) + ((e & 1) ? bb.y : bb.x)); a[e] = __fdividef(u, 1.f + __expf(-u)); } }
          sts32(stg + g * 144 + i * 16 + t * 4, pack2(a[0], a[1])); sts32(stg + (g + 8) * 144 + i * 16 + t * 4, pack2(a[2], a[3])); }
        __syncwarp();
        #pragma unroll
        for (int i = 0; i < 4; i++) { int r = i * 4 + lm; uint4 v = lds128(stg + r * 144 + lr * 16);
          if (I.type == 4) { const size_t off = (size_t)(row0 + r) * DM + I.nt * 256 + ch * 64 + lr * 8;
            uint4 xv = *(const uint4*)(x + off), gv = __ldcg((const uint4*)(g_g + off)); float q[8];
            #pragma unroll
            for (int e = 0; e < 8; e++) q[e] = __bfloat162float(((const bf16*)&xv)[e]) + rbf(__bfloat162float(((const bf16*)&v)[e]) * __bfloat162float(((const bf16*)&gv)[e]));
            v = make_uint4(pack2(q[0], q[1]), pack2(q[2], q[3]), pack2(q[4], q[5]), pack2(q[6], q[7])); }
          *(uint4*)(dst + (size_t)r * ld + ch * 64 + lr * 8) = v; }
        __syncwarp();
      }
    } else {
      float* dst = g_sp + ((size_t)((I.rb - NFULL) * 8 + I.ks) * 128 + warp * 16 + g) * DM + I.nt * 256 + 2 * t;
      #pragma unroll
      for (int i = 0; i < 32; i++) {
        asm volatile("st.global.cg.v2.f32 [%0], {%1,%2};" ::"l"(dst + i * 8), "f"(d[4*i]), "f"(d[4*i+1]) : "memory");
        asm volatile("st.global.cg.v2.f32 [%0], {%1,%2};" ::"l"(dst + 8 * DM + i * 8), "f"(d[4*i+2]), "f"(d[4*i+3]) : "memory");
      }
    }
    bar_arrive(6 + (n & 1), 288);
  }
}

__global__ void __cluster_dims__(2, 1, 1) __launch_bounds__(384, 1)
main_kernel(const __grid_constant__ Maps mp, const bf16* x, const bf16* Wq, const bf16* Wk, const bf16* Wv, const bf16* Wo, const bf16* b1, const bf16* b2, bf16* out) {
  const uint32_t sb = smem_u32(smem_raw);
  if (sb & 1023) __trap();
  if (threadIdx.x == 0) {
    if (blockIdx.x < NREC) { mbar_init(sb + R_BAR, 1); mbar_init(sb + R_BAR + 8, 1); mbar_init(sb + R_BAR + 16, 1); }
    else { for (int i = 0; i < 4; i++) { mbar_init(sb + B_BAR + i * 8, 1); mbar_init(sb + B_BAR + 32 + i * 8, 8); }
      for (int i = 0; i < 2; i++) { mbar_init(sb + B_BAR + 64 + i * 8, 1); mbar_init(sb + B_BAR + 80 + i * 8, 9); } }
    asm volatile("fence.mbarrier_init.release.cluster;" ::: "memory");
  }
  asm volatile("barrier.cluster.arrive.release.aligned; barrier.cluster.wait.acquire.aligned;" ::: "memory");
  if (blockIdx.x < NREC) recurrence(sb, Wq, Wk, Wv, Wo);
  else bulk(sb, mp, x, b1, b2, out);
}

typedef CUresult (*EncFn)(CUtensorMap*, CUtensorMapDataType, cuuint32_t, void*, const cuuint64_t*, const cuuint64_t*, const cuuint32_t*, const cuuint32_t*, CUtensorMapInterleave, CUtensorMapSwizzle, CUtensorMapL2promotion, CUtensorMapFloatOOBfill);
static void mk(EncFn f, CUtensorMap* m, const void* p, uint64_t rows, uint64_t cols, uint32_t boxr) {
  cuuint64_t dims[2] = {cols, rows}, str[1] = {cols * 2}; cuuint32_t box[2] = {64, boxr}, es[2] = {1, 1};
  f(m, CU_TENSOR_MAP_DATA_TYPE_BFLOAT16, 2, (void*)p, dims, str, box, es, CU_TENSOR_MAP_INTERLEAVE_NONE, CU_TENSOR_MAP_SWIZZLE_128B, CU_TENSOR_MAP_L2_PROMOTION_L2_256B, CU_TENSOR_MAP_FLOAT_OOB_FILL_NONE);
}
extern "C" void kernel_launch(void* const* d_in, const int* in_sizes, int n_in, void* d_out, int out_size) {
  const bf16 *x = (const bf16*)d_in[0], *mem0 = (const bf16*)d_in[1], *Wq = (const bf16*)d_in[2], *Wk = (const bf16*)d_in[3], *Wv = (const bf16*)d_in[4], *Wo = (const bf16*)d_in[5];
  const bf16 *w1 = (const bf16*)d_in[8], *b1 = (const bf16*)d_in[9], *w2 = (const bf16*)d_in[10], *b2 = (const bf16*)d_in[11];
  void* fn = nullptr; cudaDriverEntryPointQueryResult qr;
  cudaGetDriverEntryPoint("cuTensorMapEncodeTiled", &fn, cudaEnableDefault, &qr);
  EncFn f = (EncFn)fn;
  void *pxn, *py, *ph, *po, *pq;
  cudaGetSymbolAddress(&pxn, g_xn); cudaGetSymbolAddress(&py, g_y); cudaGetSymbolAddress(&ph, g_hid); cudaGetSymbolAddress(&po, g_o); cudaGetSymbolAddress(&pq, g_qkv);
  Maps mp;
  mk(f, &mp.xn, pxn, SEQ, DM, 128); mk(f, &mp.y, py, SEQ, DM, 128); mk(f, &mp.hid, ph, SEQ, FF, 128); mk(f, &mp.o, po, SEQ, 4096, 128); mk(f, &mp.qkv, pq, SEQ, QW, 128);
  mk(f, &mp.wk, Wk, DM, 4096, 64); mk(f, &mp.wv, Wv, DM, 4096, 64); mk(f, &mp.wq, Wq, DM, 4096, 64);
  mk(f, &mp.w1, w1, DM, FF, 64); mk(f, &mp.w2, w2, FF, DM, 64); mk(f, &mp.wo, Wo, 4096, DM, 64);
  cudaFuncSetAttribute(main_kernel, cudaFuncAttributeMaxDynamicSharedMemorySize, SMEM_BYTES);
  prologue_kernel<<<256, 256, 0, cudaStreamPerThread>>>(x, mem0, Wq, Wk, Wv, Wo);
  main_kernel<<<NCTA, 384, SMEM_BYTES, cudaStreamPerThread>>>(mp, x, Wq, Wk, Wv, Wo, b1, b2, (bf16*)d_out);
}
```

```cpp
#include <cuda_runtime.h>
#include <cuda_bf16.h>
#include <cuda.h>
#include <stdint.h>

typedef __nv_bfloat16 bf16;
constexpr int SEQ = 2048, DM = 512, FF = 1792, QW = 12288, NSTEP = 64;
constexpr int NREC = 64, NBULK = 68, NCTA = 132;
constexpr int SPIN_LIMIT = 1 << 22;
#define THR 4
#define PDELAY 500

__device__ bf16 g_xn[SEQ * DM];
__device__ bf16 g_y[SEQ * DM];
__device__ bf16 g_qkv[(size_t)SEQ * QW];
__device__ bf16 g_hid[SEQ * FF];
__device__ bf16 g_o[(size_t)SEQ * 4096];
#define NFULL 13
__device__ bf16 g_g[SEQ * DM];
__device__ float g_sp[(16 - NFULL) * 8 * 128 * DM];
__device__ float4 g_acc[NSTEP][2][768];
__device__ bf16 g_km[NSTEP * 32 * 8 * 128];
__device__ bf16 g_vmT[NSTEP * 32 * 128 * 8];
struct Flags { int tile[16][48]; int hid[16]; int z[16][2]; int o[16][8]; int s[16][2]; int prog[16][32]; int next; };
__device__ Flags g_fl;

#define TR(i)
#define TB(i)
#define TI(i)
struct Maps { CUtensorMap xn, y, hid, o, qkv, wk, wv, wq, w1, w2, wo; };

extern __shared__ __align__(1024) uint8_t smem_raw[];
__device__ __forceinline__ uint4 ldc(uint32_t off) { return *(const uint4*)(smem_raw + off); }
__device__ __forceinline__ uint32_t smem_u32(const void* p) { return (uint32_t)__cvta_generic_to_shared(p); }
__device__ __forceinline__ int otid() { int t; asm volatile("mov.u32 %0, %%tid.x;" : "=r"(t)); return t; }
__device__ __forceinline__ uint32_t mapa(uint32_t a, uint32_t r) { uint32_t o; asm volatile("mapa.shared::cluster.u32 %0, %1, %2;" : "=r"(o) : "r"(a), "r"(r)); return o; }
__device__ __forceinline__ void st_async_v4(uint32_t addr, float a, float b, float c, float d, uint32_t mbar) {
  asm volatile("st.async.weak.shared::cluster.mbarrier::complete_tx::bytes.v4.b32 [%0], {%1,%2,%3,%4}, [%5];" ::"r"(addr), "r"(__float_as_uint(a)), "r"(__float_as_uint(b)), "r"(__float_as_uint(c)), "r"(__float_as_uint(d)), "r"(mbar) : "memory"); }
__device__ __forceinline__ void mbar_init(uint32_t m, int c) { asm volatile("mbarrier.init.shared::cta.b64 [%0], %1;" ::"r"(m), "r"(c) : "memory"); }
__device__ __forceinline__ void mbar_expect(uint32_t m, int bytes) { asm volatile("mbarrier.arrive.expect_tx.shared::cta.b64 _, [%0], %1;" ::"r"(m), "r"(bytes) : "memory"); }
__device__ __forceinline__ void mbar_arrive(uint32_t m) { asm volatile("mbarrier.arrive.shared::cta.b64 _, [%0];" ::"r"(m) : "memory"); }
__device__ __forceinline__ void mbar_wait(uint32_t m, uint32_t parity) {
  uint32_t ok; int it = 0;
  do { asm volatile("{.reg .pred p; mbarrier.try_wait.parity.shared::cta.b64 p, [%1], %2; selp.u32 %0,1,0,p;}" : "=r"(ok) : "r"(m), "r"(parity) : "memory"); } while (!ok && ++it < SPIN_LIMIT); }
__device__ __forceinline__ void mbar_spin(uint32_t m, uint32_t parity) {
  uint32_t ok; int it = 0;
  do { asm volatile("{.reg .pred p; mbarrier.test_wait.parity.shared::cta.b64 p, [%1], %2; selp.u32 %0,1,0,p;}" : "=r"(ok) : "r"(m), "r"(parity) : "memory"); } while (!ok && ++it < SPIN_LIMIT); }
__device__ __forceinline__ void bar_sync(int id, int n) { asm volatile("bar.sync %0, %1;" ::"r"(id), "r"(n) : "memory"); }
__device__ __forceinline__ void bar_arrive(int id, int n) { asm volatile("bar.arrive %0, %1;" ::"r"(id), "r"(n) : "memory"); }
__device__ __forceinline__ int ld_acq(const int* p) { int v; asm volatile("ld.acquire.gpu.global.s32 %0, [%1];" : "=r"(v) : "l"(p) : "memory"); return v; }
__device__ __forceinline__ void wait_flag(const int* p, int target) { int it = 0; while (ld_acq(p) < target && ++it < SPIN_LIMIT) { __nanosleep(40); } }
__device__ __forceinline__ void fence_async() { asm volatile("fence.proxy.async.global;" ::: "memory"); }
__device__ __forceinline__ uint4 lds128(uint32_t a) { uint4 v; asm volatile("ld.shared.v4.u32 {%0,%1,%2,%3}, [%4];" : "=r"(v.x), "=r"(v.y), "=r"(v.z), "=r"(v.w) : "r"(a) : "memory"); return v; }
__device__ __forceinline__ void sts128(uint32_t a, uint4 v) { asm volatile("st.shared.v4.u32 [%0], {%1,%2,%3,%4};" ::"r"(a), "r"(v.x), "r"(v.y), "r"(v.z), "r"(v.w) : "memory"); }
__device__ __forceinline__ void sts32(uint32_t a, uint32_t v) { asm volatile("st.shared.u32 [%0], %1;" ::"r"(a), "r"(v) : "memory"); }
__device__ __forceinline__ void sts16(uint32_t a, float f) { unsigned short h = __bfloat16_as_ushort(__float2bfloat16(f)); asm volatile("st.shared.u16 [%0], %1;" ::"r"(a), "h"(h) : "memory"); }
__device__ __forceinline__ void ldsm4(uint32_t* r, uint32_t a) { asm volatile("ldmatrix.sync.aligned.m8n8.x4.shared.b16 {%0,%1,%2,%3}, [%4];" : "=r"(r[0]), "=r"(r[1]), "=r"(r[2]), "=r"(r[3]) : "r"(a) : "memory"); }
__device__ __forceinline__ void ldsm4t(uint32_t* r, uint32_t a) { asm volatile("ldmatrix.sync.aligned.m8n8.x4.trans.shared.b16 {%0,%1,%2,%3}, [%4];" : "=r"(r[0]), "=r"(r[1]), "=r"(r[2]), "=r"(r[3]) : "r"(a) : "memory"); }
__device__ __forceinline__ void mma16(float* c, uint32_t a0, uint32_t a1, uint32_t a2, uint32_t a3, uint32_t b0, uint32_t b1) {
  asm("mma.sync.aligned.m16n8k16.row.col.f32.bf16.bf16.f32 {%0,%1,%2,%3}, {%4,%5,%6,%7}, {%8,%9}, {%0,%1,%2,%3};" : "+f"(c[0]), "+f"(c[1]), "+f"(c[2]), "+f"(c[3]) : "r"(a0), "r"(a1), "r"(a2), "r"(a3), "r"(b0), "r"(b1)); }
__device__ __forceinline__ void mma8(float* c, uint32_t a0, uint32_t a1, uint32_t b0) {
  asm("mma.sync.aligned.m16n8k8.row.col.f32.bf16.bf16.f32 {%0,%1,%2,%3}, {%4,%5}, {%6}, {%0,%1,%2,%3};" : "+f"(c[0]), "+f"(c[1]), "+f"(c[2]), "+f"(c[3]) : "r"(a0), "r"(a1), "r"(b0)); }
__device__ __forceinline__ uint32_t pack2(float a, float b) { __nv_bfloat162 h = __floats2bfloat162_rn(a, b); return *(uint32_t*)&h; }
__device__ __forceinline__ float rbf(float x) { uint32_t r; asm("cvt.rn.bf16x2.f32 %0, %1, %2;" : "=r"(r) : "f"(x), "f"(0.f)); return __uint_as_float(r); }
__device__ __forceinline__ void cp16(uint32_t d, const void* s) { asm volatile("cp.async.cg.shared.global [%0], [%1], 16;" ::"r"(d), "l"(s) : "memory"); }
__device__ __forceinline__ void tma2d(uint32_t dst, const CUtensorMap* m, int c0, int c1, uint32_t mbar) {
  asm volatile("cp.async.bulk.tensor.2d.shared::cluster.global.mbarrier::complete_tx::bytes [%0], [%1, {%2,%3}], [%4];" ::"r"(dst), "l"(m), "r"(c0), "r"(c1), "r"(mbar) : "memory"); }
__device__ __forceinline__ uint64_t mkdesc(uint32_t addr, uint32_t lbo, uint32_t sbo) {
  return (uint64_t)((addr & 0x3FFFF) >> 4) | ((uint64_t)(lbo >> 4) << 16) | ((uint64_t)(sbo >> 4) << 32) | (1ull << 62); }

#define R8(i) "+f"(d[i]), "+f"(d[i+1]), "+f"(d[i+2]), "+f"(d[i+3]), "+f"(d[i+4]), "+f"(d[i+5]), "+f"(d[i+6]), "+f"(d[i+7])
__device__ __forceinline__ void wgmma256(float* d, uint64_t da, uint64_t db, int acc) {
  asm volatile("{.reg .pred p; setp.ne.b32 p, %130, 0;\n"
    "wgmma.mma_async.sync.aligned.m64n256k16.f32.bf16.bf16 {"
    "%0,%1,%2,%3,%4,%5,%6,%7,%8,%9,%10,%11,%12,%13,%14,%15,%16,%17,%18,%19,%20,%21,%22,%23,%24,%25,%26,%27,%28,%29,%30,%31,"
    "%32,%33,%34,%35,%36,%37,%38,%39,%40,%41,%42,%43,%44,%45,%46,%47,%48,%49,%50,%51,%52,%53,%54,%55,%56,%57,%58,%59,%60,%61,%62,%63,"
    "%64,%65,%66,%67,%68,%69,%70,%71,%72,%73,%74,%75,%76,%77,%78,%79,%80,%81,%82,%83,%84,%85,%86,%87,%88,%89,%90,%91,%92,%93,%94,%95,"
    "%96,%97,%98,%99,%100,%101,%102,%103,%104,%105,%106,%107,%108,%109,%110,%111,%112,%113,%114,%115,%116,%117,%118,%119,%120,%121,%122,%123,%124,%125,%126,%127"
    "}, %128, %129, p, 1, 1, 0, 1;}"
    : R8(0), R8(8), R8(16), R8(24), R8(32), R8(40), R8(48), R8(56), R8(64), R8(72), R8(80), R8(88), R8(96), R8(104), R8(112), R8(120)
    : "l"(da), "l"(db), "r"(acc)); }

__global__ void __launch_bounds__(256) prologue_kernel(const bf16* __restrict__ x, const bf16* __restrict__ mem0, const bf16* Wq, const bf16* Wk, const bf16* Wv, const bf16* Wo) {
  int tid = threadIdx.x, lane = tid & 31, warp = tid >> 5;
  { const int gt = blockIdx.x * 256 + tid; const size_t o = (size_t)(gt & 32767) * 64;
    asm volatile("prefetch.global.L2 [%0];" ::"l"((gt < 32768 ? Wk : Wv) + o));
    asm volatile("prefetch.global.L2 [%0];" ::"l"((gt < 32768 ? Wq : Wo) + o)); }
  int row = blockIdx.x * 8 + warp;
  {
    const uint4* src = (const uint4*)(x + (size_t)row * DM);
    uint4 u[2] = { src[lane], src[lane + 32] };
    float v[16];
    #pragma unroll
    for (int i = 0; i < 2; i++) { const __nv_bfloat162* h = (const __nv_bfloat162*)&u[i];
      #pragma unroll
      for (int k = 0; k < 4; k++) { float2 f = __bfloat1622float2(h[k]); v[i * 8 + 2 * k] = f.x; v[i * 8 + 2 * k + 1] = f.y; } }
    #pragma unroll
    for (int pass = 0; pass < 2; pass++) {
      float s = 0;
      #pragma unroll
      for (int i = 0; i < 16; i++) s += v[i];
      #pragma unroll
      for (int o = 16; o; o >>= 1) s += __shfl_xor_sync(~0u, s, o);
      float mf = s * (1.f / DM);
      float q = 0;
      #pragma unroll
      for (int i = 0; i < 16; i++) { float dd = v[i] - mf; q += dd * dd; }
      #pragma unroll
      for (int o = 16; o; o >>= 1) q += __shfl_xor_sync(~0u, q, o);
      float m = rbf(mf), var = rbf(q * (1.f / DM));
      float den = rbf(sqrtf(rbf(var + 1e-5f)));
      #pragma unroll
      for (int i = 0; i < 16; i++) v[i] = rbf(rbf(v[i] - m) / den);
      uint4 o4[2];
      #pragma unroll
      for (int i = 0; i < 2; i++) { o4[i].x = pack2(v[i*8], v[i*8+1]); o4[i].y = pack2(v[i*8+2], v[i*8+3]); o4[i].z = pack2(v[i*8+4], v[i*8+5]); o4[i].w = pack2(v[i*8+6], v[i*8+7]); }
      uint4* dst = (uint4*)((pass ? g_y : g_xn) + (size_t)row * DM);
      dst[lane] = o4[0]; dst[lane + 32] = o4[1];
    }
  }
  int gt = blockIdx.x * 256 + tid;
  float4 z4 = make_float4(0, 0, 0, 0);
  for (int i = gt; i < NSTEP * 1536; i += 65536) {
    float4 val = z4;
    if (i < 1536) {
      int j = i / 768, c = i % 768, ci = c >> 8, w = (c & 255) >> 5, l = c & 31, g = l >> 2, t = l & 3;
      float e3[3];
      #pragma unroll
      for (int k = 0; k < 3; k++) { int e = ci * 3 + k; int mt = e >> 2, cc = e & 3;
        e3[k] = e < 8 ? __bfloat162float(mem0[(2 * t + (cc & 1)) * DM + 256 * j + 32 * w + 16 * mt + g + 8 * (cc >> 1)]) : 0.f; }
      val = make_float4(e3[0], e3[1], e3[2], 32.f);
    }
    (&g_acc[0][0][0])[i] = val;
  }
  if (gt < (int)(sizeof(Flags) / 4)) ((int*)&g_fl)[gt] = 0;
}

constexpr int R_WR = 0, R_WO = 65536, R_KT = 131072, KT_SZ = 40 * 256, R_VT = R_KT + 2 * KT_SZ, VT_SZ = 40 * 272,
              R_MEM = R_VT + 2 * VT_SZ, R_Q = R_MEM + 32 * 160, R_O = R_Q + 8 * 256, R_S = R_O + 8 * 256,
              R_SM = R_S + 8 * 40 * 4, R_RQK = R_SM + 1024, R_RV = R_RQK + 8192, R_WQ = R_RV + 4096, R_BAR = 232448 - 64, R_END = R_BAR + 64;
static_assert(R_WQ + 32768 <= R_BAR, "smem");
#define PI 0
#define LD1(v, p) asm volatile("ld.relaxed.gpu.global.v4.u32 {%0,%1,%2,%3}, [%4];" : "=r"(v.x), "=r"(v.y), "=r"(v.z), "=r"(v.w) : "l"(p) : "memory")
#define LD3(a, b, c) do { LD1(a, src + ((EXP & 2) ? 256 * (h % 3) : 0)); if (EXP & 2) { b = a; c = a; } else { LD1(b, src + 256); LD1(c, src + 512); } } while (0)
#define OK3(a, b, c) __all_sync(~0u, (a.w == 0x42000000u) && (b.w == 0x42000000u) && (c.w == 0x42000000u))
#define W7D 1100
#define NW0 8
#define VD 0
#define KD 150
#define VCH 2
#define VP 3
__device__ __forceinline__ void wgmma8(float* d, uint64_t da, uint64_t db, int acc) {
  asm volatile("{.reg .pred p; setp.ne.b32 p, %6, 0;\n wgmma.mma_async.sync.aligned.m64n8k16.f32.bf16.bf16 {%0,%1,%2,%3}, %4, %5, p, 1, 1, 0, 0;}"
    : "+f"(d[0]), "+f"(d[1]), "+f"(d[2]), "+f"(d[3]) : "l"(da), "l"(db), "r"(acc)); }
__device__ __forceinline__ void stsm4(uint32_t a, uint32_t r0, uint32_t r1, uint32_t r2, uint32_t r3) { asm volatile("stmatrix.sync.aligned.m8n8.x4.shared.b16 [%0], {%1,%2,%3,%4};" ::"r"(a), "r"(r0), "r"(r1), "r"(r2), "r"(r3) : "memory"); }
__device__ __forceinline__ uint32_t swz(uint32_t r) { return ((r & 1) << 2) | ((r >> 1) & 3); }
__device__ __forceinline__ void stsm4t(uint32_t a, uint32_t r0, uint32_t r1, uint32_t r2, uint32_t r3) { asm volatile("stmatrix.sync.aligned.m8n8.x4.trans.shared.b16 [%0], {%1,%2,%3,%4};" ::"r"(a), "r"(r0), "r"(r1), "r"(r2), "r"(r3) : "memory"); }
__device__ __forceinline__ void stsm2(uint32_t a, uint32_t r0, uint32_t r1) { asm volatile("stmatrix.sync.aligned.m8n8.x2.shared.b16 [%0], {%1,%2};" ::"r"(a), "r"(r0), "r"(r1) : "memory"); }
__device__ __forceinline__ float ex2(float x) { float r; asm("ex2.approx.ftz.f32 %0, %1;" : "=f"(r) : "f"(x)); return r; }
#define REDV4(p, a, b, c) asm volatile("red.relaxed.gpu.global.add.v4.f32 [%0], {%1,%2,%3,%4};" ::"l"(p), "f"(a), "f"(b), "f"(c), "f"(RCNT) : "memory")
#define EXP 0
#define RCNT ((EXP & 1) ? 4.0f : 1.0f)
constexpr int SMEM_BYTES = 232448;
static_assert(R_END <= SMEM_BYTES, "smem");

__device__ __forceinline__ void recurrence(uint32_t sb, const bf16* __restrict__ Wq, const bf16* __restrict__ Wk, const bf16* __restrict__ Wv, const bf16* __restrict__ Wo) {
  const int tid = threadIdx.x, warp = tid >> 5, lane = tid & 31, g = lane >> 2, t = lane & 3;
  const int h = blockIdx.x >> 1, j = blockIdx.x & 1;
  const uint32_t peer = j ^ 1;
  const uint32_t mQ = sb + R_BAR, mV = sb + R_BAR + 8, mK = sb + R_BAR + 16;
  uint32_t A[2][16][4];
  TI(1);
  const int lm = lane >> 3, lr = lane & 7;
  for (int i = tid; i < 256 * 16; i += 384) { const int r = i >> 4, c = i & 15; const size_t o = ((size_t)(256 * j + r)) * 4096 + h * 128 + c * 8;
    const uint32_t d = sb + r * 256 + ((c ^ ((r & 1) | ((r >> 2) & 6))) << 4);
    cp16(d + 131072, Wq + o); cp16(d + 65536, Wk + o); cp16(d, Wv + o); }
  auto ldwo = [&](int half, uint32_t st) {
    for (int i = tid; i < 64 * 32; i += 384) { const int r = i >> 5, c = i & 31;
      cp16(st + r * 512 + ((c ^ ((r & 1) | ((r >> 2) & 6))) << 4), Wo + ((size_t)(h * 128 + 64 * half + r)) * DM + 256 * j + c * 8); } };
  auto cvwo = [&](int half, uint32_t st) {
    if (warp < 8) {
      #pragma unroll
      for (int i = 0; i < 8; i++) { const int wv = warp >> 1, mt = warp & 1, kq = i & 3, hi = i >> 2;
        const int k = 32 * (kq >> 1) + 8 * (lr >> 1) + (lr & 1) + 4 * (kq & 1) + 2 * (lm >> 1); uint32_t r[4];
        ldsm4t(r, st + k * 512 + (((8 * wv + 4 * mt + 2 * hi + (lm & 1)) ^ lr) << 4));
        sts128(sb + R_WO + ((wv * 32 + mt * 16 + hi * 8 + half * 4 + kq) * 32 + lane) * 16, make_uint4(r[0], r[1], r[2], r[3])); }
    } };
  ldwo(0, sb + 196608);
  asm volatile("cp.async.wait_all;" ::: "memory"); __syncthreads();
  TI(2);
  { const uint32_t st = sb + (2 - (warp >> 2)) * 65536;
    #pragma unroll
    for (int mt = 0; mt < 2; mt++)
      #pragma unroll
      for (int ks = 0; ks < 16; ks++) {
        const int k = 32 * (ks >> 1) + 8 * (lr >> 1) + (lr & 1) + 4 * (ks & 1) + 2 * (lm >> 1);
        ldsm4t(A[mt][ks], st + k * 256 + (((4 * (warp & 3) + 2 * mt + (lm & 1)) ^ lr) << 4));
      } }
  __syncthreads();
  TI(3);
  ldwo(1, sb + 131072);
  cvwo(0, sb + 196608);
  if (warp >= 8) {
    #pragma unroll
    for (int i = 0; i < 32; i++) sts128(sb + R_WR + (((warp - 8) * 32 + i) * 32 + lane) * 16, make_uint4(A[i & 1][i >> 1][0], A[i & 1][i >> 1][1], A[i & 1][i >> 1][2], A[i & 1][i >> 1][3]));
  }
  asm volatile("cp.async.wait_all;" ::: "memory"); __syncthreads();
  TI(4);
  cvwo(1, sb + 131072);
  if (warp < 4) {
    #pragma unroll
    for (int i = 0; i < 16; i++) sts128(sb + R_WQ + ((warp * 16 + i) * 32 + lane) * 16, make_uint4(A[1][i][0], A[1][i][1], A[1][i][2], A[1][i][3]));
  }
  __syncthreads();
  if (warp >= 8) {
    const uint32_t zero = blockIdx.y;
    #pragma unroll 1
    for (int s = 0; s < NSTEP; s++) {
      const int tid = otid(), lane = tid & 31, wv = (tid >> 5) - 8, g = lane >> 2, t = lane & 3;
      if (tid == 256) mbar_expect(mV, 4096);
      const uint32_t fo = (t ^ swz(g)) << 4;
      TR(1);
      bar_sync(4, 384);
      if (VD) { long long t0 = clock64(); while (clock64() - t0 < VD); }
      TR(2);
      float c[4][4];
      #pragma unroll
      for (int i = 0; i < 4; i++) { c[i][0] = c[i][1] = c[i][2] = c[i][3] = 0.f; }
      #pragma unroll
      for (int p = 0; p < 8; p++) {
        uint4 b = ldc(R_MEM + g * 16 + t * 160 + p * 640);
        mma16(c[0], A[0][2*p][0], A[0][2*p][1], A[0][2*p][2], A[0][2*p][3], b.x, b.y);
        mma16(c[1], A[1][2*p][0], A[1][2*p][1], A[1][2*p][2], A[1][2*p][3], b.x, b.y);
        mma16(c[2], A[0][2*p+1][0], A[0][2*p+1][1], A[0][2*p+1][2], A[0][2*p+1][3], b.z, b.w);
        mma16(c[3], A[1][2*p+1][0], A[1][2*p+1][1], A[1][2*p+1][2], A[1][2*p+1][3], b.z, b.w);
      }
      #pragma unroll
      for (int i = 0; i < 4; i++) { c[0][i] += c[2][i]; c[1][i] += c[3][i]; }
      const uint32_t rx = sb + R_RV + (wv * 64 + lane) * 16;
      { uint32_t ra = mapa(rx, peer), rm = mapa(mV, peer);
        st_async_v4(ra, c[0][0], c[0][1], c[0][2], c[0][3], rm);
        st_async_v4(ra + 512, c[1][0], c[1][1], c[1][2], c[1][3], rm); }
      TR(4);
      const bool more = s < NSTEP - 1;
      uint32_t wb = sb + (wv * 1024 + lane) * 16;
      #pragma unroll
      for (int i = 0; i < NW0; i++) { uint4 v = lds128(wb + R_WO + i * 512); A[i >> 4][i & 15][0] = v.x; A[i >> 4][i & 15][1] = v.y; A[i >> 4][i & 15][2] = v.z; A[i >> 4][i & 15][3] = v.w; }
      TR(3);
      mbar_wait(mV, s & 1);
      TR(5);
      { uint4 r0 = lds128(rx), r1 = lds128(rx + 512);
        stsm4t(sb + R_VT + (s & 1) * VT_SZ + (32 + (lane & 7)) * 272 + (4 * wv + (lane >> 3)) * 16,
          pack2(c[0][0] + __uint_as_float(r0.x), c[0][1] + __uint_as_float(r0.y)), pack2(c[0][2] + __uint_as_float(r0.z), c[0][3] + __uint_as_float(r0.w)),
          pack2(c[1][0] + __uint_as_float(r1.x), c[1][1] + __uint_as_float(r1.y)), pack2(c[1][2] + __uint_as_float(r1.z), c[1][3] + __uint_as_float(r1.w))); }
      if (more) {
      bar_arrive(3, 256);
      TR(8);
      #pragma unroll
      for (int i = NW0; i < 32; i++) { uint4 v = lds128(wb + R_WO + i * 512); A[i >> 4][i & 15][0] = v.x; A[i >> 4][i & 15][1] = v.y; A[i >> 4][i & 15][2] = v.z; A[i >> 4][i & 15][3] = v.w;
        if ((i % THR) == THR - 1) wb += v.x & zero; }
      TR(10);
      bar_sync(7, 256);
      TR(9);
      #pragma unroll
      for (int i = 0; i < 4; i++) { c[i][0] = c[i][1] = c[i][2] = c[i][3] = 0.f; }
      #pragma unroll
      for (int p = 0; p < 4; p++) {
        uint4 b = ldc(R_O + g * 256 + (p >> 1) * 128 + (fo ^ ((p & 1) << 6)));
        #pragma unroll
        for (int mt = 0; mt < 4; mt++) { const uint32_t* a = A[mt >> 1][(mt & 1) * 8 + 2 * p]; mma16(c[mt], a[0], a[1], a[2], a[3], b.x, b.y); }
        #pragma unroll
        for (int mt = 0; mt < 4; mt++) { const uint32_t* a = A[mt >> 1][(mt & 1) * 8 + 2 * p + 1]; mma16(c[mt], a[0], a[1], a[2], a[3], b.z, b.w); }
      }
      TR(6);
      float4* dst = &g_acc[s + 1][j][wv * 64 + lane];
      if (!(EXP & 1) || (h & 3) == wv) {
      REDV4(dst, c[0][0], c[0][1], c[0][2]); REDV4(dst + 256, c[0][3], c[1][0], c[1][1]); REDV4(dst + 512, c[1][2], c[1][3], 0.f);
      REDV4(dst + 32, c[2][0], c[2][1], c[2][2]); REDV4(dst + 288, c[2][3], c[3][0], c[3][1]); REDV4(dst + 544, c[3][2], c[3][3], 0.f); }
      bar_arrive(8, 352);
      TR(7);
      } else bar_sync(6, 256);
      { const int vt = tid - 256;
        if (j == 0) { const int r = vt >> 4, cc = vt & 15; uint4 v = lds128(sb + R_KT + (s & 1) * KT_SZ + (32 + r) * 256 + ((cc ^ swz(r)) << 4));
          __stcg((uint4*)(g_km + ((size_t)(s * 32 + h)) * 1024) + vt, v); }
        else { uint32_t vb = sb + R_VT + (s & 1) * VT_SZ + 32 * 272 + vt * 2; uint32_t e[8];
          #pragma unroll
          for (int k = 0; k < 8; k++) { unsigned short x; asm volatile("ld.shared.u16 %0, [%1];" : "=h"(x) : "r"(vb + k * 272) : "memory"); e[k] = x; }
          __stcg((uint4*)(g_vmT + ((size_t)(s * 32 + h)) * 1024) + vt, make_uint4(e[0] | (e[1] << 16), e[2] | (e[3] << 16), e[4] | (e[5] << 16), e[6] | (e[7] << 16))); }
        if (!more) { __syncwarp(); if (lane == 0) { __threadfence(); atomicAdd(&g_fl.prog[15][h], 1); } } }
      #pragma unroll
      for (int i = 0; i < 32; i++) { uint4 v = lds128(wb + R_WR + i * 512); A[i & 1][i >> 1][0] = v.x; A[i & 1][i >> 1][1] = v.y; A[i & 1][i >> 1][2] = v.z; A[i & 1][i >> 1][3] = v.w; }
    }
    return;
  }
  const float scale = 0.08838834764831845f, l2e = 1.4426950408889634f;
  auto prefetch = [&](int s) {
    const int vt = otid() - 160;
    if ((s & 3) == 0) { wait_flag(&g_fl.tile[s >> 2][h >> 1], 1); wait_flag(&g_fl.tile[s >> 2][16 + (h >> 1)], 1); }
    const int r = vt >> 4, c = vt & 15;
    const bf16* src = g_qkv + (size_t)(32 * s + r) * QW + h * 128 + c * 8;
    uint32_t kb = sb + R_KT + (s & 1) * KT_SZ + r * 256, vb = sb + R_VT + (s & 1) * VT_SZ + r * 272 + c * 16;
    #pragma unroll
    for (int i = 0; i < 8; i++) { cp16(kb + i * 1024 + ((c ^ swz(r + 4 * i)) << 4), src + (size_t)i * 4 * QW); cp16(vb + i * 1088, src + (size_t)i * 4 * QW + 4096); }
  };
  if (warp >= 4) {
  if (warp == 5 || warp == 6) prefetch(0);
  #pragma unroll 1
  for (int s = 0; s < NSTEP; s++) {
    TR(0); TR(1);
    const int tid = otid(), lane = tid & 31, warp = tid >> 5, g = lane >> 2, t = lane & 3;
    const uint32_t fo = (t ^ swz(g)) << 4;
    {
      if (tid == 0) mbar_expect(mQ, 4096);
      if (tid == 128) mbar_expect(mK, 4096);
      const float4* src = &g_acc[s][j][tid];
      uint4 v0, v1, v2; int it = 0;
      do { LD3(v0, v1, v2); } while (!OK3(v0, v1, v2) && ++it < SPIN_LIMIT);
      __syncwarp();
      stsm4t(sb + R_MEM + (lane & 7) * 16 + (4 * warp + (lane >> 3)) * 160,
        pack2(__uint_as_float(v0.x), __uint_as_float(v0.y)), pack2(__uint_as_float(v0.z), __uint_as_float(v1.x)),
        pack2(__uint_as_float(v1.y), __uint_as_float(v1.z)), pack2(__uint_as_float(v2.x), __uint_as_float(v2.y)));
    }
    TR(2);
    asm volatile("cp.async.wait_all;" ::: "memory");
    bar_sync(1, 256);
    { long long t0 = clock64(); while (clock64() - t0 < KD); }
    if (VP < 0) bar_arrive(4, 384);
    TR(3);
    float c[4][4];
    #pragma unroll
    for (int i = 0; i < 4; i++) { c[i][0] = c[i][1] = c[i][2] = c[i][3] = 0.f; }
    #pragma unroll
    for (int p = 0; p < 8; p++) {
      uint4 b = ldc(R_MEM + g * 16 + t * 160 + p * 640);
      mma16(c[0], A[0][2*p][0], A[0][2*p][1], A[0][2*p][2], A[0][2*p][3], b.x, b.y);
      mma16(c[1], A[1][2*p][0], A[1][2*p][1], A[1][2*p][2], A[1][2*p][3], b.x, b.y);
      mma16(c[2], A[0][2*p+1][0], A[0][2*p+1][1], A[0][2*p+1][2], A[0][2*p+1][3], b.z, b.w);
      mma16(c[3], A[1][2*p+1][0], A[1][2*p+1][1], A[1][2*p+1][2], A[1][2*p+1][3], b.z, b.w);
      if (p == VP) asm volatile("bar.arrive 4, 384;");
    }
    #pragma unroll
    for (int i = 0; i < 4; i++) { c[0][i] += c[2][i]; c[1][i] += c[3][i]; }
    const uint32_t rx = sb + R_RQK + (warp * 64 + lane) * 16;
    { uint32_t ra = mapa(rx, peer), rm = mapa(mK, peer);
      st_async_v4(ra, c[0][0], c[0][1], c[0][2], c[0][3], rm);
      st_async_v4(ra + 512, c[1][0], c[1][1], c[1][2], c[1][3], rm); }
    if (VP > 7) bar_arrive(4, 384);
    TR(4);
    const uint32_t so = (lane & 7) * 256 + (((4 * (warp & 3) + (lane >> 3)) ^ swz(lane & 7)) << 4);
    mbar_wait(mK, s & 1);
    TR(5);
    uint32_t m0, m1, m2, m3;
    { uint4 r0 = lds128(rx), r1 = lds128(rx + 512);
      m0 = pack2(c[0][0] + __uint_as_float(r0.x), c[0][1] + __uint_as_float(r0.y)); m1 = pack2(c[0][2] + __uint_as_float(r0.z), c[0][3] + __uint_as_float(r0.w));
      m2 = pack2(c[1][0] + __uint_as_float(r1.x), c[1][1] + __uint_as_float(r1.y)); m3 = pack2(c[1][2] + __uint_as_float(r1.z), c[1][3] + __uint_as_float(r1.w)); }
    stsm4t(sb + R_KT + (s & 1) * KT_SZ + 32 * 256 + so, m0, m1, m2, m3);
    if (s == NSTEP - 1) { bar_arrive(6, 256); break; }
    asm("movmatrix.sync.aligned.m8n8.trans.b16 %0, %0;" : "+r"(m0)); asm("movmatrix.sync.aligned.m8n8.trans.b16 %0, %0;" : "+r"(m1));
    asm("movmatrix.sync.aligned.m8n8.trans.b16 %0, %0;" : "+r"(m2)); asm("movmatrix.sync.aligned.m8n8.trans.b16 %0, %0;" : "+r"(m3));
    TR(8);
    bar_sync(9, 256);
    TR(9);
    { uint32_t qa[4]; ldsm4(qa, sb + R_Q + so);
      #pragma unroll
      for (int i = 0; i < 2; i++) { c[i][0] = c[i][1] = c[i][2] = c[i][3] = 0.f; }
      mma16(c[0], qa[0], 0, qa[1], 0, m0, m1); mma16(c[1], qa[2], 0, qa[3], 0, m2, m3);
      asm volatile("st.shared.v2.f32 [%0], {%1,%2};" ::"r"(sb + R_SM + (warp - 4) * 256 + lane * 8), "f"(c[0][0] + c[1][0]), "f"(c[0][1] + c[1][1]) : "memory"); }
    bar_arrive(2, 256);
    TR(10);
    if ((warp == 5 || warp == 6) && s < NSTEP - 2) prefetch(s + 1);
    TR(7);
    if (warp == 7) { if ((s & 3) == 1 && s > 1 && lane == 0) asm volatile("red.release.gpu.global.add.s32 [%0], 4;" ::"l"(&g_fl.prog[(s - 2) >> 2][h]) : "memory"); __syncwarp();
      long long t0 = clock64(); while (clock64() - t0 < W7D); }
    else bar_sync(8, 352);
    { long long t0 = clock64(); while (clock64() - t0 < PDELAY); }
  }
  return;
  }
  #pragma unroll 1
  for (int s = 0; s < NSTEP; s++) {
    TR(0); TR(1);
    const int tid = otid(), lane = tid & 31, warp = tid >> 5, g = lane >> 2, t = lane & 3;
    const uint32_t fo = (t ^ swz(g)) << 4;
    {
      if (tid == 0) mbar_expect(mQ, 4096);
      if (tid == 128) mbar_expect(mK, 4096);
      const float4* src = &g_acc[s][j][tid];
      uint4 v0, v1, v2; int it = 0;
      do { LD3(v0, v1, v2); } while (!OK3(v0, v1, v2) && ++it < SPIN_LIMIT);
      __syncwarp();
      stsm4t(sb + R_MEM + (lane & 7) * 16 + (4 * warp + (lane >> 3)) * 160,
        pack2(__uint_as_float(v0.x), __uint_as_float(v0.y)), pack2(__uint_as_float(v0.z), __uint_as_float(v1.x)),
        pack2(__uint_as_float(v1.y), __uint_as_float(v1.z)), pack2(__uint_as_float(v2.x), __uint_as_float(v2.y)));
    }
    TR(2);

    bar_sync(1, 256);
    bar_arrive(4, 384);
    TR(3);
    float c[4][4];
    #pragma unroll
    for (int i = 0; i < 4; i++) { c[i][0] = c[i][1] = c[i][2] = c[i][3] = 0.f; }
    #pragma unroll
    for (int p = 0; p < 8; p++) {
      uint4 b = ldc(R_MEM + g * 16 + t * 160 + p * 640);
      mma16(c[0], A[0][2*p][0], A[0][2*p][1], A[0][2*p][2], A[0][2*p][3], b.x, b.y);
      mma16(c[1], A[1][2*p][0], A[1][2*p][1], A[1][2*p][2], A[1][2*p][3], b.x, b.y);
      mma16(c[2], A[0][2*p+1][0], A[0][2*p+1][1], A[0][2*p+1][2], A[0][2*p+1][3], b.z, b.w);
      mma16(c[3], A[1][2*p+1][0], A[1][2*p+1][1], A[1][2*p+1][2], A[1][2*p+1][3], b.z, b.w);
    }
    #pragma unroll
    for (int i = 0; i < 4; i++) { c[0][i] += c[2][i]; c[1][i] += c[3][i]; }
    const uint32_t rx = sb + R_RQK + (warp * 64 + lane) * 16;
    { uint32_t ra = mapa(rx, peer), rm = mapa(mQ, peer);
      st_async_v4(ra, c[0][0], c[0][1], c[0][2], c[0][3], rm);
      st_async_v4(ra + 512, c[1][0], c[1][1], c[1][2], c[1][3], rm); }
    TR(4);
    const uint32_t so = (lane & 7) * 256 + (((4 * (warp & 3) + (lane >> 3)) ^ swz(lane & 7)) << 4);
    if (s == NSTEP - 1) { mbar_wait(mQ, s & 1); break; }
    uint4 kf[4]; uint32_t vf[4][4];
    const uint32_t vb = sb + R_VT + (s & 1) * VT_SZ + (lane & 15) * 272 + (32 * warp + 8 * (lane >> 4)) * 2;
    #pragma unroll
    for (int p = 0; p < 4; p++) kf[p] = lds128(sb + R_KT + (s & 1) * KT_SZ + warp * 2048 + g * 256 + (p >> 1) * 128 + (fo ^ ((p & 1) << 6)));
    #pragma unroll
    for (int i = 0; i < 4; i++) ldsm4t(vf[i], vb + (i >> 1) * 16 * 272 + (i & 1) * 32);
    mbar_wait(mQ, s & 1);
    TR(5);
    uint32_t m0, m1, m2, m3;
    { uint4 r0 = lds128(rx), r1 = lds128(rx + 512);
      m0 = pack2(c[0][0] + __uint_as_float(r0.x), c[0][1] + __uint_as_float(r0.y)); m1 = pack2(c[0][2] + __uint_as_float(r0.z), c[0][3] + __uint_as_float(r0.w));
      m2 = pack2(c[1][0] + __uint_as_float(r1.x), c[1][1] + __uint_as_float(r1.y)); m3 = pack2(c[1][2] + __uint_as_float(r1.z), c[1][3] + __uint_as_float(r1.w)); }
    stsm4t(sb + R_Q + so, m0, m1, m2, m3);
    TR(8);
    bar_arrive(9, 256); bar_sync(5, 128);
    TR(9);
    {
      uint4 qa[4];
      #pragma unroll
      for (int p = 0; p < 4; p++) qa[p] = lds128(sb + R_Q + g * 256 + (p >> 1) * 128 + (fo ^ ((p & 1) << 6)));
      #pragma unroll
      for (int i = 0; i < 4; i++) { c[i][0] = c[i][1] = c[i][2] = c[i][3] = 0.f; }
      #pragma unroll
      for (int p = 0; p < 4; p++) { mma16(c[(p & 1) * 2], qa[p].x, 0, qa[p].y, 0, kf[p].x, kf[p].y); mma16(c[(p & 1) * 2 + 1], qa[p].z, 0, qa[p].w, 0, kf[p].z, kf[p].w); }
      float a = rbf(rbf((c[0][0] + c[1][0]) + (c[2][0] + c[3][0])) * scale) * l2e, b = rbf(rbf((c[0][1] + c[1][1]) + (c[2][1] + c[3][1])) * scale) * l2e;
      asm volatile("st.shared.v2.f32 [%0], {%1,%2};" ::"r"(sb + R_S + g * 160 + (8 * warp + 2 * t) * 4), "f"(a), "f"(b) : "memory");
    }
    TR(10);
    bar_sync(10, 128);
    float sv[8], pm[8];
    #pragma unroll
    for (int i = 0; i < 4; i++) asm volatile("ld.shared.v2.f32 {%0,%1}, [%2];" : "=f"(sv[2*i]), "=f"(sv[2*i+1]) : "r"(sb + R_S + g * 160 + (8 * i + 2 * t) * 4) : "memory");
    float mx = fmaxf(fmaxf(fmaxf(sv[0], sv[1]), fmaxf(sv[2], sv[3])), fmaxf(fmaxf(sv[4], sv[5]), fmaxf(sv[6], sv[7])));
    mx = fmaxf(mx, __shfl_xor_sync(~0u, mx, 1)); mx = fmaxf(mx, __shfl_xor_sync(~0u, mx, 2));
    uint32_t P[5];
    #pragma unroll
    for (int i = 0; i < 4; i++) P[i] = pack2(ex2(sv[2*i] - mx), ex2(sv[2*i+1] - mx));
    #pragma unroll
    for (int i = 0; i < 4; i++) { c[i][0] = c[i][1] = c[i][2] = c[i][3] = 0.f; }
    #pragma unroll
    for (int kk = 0; kk < 2; kk++) {
      mma16(c[0], P[2*kk], 0, P[2*kk+1], 0, vf[2*kk][0], vf[2*kk][1]); mma16(c[1], P[2*kk], 0, P[2*kk+1], 0, vf[2*kk][2], vf[2*kk][3]);
      mma16(c[2], P[2*kk], 0, P[2*kk+1], 0, vf[2*kk+1][0], vf[2*kk+1][1]); mma16(c[3], P[2*kk], 0, P[2*kk+1], 0, vf[2*kk+1][2], vf[2*kk+1][3]);
    }
    float sum = 0.f;
    #pragma unroll
    for (int i = 0; i < 4; i++) sum += __uint_as_float(P[i] << 16) + __uint_as_float(P[i] & 0xffff0000u);
    TR(11);
    bar_sync(2, 256);
    #pragma unroll
    for (int i = 0; i < 4; i++) asm volatile("ld.shared.v2.f32 {%0,%1}, [%2];" : "=f"(pm[2*i]), "=f"(pm[2*i+1]) : "r"(sb + R_SM + i * 256 + lane * 8) : "memory");
    const float s8 = rbf(rbf((pm[0] + pm[2]) + (pm[4] + pm[6])) * scale) * l2e, s9 = rbf(rbf((pm[1] + pm[3]) + (pm[5] + pm[7])) * scale) * l2e;
    float mg = fmaxf(mx, fmaxf(s8, s9));
    mg = fmaxf(mg, __shfl_xor_sync(~0u, mg, 1)); mg = fmaxf(mg, __shfl_xor_sync(~0u, mg, 2));
    const float fs = ex2(mx - mg);
    P[4] = pack2(ex2(s8 - mg), ex2(s9 - mg));
    #pragma unroll
    for (int i = 0; i < 4; i++) { c[i][0] *= fs; c[i][1] *= fs; }
    sum = fmaf(sum, fs, __uint_as_float(P[4] << 16) + __uint_as_float(P[4] & 0xffff0000u));
    sum += __shfl_xor_sync(~0u, sum, 1); sum += __shfl_xor_sync(~0u, sum, 2);
    float inv; asm("rcp.approx.ftz.f32 %0, %1;" : "=f"(inv) : "f"(sum));
    TR(6);
    bar_sync(3, 256);
    { uint32_t r[4]; ldsm4t(r, sb + R_VT + (s & 1) * VT_SZ + (32 + (lane & 7)) * 272 + (4 * warp + (lane >> 3)) * 16);
      #pragma unroll
      for (int i = 0; i < 4; i++) mma8(c[i], P[4], 0, r[i]); }
    asm volatile("stmatrix.sync.aligned.m8n8.x4.shared.b16 [%0], {%1,%2,%3,%4};" ::"r"(sb + R_O + so),
      "r"(pack2(c[0][0] * inv, c[0][1] * inv)), "r"(pack2(c[1][0] * inv, c[1][1] * inv)), "r"(pack2(c[2][0] * inv, c[2][1] * inv)), "r"(pack2(c[3][0] * inv, c[3][1] * inv)) : "memory");
    bar_arrive(7, 256);
    TR(7);
    bar_sync(8, 352);
    long long t0 = clock64();
    #pragma unroll
    for (int i = 0; i < 16; i++) { uint4 v = lds128(sb + R_WQ + ((warp * 16 + i) * 32 + lane) * 16); A[1][i][0] = v.x; A[1][i][1] = v.y; A[1][i][2] = v.z; A[1][i][3] = v.w; }
    while (clock64() - t0 < PDELAY);
  }
}

constexpr int I_M1 = 512, I_Q = 624, I_M2 = 688, I_Q2 = 720, I_G = 912, I_S = I_G + NFULL * 34, I_END = I_S + (16 - NFULL) * 56;
constexpr int B_STG = 4 * 49152, B_BAR = B_STG + 8 * 2304;
template <int N> struct IC { static constexpr int v = N; };
struct Item { int type, rb, nt, ks; };
__device__ __forceinline__ Item decode(int it) {
  Item r; r.ks = 0;
  if (it < I_M1) { r.type = 0; r.rb = it >> 5; r.nt = it & 31; }
  else if (it < I_Q) { int i = it - I_M1; r.type = 1; r.rb = i / 7; r.nt = i % 7; }
  else if (it < I_M2) { int i = it - I_Q; r.type = 0; r.rb = i >> 4; r.nt = 32 + (i & 15); }
  else if (it < I_Q2) { int i = it - I_M2; r.type = 2; r.rb = i >> 1; r.nt = i & 1; }
  else if (it < I_G) { int i = it - I_Q2 + 64; r.type = 0; r.rb = i >> 4; r.nt = 32 + (i & 15); }
  else if (it < I_S) { int i = it - I_G, q = i % 34; r.rb = i / 34; if (q < 32) { r.type = 3; r.nt = q; } else { r.type = 4; r.nt = q - 32; } }
  else { int i = it - I_S, q = i % 56; r.rb = NFULL + i / 56;
    if (q < 32) { r.type = 3; r.nt = q; }
    else if (q < 48) { r.type = 6; r.nt = (q - 32) >> 3; r.ks = (q - 32) & 7; }
    else { r.type = 5; r.nt = q - 48; } }
  return r;
}
__device__ __forceinline__ float gelu_t(float x) { float u = 0.7978845608028654f * (x + 0.044715f * x * x * x); float th; asm("tanh.approx.f32 %0, %1;" : "=f"(th) : "f"(u)); float hx = 0.5f * x; return fmaf(hx, th, hx); }

__device__ __forceinline__ void bulk(uint32_t sb, const Maps& mp, const bf16* __restrict__ x, const bf16* __restrict__ b1, const bf16* __restrict__ b2, bf16* __restrict__ out) {
  const int tid = threadIdx.x, warp = tid >> 5, lane = tid & 31, g = lane >> 2, t = lane & 3;
  const int bid = blockIdx.x - NREC;
  const uint32_t full = sb + B_BAR, empty = sb + B_BAR + 32, ifull = sb + B_BAR + 64, iempty = sb + B_BAR + 80;
  volatile int* ring = (volatile int*)(__cvta_shared_to_generic(sb + B_BAR + 96));
  if (warp >= 8) {
    asm volatile("setmaxnreg.dec.sync.aligned.u32 40;");
    if (tid == 256) {
      uint32_t st = 0, ph = 0;
      for (int n = 0;; n++) {
        int it = n == 0 ? bid : NBULK + atomicAdd(&g_fl.next, 1);
        Item I = decode(it);
        if (it < I_END) {
          if (I.type == 5) { wait_flag(&g_fl.s[I.rb][0], 16); wait_flag(&g_fl.z[I.rb][0], 1); wait_flag(&g_fl.z[I.rb][1], 1); }
          else if (I.type == 3) { wait_flag(&g_fl.tile[I.rb][I.nt >> 1], 1); wait_flag(&g_fl.tile[I.rb][16 + (I.nt >> 1)], 1); wait_flag(&g_fl.tile[I.rb][32 + (I.nt >> 1)], 1); fence_async();
            for (int m = 0; m < 3; m++) {
              mbar_wait(empty + st * 8, ph ^ 1);
              mbar_expect(full + st * 8, 32768);
              int col = (m == 0 ? 8192 : (m == 1 ? 0 : 4096)) + I.nt * 128;
              tma2d(sb + st * 49152, &mp.qkv, col, I.rb * 128, full + st * 8);
              tma2d(sb + st * 49152 + 16384, &mp.qkv, col + 64, I.rb * 128, full + st * 8);
              if (++st == 4) { st = 0; ph ^= 1; }
            }
            wait_flag(&g_fl.prog[I.rb][I.nt], 8); }
          else if (I.type == 2) { wait_flag(&g_fl.hid[I.rb], 7); fence_async(); }
          else if (I.type == 4) { wait_flag(&g_fl.z[I.rb][I.nt], 1); wait_flag(&g_fl.o[I.rb][0], 4); fence_async(); }
          else if (I.type == 6) { wait_flag(&g_fl.o[I.rb][I.ks], 4); fence_async(); }
        }
        mbar_wait(iempty + (n & 1) * 8, ((n >> 1) & 1) ^ 1);
        ring[n & 1] = it; mbar_arrive(ifull + (n & 1) * 8);
        if (it >= I_END) break;
        if (I.type == 5 || I.type == 3) continue;
        const CUtensorMap *ma, *mb; int nkb = 8, kb0 = 0, n0;
        if (I.type == 0) { ma = &mp.xn; mb = I.nt < 16 ? &mp.wk : (I.nt < 32 ? &mp.wv : &mp.wq); n0 = (I.nt & 15) * 256; }
        else if (I.type == 1) { ma = &mp.y; mb = &mp.w1; n0 = I.nt * 256; }
        else if (I.type == 2) { ma = &mp.hid; mb = &mp.w2; n0 = I.nt * 256; nkb = 28; }
        else { ma = &mp.o; mb = &mp.wo; n0 = I.nt * 256; kb0 = I.ks * 8; if (I.type == 4) nkb = 64; }
        for (int kb = kb0; kb < kb0 + nkb; kb++) {
          if (I.type == 4 && kb && !(kb & 7)) { wait_flag(&g_fl.o[I.rb][kb >> 3], 4); fence_async(); }
          mbar_wait(empty + st * 8, ph ^ 1);
          mbar_expect(full + st * 8, 49152);
          uint32_t sa = sb + st * 49152;
          tma2d(sa, ma, kb * 64, I.rb * 128, full + st * 8);
          #pragma unroll
          for (int q = 0; q < 4; q++) tma2d(sa + 16384 + q * 8192, mb, n0 + q * 64, kb * 64, full + st * 8);
          if (++st == 4) { st = 0; ph ^= 1; }
        }
      }
    } else if (warp == 9) {
      for (int n = 0;; n++) {
        mbar_wait(ifull + (n & 1) * 8, (n >> 1) & 1);
        int it = ring[n & 1];
        if (it >= I_END) break;
        Item I = decode(it);
        bar_sync(6 + (n & 1), 288);
        if (lane == 0) {
          if (I.type != 5 && I.type != 4) {
            fence_async(); __threadfence();
            int* f = I.type == 0 ? &g_fl.tile[I.rb][I.nt] : I.type == 1 ? &g_fl.hid[I.rb] : I.type == 2 ? &g_fl.z[I.rb][I.nt] : I.type == 3 ? &g_fl.o[I.rb][I.nt >> 2] : &g_fl.s[I.rb][0];
            atomicAdd(f, 1);
          }
          mbar_arrive(iempty + (n & 1) * 8);
        }
      }
    }
    return;
  }
  asm volatile("setmaxnreg.inc.sync.aligned.u32 232;");
  const int wg = warp >> 2;
  const uint32_t stg = sb + B_STG + warp * 2304;
  const int lm = lane >> 3, lr = lane & 7;
  uint32_t st = 0, ph = 0;
  float d[128];
  #pragma unroll 1
  for (int n = 0;; n++) {
    mbar_wait(ifull + (n & 1) * 8, (n >> 1) & 1);
    const int it = ring[n & 1];
    __syncwarp(); if (lane == 0) mbar_arrive(iempty + (n & 1) * 8);
    if (it >= I_END) break;
    Item I = decode(it);
    const int row0 = I.rb * 128 + warp * 16;
    TB(0);
    if (I.type == 5) {
      #pragma unroll
      for (int i = 0; i < 4; i++) {
        size_t off = (size_t)(I.rb * 128 + I.nt * 16 + warp * 2 + (i >> 1)) * DM + (i & 1) * 256 + lane * 8;
        const float* sp = g_sp + off + (size_t)(I.rb - NFULL) * 7 * 128 * DM - (size_t)NFULL * 128 * DM;
        float4 s0 = __ldcg((const float4*)sp), s1 = __ldcg((const float4*)(sp + 4));
        #pragma unroll
        for (int k = 1; k < 8; k++) { float4 a = __ldcg((const float4*)(sp + k * 128 * DM)), b = __ldcg((const float4*)(sp + k * 128 * DM + 4));
          s0.x += a.x; s0.y += a.y; s0.z += a.z; s0.w += a.w; s1.x += b.x; s1.y += b.y; s1.z += b.z; s1.w += b.w; }
        uint4 xv = *(const uint4*)(x + off), gv = __ldcg((const uint4*)(g_g + off));
        float sa[8] = {s0.x, s0.y, s0.z, s0.w, s1.x, s1.y, s1.z, s1.w}, r[8];
        #pragma unroll
        for (int e = 0; e < 8; e++) r[e] = __bfloat162float(((const bf16*)&xv)[e]) + rbf(rbf(sa[e]) * __bfloat162float(((const bf16*)&gv)[e]));
        *(uint4*)(out + off) = make_uint4(pack2(r[0], r[1]), pack2(r[2], r[3]), pack2(r[4], r[5]), pack2(r[6], r[7]));
      }
      bar_arrive(6 + (n & 1), 288);
      continue;
    }
    if (I.type == 3) {
      const int h = I.nt, seg = warp >> 1, half = warp & 1, step = I.rb * 4 + seg;
      uint32_t kmr[16], vmr[16];
      { const uint32_t* km = (const uint32_t*)(g_km + ((size_t)(step * 32 + h)) * 1024) + g * 64 + t;
        const uint32_t* vm = (const uint32_t*)(g_vmT + ((size_t)(step * 32 + h)) * 1024) + g * 4 + t;
        #pragma unroll
        for (int i = 0; i < 16; i++) { kmr[i] = __ldcg(km + i * 4); vmr[i] = __ldcg(vm + i * 32); } }
      uint32_t sQ = sb + st * 49152; mbar_wait(full + st * 8, ph); uint32_t eQ = empty + st * 8; if (++st == 4) { st = 0; ph ^= 1; }
      uint32_t sK = sb + st * 49152; mbar_wait(full + st * 8, ph); uint32_t eK = empty + st * 8; if (++st == 4) { st = 0; ph ^= 1; }
      float sc[5][4];
      #pragma unroll
      for (int i = 0; i < 5; i++) { sc[i][0] = sc[i][1] = sc[i][2] = sc[i][3] = 0.f; }
      #pragma unroll
      for (int ks = 0; ks < 8; ks++) {
        uint32_t a[4]; { int r = warp * 16 + 8 * (lm & 1) + lr, c8 = 2 * ks + (lm >> 1); ldsm4(a, sQ + (c8 >> 3) * 16384 + r * 128 + (((c8 & 7) ^ (r & 7)) << 4)); }
        #pragma unroll
        for (int np = 0; np < 2; np++) {
          if (np == 1 && half == 0) continue;
          uint32_t b[4]; int r = seg * 32 + 16 * np + 8 * (lm >> 1) + lr, c8 = 2 * ks + (lm & 1);
          ldsm4(b, sK + (c8 >> 3) * 16384 + r * 128 + (((c8 & 7) ^ (r & 7)) << 4));
          mma16(sc[2*np], a[0], a[1], a[2], a[3], b[0], b[1]); mma16(sc[2*np+1], a[0], a[1], a[2], a[3], b[2], b[3]);
        }
        mma16(sc[4], a[0], a[1], a[2], a[3], kmr[2*ks], kmr[2*ks+1]);
      }
      __syncwarp(); if (lane == 0) { mbar_arrive(eQ); mbar_arrive(eK); }
      const float scale = 0.08838834764831845f;
      uint32_t P[5][2];
      #pragma unroll
      for (int rr = 0; rr < 2; rr++) {
        const int qi = 16 * half + g + 8 * rr;
        float mx = -3.0e38f;
        #pragma unroll
        for (int i = 0; i < 5; i++)
          #pragma unroll
          for (int e = 0; e < 2; e++) { float v = rbf(rbf(sc[i][2*rr+e]) * scale); if (i < 4 && 8 * i + 2 * t + e > qi) v = -1.0e9f; sc[i][2*rr+e] = v; mx = fmaxf(mx, v); }
        mx = fmaxf(mx, __shfl_xor_sync(~0u, mx, 1)); mx = fmaxf(mx, __shfl_xor_sync(~0u, mx, 2));
        float sum = 0;
        #pragma unroll
        for (int i = 0; i < 5; i++)
          #pragma unroll
          for (int e = 0; e < 2; e++) { float v = __expf(sc[i][2*rr+e] - mx); sc[i][2*rr+e] = v; sum += v; }
        sum += __shfl_xor_sync(~0u, sum, 1); sum += __shfl_xor_sync(~0u, sum, 2);
        float inv = __fdividef(1.f, sum);
        #pragma unroll
        for (int i = 0; i < 5; i++) P[i][rr] = pack2(sc[i][2*rr] * inv, sc[i][2*rr+1] * inv);
      }
      uint32_t sV = sb + st * 49152; mbar_wait(full + st * 8, ph); uint32_t eV = empty + st * 8; if (++st == 4) { st = 0; ph ^= 1; }
      #pragma unroll
      for (int i = 0; i < 64; i++) d[i] = 0.f;
      #pragma unroll
      for (int n2 = 0; n2 < 8; n2++) {
        #pragma unroll
        for (int kk = 0; kk < 2; kk++) {
          if (kk == 1 && half == 0) continue;
          uint32_t b[4]; int r = seg * 32 + 16 * kk + 8 * (lm & 1) + lr, c8 = 2 * n2 + (lm >> 1);
          ldsm4t(b, sV + (c8 >> 3) * 16384 + r * 128 + (((c8 & 7) ^ (r & 7)) << 4));
          mma16(d + 8 * n2, P[2*kk][0], P[2*kk][1], P[2*kk+1][0], P[2*kk+1][1], b[0], b[1]);
          mma16(d + 8 * n2 + 4, P[2*kk][0], P[2*kk][1], P[2*kk+1][0], P[2*kk+1][1], b[2], b[3]);
        }
        mma8(d + 8 * n2, P[4][0], P[4][1], vmr[2*n2]); mma8(d + 8 * n2 + 4, P[4][0], P[4][1], vmr[2*n2+1]);
      }
      __syncwarp(); if (lane == 0) mbar_arrive(eV);
      #pragma unroll
      for (int ch = 0; ch < 2; ch++) {
        #pragma unroll
        for (int i = 0; i < 8; i++) { const float* a = d + ch * 32 + i * 4;
          sts32(stg + g * 144 + i * 16 + t * 4, pack2(a[0], a[1])); sts32(stg + (g + 8) * 144 + i * 16 + t * 4, pack2(a[2], a[3])); }
        __syncwarp();
        #pragma unroll
        for (int i = 0; i < 4; i++) { int r = i * 4 + lm; uint4 v = lds128(stg + r * 144 + lr * 16);
          *(uint4*)(g_o + (size_t)(row0 + r) * 4096 + h * 128 + ch * 64 + lr * 8) = v; }
        __syncwarp();
      }
      bar_arrive(6 + (n & 1), 288);
      continue;
    }
    const int nkb = I.type == 2 ? 28 : I.type == 4 ? 64 : 8;
    uint32_t prev = 0;
    for (int kb = 0; kb < nkb; kb++) {
      mbar_wait(full + st * 8, ph);
      uint32_t sa = sb + st * 49152;
      asm volatile("wgmma.fence.sync.aligned;" ::: "memory");
      #pragma unroll
      for (int k = 0; k < 4; k++)
        wgmma256(d, mkdesc(sa + wg * 8192 + k * 32, 16, 1024), mkdesc(sa + 16384 + k * 2048, 8192, 1024), (kb | k) != 0);
      asm volatile("wgmma.commit_group.sync.aligned;" ::: "memory");
      if (kb > 0) { asm volatile("wgmma.wait_group.sync.aligned 1;" ::: "memory"); if (lane == 0) mbar_arrive(prev); }
      prev = empty + st * 8;
      if (++st == 4) { st = 0; ph ^= 1; }
    }
    asm volatile("wgmma.wait_group.sync.aligned 0;" ::: "memory");
    if (lane == 0) mbar_arrive(prev);
    TB(1);
    auto epi = [&](auto tc) {
      constexpr int TY = decltype(tc)::v;
      bf16* dst; int ld;
      if (TY == 0) { dst = g_qkv + (size_t)row0 * QW + I.nt * 256; ld = QW; } else if (TY == 1) { dst = g_hid + (size_t)row0 * FF + I.nt * 256; ld = FF; }
      else { dst = (TY == 2 ? g_g : out) + (size_t)row0 * DM + I.nt * 256; ld = DM; }
      #pragma unroll
      for (int ch = 0; ch < 4; ch++) {
        #pragma unroll
        for (int i = 0; i < 8; i++) { float* a = d + ch * 32 + i * 4;
          if (TY == 1) { float2 bb = __bfloat1622float2(*(const __nv_bfloat162*)(b1 + I.nt * 256 + ch * 64 + i * 8 + 2 * t));
            a[0] = gelu_t(rbf(rbf(a[0]) + bb.x)); a[1] = gelu_t(rbf(rbf(a[1]) + bb.y)); a[2] = gelu_t(rbf(rbf(a[2]) + bb.x)); a[3] = gelu_t(rbf(rbf(a[3]) + bb.y)); }
          if (TY == 2) { float2 bb = __bfloat1622float2(*(const __nv_bfloat162*)(b2 + I.nt * 256 + ch * 64 + i * 8 + 2 * t));
            #pragma unroll
            for (int e = 0; e < 4; e++) { float u = rbf(rbf(a[e]) + ((e & 1) ? bb.y : bb.x)); a[e] = __fdividef(u, 1.f + __expf(-u)); } }
          sts32(stg + g * 144 + i * 16 + t * 4, pack2(a[0], a[1])); sts32(stg + (g + 8) * 144 + i * 16 + t * 4, pack2(a[2], a[3])); }
        __syncwarp();
        #pragma unroll
        for (int i = 0; i < 4; i++) { int r = i * 4 + lm; uint4 v = lds128(stg + r * 144 + lr * 16);
          if (TY == 4) { const size_t off = (size_t)(row0 + r) * DM + I.nt * 256 + ch * 64 + lr * 8;
            uint4 xv = *(const uint4*)(x + off), gv = __ldcg((const uint4*)(g_g + off)); float q[8];
            #pragma unroll
            for (int e = 0; e < 8; e++) q[e] = __bfloat162float(((const bf16*)&xv)[e]) + rbf(__bfloat162float(((const bf16*)&v)[e]) * __bfloat162float(((const bf16*)&gv)[e]));
            v = make_uint4(pack2(q[0], q[1]), pack2(q[2], q[3]), pack2(q[4], q[5]), pack2(q[6], q[7])); }
          *(uint4*)(dst + (size_t)r * ld + ch * 64 + lr * 8) = v; }
        __syncwarp();
      }
    };
    if (I.type == 0) epi(IC<0>{}); else if (I.type == 1) epi(IC<1>{}); else if (I.type == 2) epi(IC<2>{}); else if (I.type == 4) epi(IC<4>{});
    else {
      float* dst = g_sp + ((size_t)((I.rb - NFULL) * 8 + I.ks) * 128 + warp * 16 + g) * DM + I.nt * 256 + 2 * t;
      #pragma unroll
      for (int i = 0; i < 32; i++) {
        asm volatile("st.global.cg.v2.f32 [%0], {%1,%2};" ::"l"(dst + i * 8), "f"(d[4*i]), "f"(d[4*i+1]) : "memory");
        asm volatile("st.global.cg.v2.f32 [%0], {%1,%2};" ::"l"(dst + 8 * DM + i * 8), "f"(d[4*i+2]), "f"(d[4*i+3]) : "memory");
      }
    }
    bar_arrive(6 + (n & 1), 288);
  }
}

__global__ void __cluster_dims__(2, 1, 1) __launch_bounds__(384, 1)
main_kernel(const __grid_constant__ Maps mp, const bf16* x, const bf16* Wq, const bf16* Wk, const bf16* Wv, const bf16* Wo, const bf16* b1, const bf16* b2, bf16* out) {
  const uint32_t sb = smem_u32(smem_raw);
  if (sb & 1023) __trap();
  if (threadIdx.x == 0) {
    if (blockIdx.x < NREC) { mbar_init(sb + R_BAR, 1); mbar_init(sb + R_BAR + 8, 1); mbar_init(sb + R_BAR + 16, 1); }
    else { for (int i = 0; i < 4; i++) { mbar_init(sb + B_BAR + i * 8, 1); mbar_init(sb + B_BAR + 32 + i * 8, 8); }
      for (int i = 0; i < 2; i++) { mbar_init(sb + B_BAR + 64 + i * 8, 1); mbar_init(sb + B_BAR + 80 + i * 8, 9); } }
    asm volatile("fence.mbarrier_init.release.cluster;" ::: "memory");
  }
  asm volatile("barrier.cluster.arrive.release.aligned; barrier.cluster.wait.acquire.aligned;" ::: "memory");
  if (blockIdx.x < NREC) recurrence(sb, Wq, Wk, Wv, Wo);
  else bulk(sb, mp, x, b1, b2, out);
}

typedef CUresult (*EncFn)(CUtensorMap*, CUtensorMapDataType, cuuint32_t, void*, const cuuint64_t*, const cuuint64_t*, const cuuint32_t*, const cuuint32_t*, CUtensorMapInterleave, CUtensorMapSwizzle, CUtensorMapL2promotion, CUtensorMapFloatOOBfill);
static void mk(EncFn f, CUtensorMap* m, const void* p, uint64_t rows, uint64_t cols, uint32_t boxr) {
  cuuint64_t dims[2] = {cols, rows}, str[1] = {cols * 2}; cuuint32_t box[2] = {64, boxr}, es[2] = {1, 1};
  f(m, CU_TENSOR_MAP_DATA_TYPE_BFLOAT16, 2, (void*)p, dims, str, box, es, CU_TENSOR_MAP_INTERLEAVE_NONE, CU_TENSOR_MAP_SWIZZLE_128B, CU_TENSOR_MAP_L2_PROMOTION_L2_256B, CU_TENSOR_MAP_FLOAT_OOB_FILL_NONE);
}
extern "C" void kernel_launch(void* const* d_in, const int* in_sizes, int n_in, void* d_out, int out_size) {
  const bf16 *x = (const bf16*)d_in[0], *mem0 = (const bf16*)d_in[1], *Wq = (const bf16*)d_in[2], *Wk = (const bf16*)d_in[3], *Wv = (const bf16*)d_in[4], *Wo = (const bf16*)d_in[5];
  const bf16 *w1 = (const bf16*)d_in[8], *b1 = (const bf16*)d_in[9], *w2 = (const bf16*)d_in[10], *b2 = (const bf16*)d_in[11];
  void* fn = nullptr; cudaDriverEntryPointQueryResult qr;
  cudaGetDriverEntryPoint("cuTensorMapEncodeTiled", &fn, cudaEnableDefault, &qr);
  EncFn f = (EncFn)fn;
  void *pxn, *py, *ph, *po, *pq;
  cudaGetSymbolAddress(&pxn, g_xn); cudaGetSymbolAddress(&py, g_y); cudaGetSymbolAddress(&ph, g_hid); cudaGetSymbolAddress(&po, g_o); cudaGetSymbolAddress(&pq, g_qkv);
  Maps mp;
  mk(f, &mp.xn, pxn, SEQ, DM, 128); mk(f, &mp.y, py, SEQ, DM, 128); mk(f, &mp.hid, ph, SEQ, FF, 128); mk(f, &mp.o, po, SEQ, 4096, 128); mk(f, &mp.qkv, pq, SEQ, QW, 128);
  mk(f, &mp.wk, Wk, DM, 4096, 64); mk(f, &mp.wv, Wv, DM, 4096, 64); mk(f, &mp.wq, Wq, DM, 4096, 64);
  mk(f, &mp.w1, w1, DM, FF, 64); mk(f, &mp.w2, w2, FF, DM, 64); mk(f, &mp.wo, Wo, 4096, DM, 64);
  cudaFuncSetAttribute(main_kernel, cudaFuncAttributeMaxDynamicSharedMemorySize, SMEM_BYTES);
  prologue_kernel<<<256, 256, 0, cudaStreamPerThread>>>(x, mem0, Wq, Wk, Wv, Wo);
  main_kernel<<<NCTA, 384, SMEM_BYTES, cudaStreamPerThread>>>(mp, x, Wq, Wk, Wv, Wo, b1, b2, (bf16*)d_out);
}
```

```cpp
#include <cuda_runtime.h>
#include <cuda_bf16.h>
#include <cuda.h>
#include <stdint.h>

typedef __nv_bfloat16 bf16;
constexpr int SEQ = 2048, DM = 512, FF = 1792, QW = 12288, NSTEP = 64;
constexpr int NREC = 64, NBULK = 68, NCTA = 132;
constexpr int SPIN_LIMIT = 1 << 22;
#define THR 4
#define PDELAY 500

__device__ bf16 g_xn[SEQ * DM];
__device__ bf16 g_y[SEQ * DM];
__device__ bf16 g_qkv[(size_t)SEQ * QW];
__device__ bf16 g_hid[SEQ * FF];
__device__ bf16 g_o[(size_t)SEQ * 4096];
#define NFULL 12
__device__ bf16 g_g[SEQ * DM];
__device__ float g_sp[(16 - NFULL) * 8 * 128 * DM];
__device__ float4 g_acc[NSTEP][2][768];
__device__ bf16 g_km[NSTEP * 32 * 8 * 128];
__device__ bf16 g_vmT[NSTEP * 32 * 128 * 8];
struct Flags { int tile[16][48]; int hid[16]; int z[16][2]; int o[16][8]; int s[16][2]; int prog[16][32]; int next; int role[2]; };
__device__ Flags g_fl;

#define TR(i)
#define TB(i)
#define TI(i)
struct Maps { CUtensorMap xn, y, hid, o, qkv, wk, wv, wq, w1, w2, wo; };

extern __shared__ __align__(1024) uint8_t smem_raw[];
__device__ __forceinline__ uint4 ldc(uint32_t off) { return *(const uint4*)(smem_raw + off); }
__device__ __forceinline__ uint32_t smem_u32(const void* p) { return (uint32_t)__cvta_generic_to_shared(p); }
__device__ __forceinline__ int otid() { int t; asm volatile("mov.u32 %0, %%tid.x;" : "=r"(t)); return t; }
__device__ __forceinline__ uint32_t mapa(uint32_t a, uint32_t r) { uint32_t o; asm volatile("mapa.shared::cluster.u32 %0, %1, %2;" : "=r"(o) : "r"(a), "r"(r)); return o; }
__device__ __forceinline__ void st_async_v4(uint32_t addr, float a, float b, float c, float d, uint32_t mbar) {
  asm volatile("st.async.weak.shared::cluster.mbarrier::complete_tx::bytes.v4.b32 [%0], {%1,%2,%3,%4}, [%5];" ::"r"(addr), "r"(__float_as_uint(a)), "r"(__float_as_uint(b)), "r"(__float_as_uint(c)), "r"(__float_as_uint(d)), "r"(mbar) : "memory"); }
__device__ __forceinline__ void mbar_init(uint32_t m, int c) { asm volatile("mbarrier.init.shared::cta.b64 [%0], %1;" ::"r"(m), "r"(c) : "memory"); }
__device__ __forceinline__ void mbar_expect(uint32_t m, int bytes) { asm volatile("mbarrier.arrive.expect_tx.shared::cta.b64 _, [%0], %1;" ::"r"(m), "r"(bytes) : "memory"); }
__device__ __forceinline__ void mbar_arrive(uint32_t m) { asm volatile("mbarrier.arrive.shared::cta.b64 _, [%0];" ::"r"(m) : "memory"); }
__device__ __forceinline__ void mbar_wait(uint32_t m, uint32_t parity) {
  uint32_t ok; int it = 0;
  do { asm volatile("{.reg .pred p; mbarrier.try_wait.parity.shared::cta.b64 p, [%1], %2; selp.u32 %0,1,0,p;}" : "=r"(ok) : "r"(m), "r"(parity) : "memory"); } while (!ok && ++it < SPIN_LIMIT); }
__device__ __forceinline__ void mbar_spin(uint32_t m, uint32_t parity) {
  uint32_t ok; int it = 0;
  do { asm volatile("{.reg .pred p; mbarrier.test_wait.parity.shared::cta.b64 p, [%1], %2; selp.u32 %0,1,0,p;}" : "=r"(ok) : "r"(m), "r"(parity) : "memory"); } while (!ok && ++it < SPIN_LIMIT); }
__device__ __forceinline__ void bar_sync(int id, int n) { asm volatile("bar.sync %0, %1;" ::"r"(id), "r"(n) : "memory"); }
__device__ __forceinline__ void bar_arrive(int id, int n) { asm volatile("bar.arrive %0, %1;" ::"r"(id), "r"(n) : "memory"); }
__device__ __forceinline__ int ld_acq(const int* p) { int v; asm volatile("ld.acquire.gpu.global.s32 %0, [%1];" : "=r"(v) : "l"(p) : "memory"); return v; }
__device__ __forceinline__ void wait_flag(const int* p, int target) { int it = 0; while (ld_acq(p) < target && ++it < SPIN_LIMIT) { __nanosleep(40); } }
__device__ __forceinline__ void fence_async() { asm volatile("fence.proxy.async.global;" ::: "memory"); }
__device__ __forceinline__ uint4 lds128(uint32_t a) { uint4 v; asm volatile("ld.shared.v4.u32 {%0,%1,%2,%3}, [%4];" : "=r"(v.x), "=r"(v.y), "=r"(v.z), "=r"(v.w) : "r"(a) : "memory"); return v; }
__device__ __forceinline__ void sts128(uint32_t a, uint4 v) { asm volatile("st.shared.v4.u32 [%0], {%1,%2,%3,%4};" ::"r"(a), "r"(v.x), "r"(v.y), "r"(v.z), "r"(v.w) : "memory"); }
__device__ __forceinline__ void sts32(uint32_t a, uint32_t v) { asm volatile("st.shared.u32 [%0], %1;" ::"r"(a), "r"(v) : "memory"); }
__device__ __forceinline__ void sts16(uint32_t a, float f) { unsigned short h = __bfloat16_as_ushort(__float2bfloat16(f)); asm volatile("st.shared.u16 [%0], %1;" ::"r"(a), "h"(h) : "memory"); }
__device__ __forceinline__ void ldsm4(uint32_t* r, uint32_t a) { asm volatile("ldmatrix.sync.aligned.m8n8.x4.shared.b16 {%0,%1,%2,%3}, [%4];" : "=r"(r[0]), "=r"(r[1]), "=r"(r[2]), "=r"(r[3]) : "r"(a) : "memory"); }
__device__ __forceinline__ void ldsm4t(uint32_t* r, uint32_t a) { asm volatile("ldmatrix.sync.aligned.m8n8.x4.trans.shared.b16 {%0,%1,%2,%3}, [%4];" : "=r"(r[0]), "=r"(r[1]), "=r"(r[2]), "=r"(r[3]) : "r"(a) : "memory"); }
__device__ __forceinline__ void mma16(float* c, uint32_t a0, uint32_t a1, uint32_t a2, uint32_t a3, uint32_t b0, uint32_t b1) {
  asm("mma.sync.aligned.m16n8k16.row.col.f32.bf16.bf16.f32 {%0,%1,%2,%3}, {%4,%5,%6,%7}, {%8,%9}, {%0,%1,%2,%3};" : "+f"(c[0]), "+f"(c[1]), "+f"(c[2]), "+f"(c[3]) : "r"(a0), "r"(a1), "r"(a2), "r"(a3), "r"(b0), "r"(b1)); }
__device__ __forceinline__ void mma8(float* c, uint32_t a0, uint32_t a1, uint32_t b0) {
  asm("mma.sync.aligned.m16n8k8.row.col.f32.bf16.bf16.f32 {%0,%1,%2,%3}, {%4,%5}, {%6}, {%0,%1,%2,%3};" : "+f"(c[0]), "+f"(c[1]), "+f"(c[2]), "+f"(c[3]) : "r"(a0), "r"(a1), "r"(b0)); }
__device__ __forceinline__ uint32_t pack2(float a, float b) { __nv_bfloat162 h = __floats2bfloat162_rn(a, b); return *(uint32_t*)&h; }
__device__ __forceinline__ float rbf(float x) { uint32_t r; asm("cvt.rn.bf16x2.f32 %0, %1, %2;" : "=r"(r) : "f"(x), "f"(0.f)); return __uint_as_float(r); }
__device__ __forceinline__ void cp16(uint32_t d, const void* s) { asm volatile("cp.async.cg.shared.global [%0], [%1], 16;" ::"r"(d), "l"(s) : "memory"); }
__device__ __forceinline__ void tma2d(uint32_t dst, const CUtensorMap* m, int c0, int c1, uint32_t mbar) {
  asm volatile("cp.async.bulk.tensor.2d.shared::cluster.global.mbarrier::complete_tx::bytes [%0], [%1, {%2,%3}], [%4];" ::"r"(dst), "l"(m), "r"(c0), "r"(c1), "r"(mbar) : "memory"); }
__device__ __forceinline__ uint64_t mkdesc(uint32_t addr, uint32_t lbo, uint32_t sbo) {
  return (uint64_t)((addr & 0x3FFFF) >> 4) | ((uint64_t)(lbo >> 4) << 16) | ((uint64_t)(sbo >> 4) << 32) | (1ull << 62); }

#define R8(i) "+f"(d[i]), "+f"(d[i+1]), "+f"(d[i+2]), "+f"(d[i+3]), "+f"(d[i+4]), "+f"(d[i+5]), "+f"(d[i+6]), "+f"(d[i+7])
__device__ __forceinline__ void wgmma256(float* d, uint64_t da, uint64_t db, int acc) {
  asm volatile("{.reg .pred p; setp.ne.b32 p, %130, 0;\n"
    "wgmma.mma_async.sync.aligned.m64n256k16.f32.bf16.bf16 {"
    "%0,%1,%2,%3,%4,%5,%6,%7,%8,%9,%10,%11,%12,%13,%14,%15,%16,%17,%18,%19,%20,%21,%22,%23,%24,%25,%26,%27,%28,%29,%30,%31,"
    "%32,%33,%34,%35,%36,%37,%38,%39,%40,%41,%42,%43,%44,%45,%46,%47,%48,%49,%50,%51,%52,%53,%54,%55,%56,%57,%58,%59,%60,%61,%62,%63,"
    "%64,%65,%66,%67,%68,%69,%70,%71,%72,%73,%74,%75,%76,%77,%78,%79,%80,%81,%82,%83,%84,%85,%86,%87,%88,%89,%90,%91,%92,%93,%94,%95,"
    "%96,%97,%98,%99,%100,%101,%102,%103,%104,%105,%106,%107,%108,%109,%110,%111,%112,%113,%114,%115,%116,%117,%118,%119,%120,%121,%122,%123,%124,%125,%126,%127"
    "}, %128, %129, p, 1, 1, 0, 1;}"
    : R8(0), R8(8), R8(16), R8(24), R8(32), R8(40), R8(48), R8(56), R8(64), R8(72), R8(80), R8(88), R8(96), R8(104), R8(112), R8(120)
    : "l"(da), "l"(db), "r"(acc)); }

__global__ void __launch_bounds__(256) prologue_kernel(const bf16* __restrict__ x, const bf16* __restrict__ mem0, const bf16* Wq, const bf16* Wk, const bf16* Wv, const bf16* Wo) {
  int tid = threadIdx.x, lane = tid & 31, warp = tid >> 5;
  asm volatile("griddepcontrol.launch_dependents;");
  { const int gt = blockIdx.x * 256 + tid; const size_t o = (size_t)(gt & 32767) * 64;
    asm volatile("prefetch.global.L2 [%0];" ::"l"((gt < 32768 ? Wk : Wv) + o));
    asm volatile("prefetch.global.L2 [%0];" ::"l"((gt < 32768 ? Wq : Wo) + o)); }
  int row = blockIdx.x * 8 + warp;
  {
    const uint4* src = (const uint4*)(x + (size_t)row * DM);
    uint4 u[2] = { src[lane], src[lane + 32] };
    float v[16];
    #pragma unroll
    for (int i = 0; i < 2; i++) { const __nv_bfloat162* h = (const __nv_bfloat162*)&u[i];
      #pragma unroll
      for (int k = 0; k < 4; k++) { float2 f = __bfloat1622float2(h[k]); v[i * 8 + 2 * k] = f.x; v[i * 8 + 2 * k + 1] = f.y; } }
    #pragma unroll
    for (int pass = 0; pass < 2; pass++) {
      float s = 0;
      #pragma unroll
      for (int i = 0; i < 16; i++) s += v[i];
      #pragma unroll
      for (int o = 16; o; o >>= 1) s += __shfl_xor_sync(~0u, s, o);
      float mf = s * (1.f / DM);
      float q = 0;
      #pragma unroll
      for (int i = 0; i < 16; i++) { float dd = v[i] - mf; q += dd * dd; }
      #pragma unroll
      for (int o = 16; o; o >>= 1) q += __shfl_xor_sync(~0u, q, o);
      float m = rbf(mf), var = rbf(q * (1.f / DM));
      float den = rbf(sqrtf(rbf(var + 1e-5f)));
      #pragma unroll
      for (int i = 0; i < 16; i++) v[i] = rbf(rbf(v[i] - m) / den);
      uint4 o4[2];
      #pragma unroll
      for (int i = 0; i < 2; i++) { o4[i].x = pack2(v[i*8], v[i*8+1]); o4[i].y = pack2(v[i*8+2], v[i*8+3]); o4[i].z = pack2(v[i*8+4], v[i*8+5]); o4[i].w = pack2(v[i*8+6], v[i*8+7]); }
      uint4* dst = (uint4*)((pass ? g_y : g_xn) + (size_t)row * DM);
      dst[lane] = o4[0]; dst[lane + 32] = o4[1];
    }
  }
  int gt = blockIdx.x * 256 + tid;
  float4 z4 = make_float4(0, 0, 0, 0);
  for (int i = gt; i < NSTEP * 1536; i += 65536) {
    float4 val = z4;
    if (i < 1536) {
      int j = i / 768, c = i % 768, ci = c >> 8, w = (c & 255) >> 5, l = c & 31, g = l >> 2, t = l & 3;
      float e3[3];
      #pragma unroll
      for (int k = 0; k < 3; k++) { int e = ci * 3 + k; int mt = e >> 2, cc = e & 3;
        e3[k] = e < 8 ? __bfloat162float(mem0[(2 * t + (cc & 1)) * DM + 256 * j + 32 * w + 16 * mt + g + 8 * (cc >> 1)]) : 0.f; }
      val = make_float4(e3[0], e3[1], e3[2], 32.f);
    }
    (&g_acc[0][0][0])[i] = val;
  }
  if (gt < (int)(sizeof(Flags) / 4)) ((int*)&g_fl)[gt] = 0;
}

__device__ __forceinline__ int vbid() { return *(volatile int*)(smem_raw + 232448 - 32) * 2 + (blockIdx.x & 1); }
constexpr int R_WR = 0, R_WO = 65536, R_KT = 131072, KT_SZ = 40 * 256, R_VT = R_KT + 2 * KT_SZ, VT_SZ = 40 * 272,
              R_MEM = R_VT + 2 * VT_SZ, R_Q = R_MEM + 32 * 160, R_O = R_Q + 8 * 256, R_S = R_O + 8 * 256,
              R_SM = R_S + 8 * 40 * 4, R_RQK = R_SM + 1024, R_RV = R_RQK + 8192, R_WQ = R_RV + 4096, R_BAR = 232448 - 64, R_END = R_BAR + 64;
static_assert(R_WQ + 32768 <= R_BAR, "smem");
#define PI 0
#define LD1(v, p) asm volatile("ld.relaxed.gpu.global.v4.u32 {%0,%1,%2,%3}, [%4];" : "=r"(v.x), "=r"(v.y), "=r"(v.z), "=r"(v.w) : "l"(p) : "memory")
#define LD3(a, b, c) do { LD1(a, src + ((EXP & 2) ? 256 * (h % 3) : 0)); if (EXP & 2) { b = a; c = a; } else { LD1(b, src + 256); LD1(c, src + 512); } } while (0)
#define OK3(a, b, c) __all_sync(~0u, (a.w == 0x42000000u) && (b.w == 0x42000000u) && (c.w == 0x42000000u))
#define W7D 1100
#define THR0 8
#define NW0 8
#define VD 0
#define KD 80
#define VCH 2
#define VP 6
__device__ __forceinline__ void wgmma8(float* d, uint64_t da, uint64_t db, int acc) {
  asm volatile("{.reg .pred p; setp.ne.b32 p, %6, 0;\n wgmma.mma_async.sync.aligned.m64n8k16.f32.bf16.bf16 {%0,%1,%2,%3}, %4, %5, p, 1, 1, 0, 0;}"
    : "+f"(d[0]), "+f"(d[1]), "+f"(d[2]), "+f"(d[3]) : "l"(da), "l"(db), "r"(acc)); }
__device__ __forceinline__ void stsm4(uint32_t a, uint32_t r0, uint32_t r1, uint32_t r2, uint32_t r3) { asm volatile("stmatrix.sync.aligned.m8n8.x4.shared.b16 [%0], {%1,%2,%3,%4};" ::"r"(a), "r"(r0), "r"(r1), "r"(r2), "r"(r3) : "memory"); }
__device__ __forceinline__ uint32_t swz(uint32_t r) { return ((r & 1) << 2) | ((r >> 1) & 3); }
__device__ __forceinline__ void stsm4t(uint32_t a, uint32_t r0, uint32_t r1, uint32_t r2, uint32_t r3) { asm volatile("stmatrix.sync.aligned.m8n8.x4.trans.shared.b16 [%0], {%1,%2,%3,%4};" ::"r"(a), "r"(r0), "r"(r1), "r"(r2), "r"(r3) : "memory"); }
__device__ __forceinline__ void stsm2(uint32_t a, uint32_t r0, uint32_t r1) { asm volatile("stmatrix.sync.aligned.m8n8.x2.shared.b16 [%0], {%1,%2};" ::"r"(a), "r"(r0), "r"(r1) : "memory"); }
__device__ __forceinline__ float ex2(float x) { float r; asm("ex2.approx.ftz.f32 %0, %1;" : "=f"(r) : "f"(x)); return r; }
#define REDV4(p, a, b, c) asm volatile("red.relaxed.gpu.global.add.v4.f32 [%0], {%1,%2,%3,%4};" ::"l"(p), "f"(a), "f"(b), "f"(c), "f"(RCNT) : "memory")
#define EXP 0
#define RCNT ((EXP & 1) ? 4.0f : 1.0f)
constexpr int SMEM_BYTES = 232448;
static_assert(R_END <= SMEM_BYTES, "smem");

__device__ __forceinline__ void recurrence(uint32_t sb, const bf16* __restrict__ Wq, const bf16* __restrict__ Wk, const bf16* __restrict__ Wv, const bf16* __restrict__ Wo) {
  const int tid = threadIdx.x, warp = tid >> 5, lane = tid & 31, g = lane >> 2, t = lane & 3;
  const int h = vbid() >> 1, j = blockIdx.x & 1;
  const uint32_t peer = j ^ 1;
  const uint32_t mQ = sb + R_BAR, mV = sb + R_BAR + 8, mK = sb + R_BAR + 16;
  uint32_t A[2][16][4];
  TI(1);
  const int lm = lane >> 3, lr = lane & 7;
  for (int i = tid; i < 256 * 16; i += 384) { const int r = i >> 4, c = i & 15; const size_t o = ((size_t)(256 * j + r)) * 4096 + h * 128 + c * 8;
    const uint32_t d = sb + r * 256 + ((c ^ ((r & 1) | ((r >> 2) & 6))) << 4);
    cp16(d + 131072, Wq + o); cp16(d + 65536, Wk + o); cp16(d, Wv + o); }
  auto ldwo = [&](int half, uint32_t st) {
    for (int i = tid; i < 64 * 32; i += 384) { const int r = i >> 5, c = i & 31;
      cp16(st + r * 512 + ((c ^ ((r & 1) | ((r >> 2) & 6))) << 4), Wo + ((size_t)(h * 128 + 64 * half + r)) * DM + 256 * j + c * 8); } };
  auto cvwo = [&](int half, uint32_t st) {
    if (warp < 8) {
      #pragma unroll
      for (int i = 0; i < 8; i++) { const int wv = warp >> 1, mt = warp & 1, kq = i & 3, hi = i >> 2;
        const int k = 32 * (kq >> 1) + 8 * (lr >> 1) + (lr & 1) + 4 * (kq & 1) + 2 * (lm >> 1); uint32_t r[4];
        ldsm4t(r, st + k * 512 + (((8 * wv + 4 * mt + 2 * hi + (lm & 1)) ^ lr) << 4));
        sts128(sb + R_WO + ((wv * 32 + mt * 16 + hi * 8 + half * 4 + kq) * 32 + lane) * 16, make_uint4(r[0], r[1], r[2], r[3])); }
    } };
  ldwo(0, sb + 196608);
  asm volatile("cp.async.wait_all;" ::: "memory"); __syncthreads();
  TI(2);
  { const uint32_t st = sb + (2 - (warp >> 2)) * 65536;
    #pragma unroll
    for (int mt = 0; mt < 2; mt++)
      #pragma unroll
      for (int ks = 0; ks < 16; ks++) {
        const int k = 32 * (ks >> 1) + 8 * (lr >> 1) + (lr & 1) + 4 * (ks & 1) + 2 * (lm >> 1);
        ldsm4t(A[mt][ks], st + k * 256 + (((4 * (warp & 3) + 2 * mt + (lm & 1)) ^ lr) << 4));
      } }
  __syncthreads();
  TI(3);
  ldwo(1, sb + 131072);
  cvwo(0, sb + 196608);
  if (warp >= 8) {
    #pragma unroll
    for (int i = 0; i < 32; i++) sts128(sb + R_WR + (((warp - 8) * 32 + i) * 32 + lane) * 16, make_uint4(A[i & 1][i >> 1][0], A[i & 1][i >> 1][1], A[i & 1][i >> 1][2], A[i & 1][i >> 1][3]));
  }
  asm volatile("cp.async.wait_all;" ::: "memory"); __syncthreads();
  TI(4);
  cvwo(1, sb + 131072);
  if (warp < 4) {
    #pragma unroll
    for (int i = 0; i < 16; i++) sts128(sb + R_WQ + ((warp * 16 + i) * 32 + lane) * 16, make_uint4(A[1][i][0], A[1][i][1], A[1][i][2], A[1][i][3]));
  }
  asm volatile("griddepcontrol.wait;" ::: "memory");
  __syncthreads();
  if (warp >= 8) {
    const uint32_t zero = blockIdx.y;
    #pragma unroll 1
    for (int s = 0; s < NSTEP; s++) {
      const int tid = otid(), lane = tid & 31, wv = (tid >> 5) - 8, g = lane >> 2, t = lane & 3;
      if (tid == 256) mbar_expect(mV, 4096);
      const uint32_t fo = (t ^ swz(g)) << 4;
      TR(1);
      bar_sync(4, 384);
      if (VD) { long long t0 = clock64(); while (clock64() - t0 < VD); }
      TR(2);
      float c[4][4];
      #pragma unroll
      for (int i = 0; i < 4; i++) { c[i][0] = c[i][1] = c[i][2] = c[i][3] = 0.f; }
      #pragma unroll
      for (int p = 0; p < 8; p++) {
        uint4 b = ldc(R_MEM + g * 16 + t * 160 + p * 640);
        mma16(c[0], A[0][2*p][0], A[0][2*p][1], A[0][2*p][2], A[0][2*p][3], b.x, b.y);
        mma16(c[1], A[1][2*p][0], A[1][2*p][1], A[1][2*p][2], A[1][2*p][3], b.x, b.y);
        mma16(c[2], A[0][2*p+1][0], A[0][2*p+1][1], A[0][2*p+1][2], A[0][2*p+1][3], b.z, b.w);
        mma16(c[3], A[1][2*p+1][0], A[1][2*p+1][1], A[1][2*p+1][2], A[1][2*p+1][3], b.z, b.w);
      }
      #pragma unroll
      for (int i = 0; i < 4; i++) { c[0][i] += c[2][i]; c[1][i] += c[3][i]; }
      const uint32_t rx = sb + R_RV + (wv * 64 + lane) * 16;
      { uint32_t ra = mapa(rx, peer), rm = mapa(mV, peer);
        st_async_v4(ra, c[0][0], c[0][1], c[0][2], c[0][3], rm);
        st_async_v4(ra + 512, c[1][0], c[1][1], c[1][2], c[1][3], rm); }
      TR(4);
      const bool more = s < NSTEP - 1;
      uint32_t wb = sb + (wv * 1024 + lane) * 16;
      #pragma unroll
      for (int i = 0; i < NW0; i++) { uint4 v = lds128(wb + R_WO + i * 512); A[i >> 4][i & 15][0] = v.x; A[i >> 4][i & 15][1] = v.y; A[i >> 4][i & 15][2] = v.z; A[i >> 4][i & 15][3] = v.w;
        if ((i % THR0) == THR0 - 1) wb += v.x & zero; }
      TR(3);
      mbar_wait(mV, s & 1);
      TR(5);
      { uint4 r0 = lds128(rx), r1 = lds128(rx + 512);
        stsm4t(sb + R_VT + (s & 1) * VT_SZ + (32 + (lane & 7)) * 272 + (4 * wv + (lane >> 3)) * 16,
          pack2(c[0][0] + __uint_as_float(r0.x), c[0][1] + __uint_as_float(r0.y)), pack2(c[0][2] + __uint_as_float(r0.z), c[0][3] + __uint_as_float(r0.w)),
          pack2(c[1][0] + __uint_as_float(r1.x), c[1][1] + __uint_as_float(r1.y)), pack2(c[1][2] + __uint_as_float(r1.z), c[1][3] + __uint_as_float(r1.w))); }
      if (more) {
      bar_arrive(3, 256);
      TR(8);
      #pragma unroll
      for (int i = NW0; i < 32; i++) { uint4 v = lds128(wb + R_WO + i * 512); A[i >> 4][i & 15][0] = v.x; A[i >> 4][i & 15][1] = v.y; A[i >> 4][i & 15][2] = v.z; A[i >> 4][i & 15][3] = v.w;
        if ((i % THR) == THR - 1) wb += v.x & zero; }
      TR(10);
      bar_sync(7, 256);
      TR(9);
      #pragma unroll
      for (int i = 0; i < 4; i++) { c[i][0] = c[i][1] = c[i][2] = c[i][3] = 0.f; }
      #pragma unroll
      for (int p = 0; p < 4; p++) {
        uint4 b = ldc(R_O + g * 256 + (p >> 1) * 128 + (fo ^ ((p & 1) << 6)));
        #pragma unroll
        for (int mt = 0; mt < 4; mt++) { const uint32_t* a = A[mt >> 1][(mt & 1) * 8 + 2 * p]; mma16(c[mt], a[0], a[1], a[2], a[3], b.x, b.y); }
        #pragma unroll
        for (int mt = 0; mt < 4; mt++) { const uint32_t* a = A[mt >> 1][(mt & 1) * 8 + 2 * p + 1]; mma16(c[mt], a[0], a[1], a[2], a[3], b.z, b.w); }
      }
      TR(6);
      float4* dst = &g_acc[s + 1][j][wv * 64 + lane];
      if (!(EXP & 1) || (h & 3) == wv) {
      REDV4(dst, c[0][0], c[0][1], c[0][2]); REDV4(dst + 256, c[0][3], c[1][0], c[1][1]); REDV4(dst + 512, c[1][2], c[1][3], 0.f);
      REDV4(dst + 32, c[2][0], c[2][1], c[2][2]); REDV4(dst + 288, c[2][3], c[3][0], c[3][1]); REDV4(dst + 544, c[3][2], c[3][3], 0.f); }
      bar_arrive(8, 352);
      TR(7);
      } else bar_sync(6, 256);
      { const int vt = tid - 256;
        if (j == 0) { const int r = vt >> 4, cc = vt & 15; uint4 v = lds128(sb + R_KT + (s & 1) * KT_SZ + (32 + r) * 256 + ((cc ^ swz(r)) << 4));
          __stcg((uint4*)(g_km + ((size_t)(s * 32 + h)) * 1024) + vt, v); }
        else { uint32_t vb = sb + R_VT + (s & 1) * VT_SZ + 32 * 272 + vt * 2; uint32_t e[8];
          #pragma unroll
          for (int k = 0; k < 8; k++) { unsigned short x; asm volatile("ld.shared.u16 %0, [%1];" : "=h"(x) : "r"(vb + k * 272) : "memory"); e[k] = x; }
          __stcg((uint4*)(g_vmT + ((size_t)(s * 32 + h)) * 1024) + vt, make_uint4(e[0] | (e[1] << 16), e[2] | (e[3] << 16), e[4] | (e[5] << 16), e[6] | (e[7] << 16))); }
        if (!more) { __syncwarp(); if (lane == 0) { __threadfence(); atomicAdd(&g_fl.prog[15][h], 1); } } }
      #pragma unroll
      for (int i = 0; i < 32; i++) { uint4 v = lds128(wb + R_WR + i * 512); A[i & 1][i >> 1][0] = v.x; A[i & 1][i >> 1][1] = v.y; A[i & 1][i >> 1][2] = v.z; A[i & 1][i >> 1][3] = v.w; }
    }
    return;
  }
  const float scale = 0.08838834764831845f, l2e = 1.4426950408889634f;
  auto prefetch = [&](int s) {
    const int vt = otid() - 160;
    if ((s & 3) == 0) { wait_flag(&g_fl.tile[s >> 2][h >> 1], 1); wait_flag(&g_fl.tile[s >> 2][16 + (h >> 1)], 1); }
    const int r = vt >> 4, c = vt & 15;
    const bf16* src = g_qkv + (size_t)(32 * s + r) * QW + h * 128 + c * 8;
    uint32_t kb = sb + R_KT + (s & 1) * KT_SZ + r * 256, vb = sb + R_VT + (s & 1) * VT_SZ + r * 272 + c * 16;
    #pragma unroll
    for (int i = 0; i < 8; i++) { cp16(kb + i * 1024 + ((c ^ swz(r + 4 * i)) << 4), src + (size_t)i * 4 * QW); cp16(vb + i * 1088, src + (size_t)i * 4 * QW + 4096); }
    if (s + 1 < NSTEP && vt < 3) asm volatile("prefetch.global.L2 [%0];" ::"l"(&g_acc[s + 1][0][0] + ((h * 2 + j) * 3 + vt) * 8));
  };
  if (warp >= 4) {
  if (warp == 5 || warp == 6) prefetch(0);
  #pragma unroll 1
  for (int s = 0; s < NSTEP; s++) {
    TR(0); TR(1);
    const int tid = otid(), lane = tid & 31, warp = tid >> 5, g = lane >> 2, t = lane & 3;
    const uint32_t fo = (t ^ swz(g)) << 4;
    {
      if (tid == 0) mbar_expect(mQ, 4096);
      if (tid == 128) mbar_expect(mK, 4096);
      const float4* src = &g_acc[s][j][tid];
      uint4 v0, v1, v2; int it = 0;
      do { LD3(v0, v1, v2); } while (!OK3(v0, v1, v2) && ++it < SPIN_LIMIT);
      __syncwarp();
      stsm4t(sb + R_MEM + (lane & 7) * 16 + (4 * warp + (lane >> 3)) * 160,
        pack2(__uint_as_float(v0.x), __uint_as_float(v0.y)), pack2(__uint_as_float(v0.z), __uint_as_float(v1.x)),
        pack2(__uint_as_float(v1.y), __uint_as_float(v1.z)), pack2(__uint_as_float(v2.x), __uint_as_float(v2.y)));
    }
    TR(2);
    asm volatile("cp.async.wait_all;" ::: "memory");
    bar_sync(1, 256);
    { long long t0 = clock64(); while (clock64() - t0 < KD); }
    if (VP < 0) bar_arrive(4, 384);
    TR(3);
    float c[4][4];
    #pragma unroll
    for (int i = 0; i < 4; i++) { c[i][0] = c[i][1] = c[i][2] = c[i][3] = 0.f; }
    #pragma unroll
    for (int p = 0; p < 8; p++) {
      uint4 b = ldc(R_MEM + g * 16 + t * 160 + p * 640);
      mma16(c[0], A[0][2*p][0], A[0][2*p][1], A[0][2*p][2], A[0][2*p][3], b.x, b.y);
      mma16(c[1], A[1][2*p][0], A[1][2*p][1], A[1][2*p][2], A[1][2*p][3], b.x, b.y);
      mma16(c[2], A[0][2*p+1][0], A[0][2*p+1][1], A[0][2*p+1][2], A[0][2*p+1][3], b.z, b.w);
      mma16(c[3], A[1][2*p+1][0], A[1][2*p+1][1], A[1][2*p+1][2], A[1][2*p+1][3], b.z, b.w);
      if (p == VP) asm volatile("bar.arrive 4, 384;");
    }
    #pragma unroll
    for (int i = 0; i < 4; i++) { c[0][i] += c[2][i]; c[1][i] += c[3][i]; }
    const uint32_t rx = sb + R_RQK + (warp * 64 + lane) * 16;
    { uint32_t ra = mapa(rx, peer), rm = mapa(mK, peer);
      st_async_v4(ra, c[0][0], c[0][1], c[0][2], c[0][3], rm);
      st_async_v4(ra + 512, c[1][0], c[1][1], c[1][2], c[1][3], rm); }
    if (VP > 7) bar_arrive(4, 384);
    TR(4);
    const uint32_t so = (lane & 7) * 256 + (((4 * (warp & 3) + (lane >> 3)) ^ swz(lane & 7)) << 4);
    mbar_wait(mK, s & 1);
    TR(5);
    uint32_t m0, m1, m2, m3;
    { uint4 r0 = lds128(rx), r1 = lds128(rx + 512);
      m0 = pack2(c[0][0] + __uint_as_float(r0.x), c[0][1] + __uint_as_float(r0.y)); m1 = pack2(c[0][2] + __uint_as_float(r0.z), c[0][3] + __uint_as_float(r0.w));
      m2 = pack2(c[1][0] + __uint_as_float(r1.x), c[1][1] + __uint_as_float(r1.y)); m3 = pack2(c[1][2] + __uint_as_float(r1.z), c[1][3] + __uint_as_float(r1.w)); }
    stsm4t(sb + R_KT + (s & 1) * KT_SZ + 32 * 256 + so, m0, m1, m2, m3);
    if (s == NSTEP - 1) { bar_arrive(6, 256); break; }
    asm("movmatrix.sync.aligned.m8n8.trans.b16 %0, %0;" : "+r"(m0)); asm("movmatrix.sync.aligned.m8n8.trans.b16 %0, %0;" : "+r"(m1));
    asm("movmatrix.sync.aligned.m8n8.trans.b16 %0, %0;" : "+r"(m2)); asm("movmatrix.sync.aligned.m8n8.trans.b16 %0, %0;" : "+r"(m3));
    TR(8);
    bar_sync(9, 256);
    TR(9);
    { uint32_t qa[4]; ldsm4(qa, sb + R_Q + so);
      #pragma unroll
      for (int i = 0; i < 2; i++) { c[i][0] = c[i][1] = c[i][2] = c[i][3] = 0.f; }
      mma16(c[0], qa[0], 0, qa[1], 0, m0, m1); mma16(c[1], qa[2], 0, qa[3], 0, m2, m3);
      asm volatile("st.shared.v2.f32 [%0], {%1,%2};" ::"r"(sb + R_SM + (warp - 4) * 256 + lane * 8), "f"(c[0][0] + c[1][0]), "f"(c[0][1] + c[1][1]) : "memory"); }
    bar_arrive(2, 256);
    TR(10);
    if ((warp == 5 || warp == 6) && s < NSTEP - 2) prefetch(s + 1);
    TR(7);
    if (warp == 7) { if ((s & 3) == 1 && s > 1 && lane == 0) asm volatile("red.release.gpu.global.add.s32 [%0], 4;" ::"l"(&g_fl.prog[(s - 2) >> 2][h]) : "memory"); __syncwarp();
      long long t0 = clock64(); while (clock64() - t0 < W7D); }
    else bar_sync(8, 352);
    { long long t0 = clock64(); while (clock64() - t0 < PDELAY); }
  }
  return;
  }
  #pragma unroll 1
  for (int s = 0; s < NSTEP; s++) {
    TR(0); TR(1);
    const int tid = otid(), lane = tid & 31, warp = tid >> 5, g = lane >> 2, t = lane & 3;
    const uint32_t fo = (t ^ swz(g)) << 4;
    {
      if (tid == 0) mbar_expect(mQ, 4096);
      if (tid == 128) mbar_expect(mK, 4096);
      const float4* src = &g_acc[s][j][tid];
      uint4 v0, v1, v2; int it = 0;
      do { LD3(v0, v1, v2); } while (!OK3(v0, v1, v2) && ++it < SPIN_LIMIT);
      __syncwarp();
      stsm4t(sb + R_MEM + (lane & 7) * 16 + (4 * warp + (lane >> 3)) * 160,
        pack2(__uint_as_float(v0.x), __uint_as_float(v0.y)), pack2(__uint_as_float(v0.z), __uint_as_float(v1.x)),
        pack2(__uint_as_float(v1.y), __uint_as_float(v1.z)), pack2(__uint_as_float(v2.x), __uint_as_float(v2.y)));
    }
    TR(2);

    bar_sync(1, 256);
    bar_arrive(4, 384);
    TR(3);
    float c[4][4];
    #pragma unroll
    for (int i = 0; i < 4; i++) { c[i][0] = c[i][1] = c[i][2] = c[i][3] = 0.f; }
    #pragma unroll
    for (int p = 0; p < 8; p++) {
      uint4 b = ldc(R_MEM + g * 16 + t * 160 + p * 640);
      mma16(c[0], A[0][2*p][0], A[0][2*p][1], A[0][2*p][2], A[0][2*p][3], b.x, b.y);
      mma16(c[1], A[1][2*p][0], A[1][2*p][1], A[1][2*p][2], A[1][2*p][3], b.x, b.y);
      mma16(c[2], A[0][2*p+1][0], A[0][2*p+1][1], A[0][2*p+1][2], A[0][2*p+1][3], b.z, b.w);
      mma16(c[3], A[1][2*p+1][0], A[1][2*p+1][1], A[1][2*p+1][2], A[1][2*p+1][3], b.z, b.w);
    }
    #pragma unroll
    for (int i = 0; i < 4; i++) { c[0][i] += c[2][i]; c[1][i] += c[3][i]; }
    const uint32_t rx = sb + R_RQK + (warp * 64 + lane) * 16;
    { uint32_t ra = mapa(rx, peer), rm = mapa(mQ, peer);
      st_async_v4(ra, c[0][0], c[0][1], c[0][2], c[0][3], rm);
      st_async_v4(ra + 512, c[1][0], c[1][1], c[1][2], c[1][3], rm); }
    TR(4);
    const uint32_t so = (lane & 7) * 256 + (((4 * (warp & 3) + (lane >> 3)) ^ swz(lane & 7)) << 4);
    if (s == NSTEP - 1) { mbar_wait(mQ, s & 1); break; }
    uint32_t kf[4][4], vf[4][4];
    const uint32_t vb = sb + R_VT + (s & 1) * VT_SZ + (lane & 15) * 272 + (32 * warp + 8 * (lane >> 4)) * 2;
    #pragma unroll
    for (int p = 0; p < 4; p++) ldsm4(kf[p], sb + R_KT + (s & 1) * KT_SZ + p * 2048 + so);
    #pragma unroll
    for (int i = 0; i < 4; i++) ldsm4t(vf[i], vb + (i >> 1) * 16 * 272 + (i & 1) * 32);
    mbar_wait(mQ, s & 1);
    TR(5);
    uint32_t m0, m1, m2, m3;
    { uint4 r0 = lds128(rx), r1 = lds128(rx + 512);
      m0 = pack2(c[0][0] + __uint_as_float(r0.x), c[0][1] + __uint_as_float(r0.y)); m1 = pack2(c[0][2] + __uint_as_float(r0.z), c[0][3] + __uint_as_float(r0.w));
      m2 = pack2(c[1][0] + __uint_as_float(r1.x), c[1][1] + __uint_as_float(r1.y)); m3 = pack2(c[1][2] + __uint_as_float(r1.z), c[1][3] + __uint_as_float(r1.w)); }
    stsm4t(sb + R_Q + so, m0, m1, m2, m3);
    bar_arrive(9, 256);
    TR(8);
    asm("movmatrix.sync.aligned.m8n8.trans.b16 %0, %0;" : "+r"(m0)); asm("movmatrix.sync.aligned.m8n8.trans.b16 %0, %0;" : "+r"(m1));
    asm("movmatrix.sync.aligned.m8n8.trans.b16 %0, %0;" : "+r"(m2)); asm("movmatrix.sync.aligned.m8n8.trans.b16 %0, %0;" : "+r"(m3));
    #pragma unroll
    for (int i = 0; i < 4; i++) { c[i][0] = c[i][1] = c[i][2] = c[i][3] = 0.f; mma16(c[i], m0, 0, m1, 0, kf[i][0], kf[i][1]); }
    #pragma unroll
    for (int i = 0; i < 4; i++) mma16(c[i], m2, 0, m3, 0, kf[i][2], kf[i][3]);
    sts128(rx, make_uint4(__float_as_uint(c[0][0]), __float_as_uint(c[0][1]), __float_as_uint(c[1][0]), __float_as_uint(c[1][1])));
    sts128(rx + 512, make_uint4(__float_as_uint(c[2][0]), __float_as_uint(c[2][1]), __float_as_uint(c[3][0]), __float_as_uint(c[3][1])));
    TR(9);
    bar_sync(10, 128);
    TR(10);
    float sv[8], pm[8];
    { uint4 u[8];
      #pragma unroll
      for (int i = 0; i < 8; i++) u[i] = lds128(sb + R_RQK + lane * 16 + i * 512);
      #pragma unroll
      for (int i = 0; i < 2; i++) {
        sv[4*i]   = (__uint_as_float(u[i].x) + __uint_as_float(u[i+2].x)) + (__uint_as_float(u[i+4].x) + __uint_as_float(u[i+6].x));
        sv[4*i+1] = (__uint_as_float(u[i].y) + __uint_as_float(u[i+2].y)) + (__uint_as_float(u[i+4].y) + __uint_as_float(u[i+6].y));
        sv[4*i+2] = (__uint_as_float(u[i].z) + __uint_as_float(u[i+2].z)) + (__uint_as_float(u[i+4].z) + __uint_as_float(u[i+6].z));
        sv[4*i+3] = (__uint_as_float(u[i].w) + __uint_as_float(u[i+2].w)) + (__uint_as_float(u[i+4].w) + __uint_as_float(u[i+6].w)); }
      #pragma unroll
      for (int i = 0; i < 4; i++) { uint32_t a = pack2(sv[2*i], sv[2*i+1]);
        a = pack2(__uint_as_float(a << 16) * scale, __uint_as_float(a & 0xffff0000u) * scale);
        sv[2*i] = __uint_as_float(a << 16) * l2e; sv[2*i+1] = __uint_as_float(a & 0xffff0000u) * l2e; } }
    float mx = fmaxf(fmaxf(fmaxf(sv[0], sv[1]), fmaxf(sv[2], sv[3])), fmaxf(fmaxf(sv[4], sv[5]), fmaxf(sv[6], sv[7])));
    mx = fmaxf(mx, __shfl_xor_sync(~0u, mx, 1)); mx = fmaxf(mx, __shfl_xor_sync(~0u, mx, 2));
    uint32_t P[5];
    #pragma unroll
    for (int i = 0; i < 4; i++) P[i] = pack2(ex2(sv[2*i] - mx), ex2(sv[2*i+1] - mx));
    #pragma unroll
    for (int i = 0; i < 4; i++) { c[i][0] = c[i][1] = c[i][2] = c[i][3] = 0.f; }
    #pragma unroll
    for (int kk = 0; kk < 2; kk++) {
      mma16(c[0], P[2*kk], 0, P[2*kk+1], 0, vf[2*kk][0], vf[2*kk][1]); mma16(c[1], P[2*kk], 0, P[2*kk+1], 0, vf[2*kk][2], vf[2*kk][3]);
      mma16(c[2], P[2*kk], 0, P[2*kk+1], 0, vf[2*kk+1][0], vf[2*kk+1][1]); mma16(c[3], P[2*kk], 0, P[2*kk+1], 0, vf[2*kk+1][2], vf[2*kk+1][3]);
    }
    float sum = 0.f;
    #pragma unroll
    for (int i = 0; i < 4; i++) sum += __uint_as_float(P[i] << 16) + __uint_as_float(P[i] & 0xffff0000u);
    TR(11);
    bar_sync(2, 256);
    #pragma unroll
    for (int i = 0; i < 4; i++) asm volatile("ld.shared.v2.f32 {%0,%1}, [%2];" : "=f"(pm[2*i]), "=f"(pm[2*i+1]) : "r"(sb + R_SM + i * 256 + lane * 8) : "memory");
    const float s8 = rbf(rbf((pm[0] + pm[2]) + (pm[4] + pm[6])) * scale) * l2e, s9 = rbf(rbf((pm[1] + pm[3]) + (pm[5] + pm[7])) * scale) * l2e;
    float mg = fmaxf(mx, fmaxf(s8, s9));
    mg = fmaxf(mg, __shfl_xor_sync(~0u, mg, 1)); mg = fmaxf(mg, __shfl_xor_sync(~0u, mg, 2));
    const float fs = ex2(mx - mg);
    P[4] = pack2(ex2(s8 - mg), ex2(s9 - mg));
    #pragma unroll
    for (int i = 0; i < 4; i++) { c[i][0] *= fs; c[i][1] *= fs; }
    sum = fmaf(sum, fs, __uint_as_float(P[4] << 16) + __uint_as_float(P[4] & 0xffff0000u));
    sum += __shfl_xor_sync(~0u, sum, 1); sum += __shfl_xor_sync(~0u, sum, 2);
    float inv; asm("rcp.approx.ftz.f32 %0, %1;" : "=f"(inv) : "f"(sum));
    TR(6);
    bar_sync(3, 256);
    { uint32_t r[4]; ldsm4t(r, sb + R_VT + (s & 1) * VT_SZ + (32 + (lane & 7)) * 272 + (4 * warp + (lane >> 3)) * 16);
      #pragma unroll
      for (int i = 0; i < 4; i++) mma8(c[i], P[4], 0, r[i]); }
    asm volatile("stmatrix.sync.aligned.m8n8.x4.shared.b16 [%0], {%1,%2,%3,%4};" ::"r"(sb + R_O + so),
      "r"(pack2(c[0][0] * inv, c[0][1] * inv)), "r"(pack2(c[1][0] * inv, c[1][1] * inv)), "r"(pack2(c[2][0] * inv, c[2][1] * inv)), "r"(pack2(c[3][0] * inv, c[3][1] * inv)) : "memory");
    bar_arrive(7, 256);
    TR(7);
    bar_sync(8, 352);
    long long t0 = clock64();
    #pragma unroll
    for (int i = 0; i < 16; i++) { uint4 v = lds128(sb + R_WQ + ((warp * 16 + i) * 32 + lane) * 16); A[1][i][0] = v.x; A[1][i][1] = v.y; A[1][i][2] = v.z; A[1][i][3] = v.w; }
    while (clock64() - t0 < PDELAY);
  }
}

constexpr int I_M1 = 512, I_Q = 624, I_M2 = 688, I_Q2 = 720, I_G = 912, I_S = I_G + NFULL * 34, I_END = I_S + (16 - NFULL) * 80;
constexpr int B_STG = 4 * 49152, B_BAR = B_STG + 8 * 2304;
template <int N> struct IC { static constexpr int v = N; };
struct Item { int type, rb, nt, ks; };
__device__ __forceinline__ Item decode(int it) {
  Item r; r.ks = 0;
  if (it < I_M1) { r.type = 0; r.rb = it >> 5; r.nt = it & 31; }
  else if (it < I_Q) { int i = it - I_M1; r.type = 1; r.rb = i / 7; r.nt = i % 7; }
  else if (it < I_M2) { int i = it - I_Q; r.type = 0; r.rb = i >> 4; r.nt = 32 + (i & 15); }
  else if (it < I_Q2) { int i = it - I_M2; r.type = 2; r.rb = i >> 1; r.nt = i & 1; }
  else if (it < I_G) { int i = it - I_Q2 + 64; r.type = 0; r.rb = i >> 4; r.nt = 32 + (i & 15); }
  else if (it < I_S) { int i = it - I_G, q = i % 34; r.rb = i / 34; if (q < 32) { r.type = 3; r.nt = q; } else { r.type = 4; r.nt = q - 32; } }
  else { int i = it - I_S; if (i >= 48) i += 32; int q = i % 80; r.rb = NFULL + i / 80; if (r.rb == 16) q += 48;
    if (q < 32) { r.type = 3; r.nt = q; }
    else if (q < 48) { r.type = 6; r.nt = (q - 32) >> 3; r.ks = (q - 32) & 7; }
    else { r.type = 5; r.nt = q - 48; r.rb--; } }
  return r;
}
__device__ __forceinline__ float gelu_t(float x) { float u = 0.7978845608028654f * (x + 0.044715f * x * x * x); float th; asm("tanh.approx.f32 %0, %1;" : "=f"(th) : "f"(u)); float hx = 0.5f * x; return fmaf(hx, th, hx); }

__device__ __forceinline__ void bulk(uint32_t sb, const Maps& mp, const bf16* __restrict__ x, const bf16* __restrict__ b1, const bf16* __restrict__ b2, bf16* __restrict__ out) {
  const int tid = threadIdx.x, warp = tid >> 5, lane = tid & 31, g = lane >> 2, t = lane & 3;
  const int bid = vbid() - NREC;
  const uint32_t full = sb + B_BAR, empty = sb + B_BAR + 32, ifull = sb + B_BAR + 64, iempty = sb + B_BAR + 80;
  asm volatile("griddepcontrol.wait;" ::: "memory");
  volatile int* ring = (volatile int*)(__cvta_shared_to_generic(sb + B_BAR + 96));
  if (warp >= 8) {
    asm volatile("setmaxnreg.dec.sync.aligned.u32 40;");
    if (tid == 256) {
      uint32_t st = 0, ph = 0;
      for (int n = 0;; n++) {
        int it = n == 0 ? bid : NBULK + atomicAdd(&g_fl.next, 1);
        Item I = decode(it);
        const CUtensorMap *ma, *mb; int nkb = 8, kb0 = 0, n0;
        if (I.type == 0) { ma = &mp.xn; mb = I.nt < 16 ? &mp.wk : (I.nt < 32 ? &mp.wv : &mp.wq); n0 = (I.nt & 15) * 256; }
        else if (I.type == 1) { ma = &mp.y; mb = &mp.w1; n0 = I.nt * 256; }
        else if (I.type == 2) { ma = &mp.hid; mb = &mp.w2; n0 = I.nt * 256; nkb = 28; }
        else { ma = &mp.o; mb = &mp.wo; n0 = I.nt * 256; kb0 = I.ks * 8; if (I.type == 4) nkb = 64; }
        const bool pre = it < I_END && I.type == 6;
        if (pre) {
          for (int m = 0; m < 4; m++) {
            mbar_wait(empty + st * 8, ph ^ 1);
            mbar_expect(full + st * 8, 49152);
            #pragma unroll
            for (int q = 0; q < 4; q++) tma2d(sb + st * 49152 + 16384 + q * 8192, mb, n0 + q * 64, (kb0 + m) * 64, full + st * 8);
            if (++st == 4) { st = 0; ph ^= 1; }
          }
        }
        if (it < I_END) {
          if (I.type == 5) { wait_flag(&g_fl.s[I.rb][0], 16); wait_flag(&g_fl.z[I.rb][0], 1); wait_flag(&g_fl.z[I.rb][1], 1); }
          else if (I.type == 3) { wait_flag(&g_fl.tile[I.rb][I.nt >> 1], 1); wait_flag(&g_fl.tile[I.rb][16 + (I.nt >> 1)], 1); wait_flag(&g_fl.tile[I.rb][32 + (I.nt >> 1)], 1); fence_async();
            for (int m = 0; m < 3; m++) {
              mbar_wait(empty + st * 8, ph ^ 1);
              mbar_expect(full + st * 8, 32768);
              int col = (m == 0 ? 8192 : (m == 1 ? 0 : 4096)) + I.nt * 128;
              tma2d(sb + st * 49152, &mp.qkv, col, I.rb * 128, full + st * 8);
              tma2d(sb + st * 49152 + 16384, &mp.qkv, col + 64, I.rb * 128, full + st * 8);
              if (++st == 4) { st = 0; ph ^= 1; }
            }
            wait_flag(&g_fl.prog[I.rb][I.nt], 8); }
          else if (I.type == 2) { wait_flag(&g_fl.hid[I.rb], 7); fence_async(); }
          else if (I.type == 4) { wait_flag(&g_fl.z[I.rb][I.nt], 1); wait_flag(&g_fl.o[I.rb][0], 4); fence_async(); }
          else if (I.type == 6) { wait_flag(&g_fl.o[I.rb][I.ks], 4); fence_async(); }
        }
        mbar_wait(iempty + (n & 1) * 8, ((n >> 1) & 1) ^ 1);
        ring[n & 1] = it; mbar_arrive(ifull + (n & 1) * 8);
        if (it >= I_END) break;
        if (I.type == 5 || I.type == 3) continue;
        if (pre) {
          #pragma unroll
          for (int m = 0; m < 4; m++) tma2d(sb + ((st + m) & 3) * 49152, ma, (kb0 + m) * 64, I.rb * 128, full + ((st + m) & 3) * 8);
          kb0 += 4; nkb -= 4;
        }
        for (int kb = kb0; kb < kb0 + nkb; kb++) {
          if (I.type == 4 && kb && !(kb & 7)) { wait_flag(&g_fl.o[I.rb][kb >> 3], 4); fence_async(); }
          mbar_wait(empty + st * 8, ph ^ 1);
          mbar_expect(full + st * 8, 49152);
          uint32_t sa = sb + st * 49152;
          tma2d(sa, ma, kb * 64, I.rb * 128, full + st * 8);
          #pragma unroll
          for (int q = 0; q < 4; q++) tma2d(sa + 16384 + q * 8192, mb, n0 + q * 64, kb * 64, full + st * 8);
          if (++st == 4) { st = 0; ph ^= 1; }
        }
      }
    } else if (warp == 9) {
      for (int n = 0;; n++) {
        mbar_wait(ifull + (n & 1) * 8, (n >> 1) & 1);
        int it = ring[n & 1];
        if (it >= I_END) break;
        Item I = decode(it);
        bar_sync(6 + (n & 1), 288);
        if (lane == 0) {
          if (I.type != 5 && I.type != 4) {
            fence_async(); __threadfence();
            int* f = I.type == 0 ? &g_fl.tile[I.rb][I.nt] : I.type == 1 ? &g_fl.hid[I.rb] : I.type == 2 ? &g_fl.z[I.rb][I.nt] : I.type == 3 ? &g_fl.o[I.rb][I.nt >> 2] : &g_fl.s[I.rb][0];
            atomicAdd(f, 1);
          }
          mbar_arrive(iempty + (n & 1) * 8);
        }
      }
    }
    return;
  }
  asm volatile("setmaxnreg.inc.sync.aligned.u32 232;");
  const int wg = warp >> 2;
  const uint32_t stg = sb + B_STG + warp * 2304;
  const int lm = lane >> 3, lr = lane & 7;
  uint32_t st = 0, ph = 0;
  float d[128];
  #pragma unroll 1
  for (int n = 0;; n++) {
    mbar_wait(ifull + (n & 1) * 8, (n >> 1) & 1);
    const int it = ring[n & 1];
    __syncwarp(); if (lane == 0) mbar_arrive(iempty + (n & 1) * 8);
    if (it >= I_END) break;
    Item I = decode(it);
    const int row0 = I.rb * 128 + warp * 16;
    TB(0);
    if (I.type == 5) {
      #pragma unroll
      for (int i = 0; i < 2; i++) {
        const float4* sp = (const float4*)g_sp + (size_t)((I.rb - NFULL) * 16 + (I.nt >> 4)) * 8192 + (2 * (I.nt & 15) + i) * 256 + tid;
        float4 a = __ldcg(sp);
        #pragma unroll
        for (int k = 1; k < 8; k++) { float4 b = __ldcg(sp + k * 16384); a.x += b.x; a.y += b.y; a.z += b.z; a.w += b.w; }
        const size_t off = (size_t)(row0 + g) * DM + I.nt * 16 + i * 8 + 2 * t;
        #pragma unroll
        for (int r = 0; r < 2; r++) {
          const uint32_t xv = *(const uint32_t*)(x + off + r * 8 * DM), gv = __ldcg((const uint32_t*)(g_g + off + r * 8 * DM));
          const float s0 = r ? a.z : a.x, s1 = r ? a.w : a.y;
          *(uint32_t*)(out + off + r * 8 * DM) = pack2(__uint_as_float(xv << 16) + rbf(rbf(s0) * __uint_as_float(gv << 16)), __uint_as_float(xv & 0xffff0000u) + rbf(rbf(s1) * __uint_as_float(gv & 0xffff0000u)));
        }
      }
      bar_arrive(6 + (n & 1), 288);
      continue;
    }
    if (I.type == 3) {
      const int h = I.nt, seg = warp >> 1, half = warp & 1, step = I.rb * 4 + seg;
      uint32_t kmr[16], vmr[16];
      { const uint32_t* km = (const uint32_t*)(g_km + ((size_t)(step * 32 + h)) * 1024) + g * 64 + t;
        const uint32_t* vm = (const uint32_t*)(g_vmT + ((size_t)(step * 32 + h)) * 1024) + g * 4 + t;
        #pragma unroll
        for (int i = 0; i < 16; i++) { kmr[i] = __ldcg(km + i * 4); vmr[i] = __ldcg(vm + i * 32); } }
      uint32_t sQ = sb + st * 49152; mbar_wait(full + st * 8, ph); uint32_t eQ = empty + st * 8; if (++st == 4) { st = 0; ph ^= 1; }
      uint32_t sK = sb + st * 49152; mbar_wait(full + st * 8, ph); uint32_t eK = empty + st * 8; if (++st == 4) { st = 0; ph ^= 1; }
      float sc[5][4];
      #pragma unroll
      for (int i = 0; i < 5; i++) { sc[i][0] = sc[i][1] = sc[i][2] = sc[i][3] = 0.f; }
      #pragma unroll
      for (int ks = 0; ks < 8; ks++) {
        uint32_t a[4]; { int r = warp * 16 + 8 * (lm & 1) + lr, c8 = 2 * ks + (lm >> 1); ldsm4(a, sQ + (c8 >> 3) * 16384 + r * 128 + (((c8 & 7) ^ (r & 7)) << 4)); }
        #pragma unroll
        for (int np = 0; np < 2; np++) {
          if (np == 1 && half == 0) continue;
          uint32_t b[4]; int r = seg * 32 + 16 * np + 8 * (lm >> 1) + lr, c8 = 2 * ks + (lm & 1);
          ldsm4(b, sK + (c8 >> 3) * 16384 + r * 128 + (((c8 & 7) ^ (r & 7)) << 4));
          mma16(sc[2*np], a[0], a[1], a[2], a[3], b[0], b[1]); mma16(sc[2*np+1], a[0], a[1], a[2], a[3], b[2], b[3]);
        }
        mma16(sc[4], a[0], a[1], a[2], a[3], kmr[2*ks], kmr[2*ks+1]);
      }
      __syncwarp(); if (lane == 0) { mbar_arrive(eQ); mbar_arrive(eK); }
      const float scale = 0.08838834764831845f;
      uint32_t P[5][2];
      #pragma unroll
      for (int rr = 0; rr < 2; rr++) {
        const int qi = 16 * half + g + 8 * rr;
        float mx = -3.0e38f;
        #pragma unroll
        for (int i = 0; i < 5; i++)
          #pragma unroll
          for (int e = 0; e < 2; e++) { float v = rbf(rbf(sc[i][2*rr+e]) * scale); if (i < 4 && 8 * i + 2 * t + e > qi) v = -1.0e9f; sc[i][2*rr+e] = v; mx = fmaxf(mx, v); }
        mx = fmaxf(mx, __shfl_xor_sync(~0u, mx, 1)); mx = fmaxf(mx, __shfl_xor_sync(~0u, mx, 2));
        float sum = 0;
        #pragma unroll
        for (int i = 0; i < 5; i++)
          #pragma unroll
          for (int e = 0; e < 2; e++) { float v = __expf(sc[i][2*rr+e] - mx); sc[i][2*rr+e] = v; sum += v; }
        sum += __shfl_xor_sync(~0u, sum, 1); sum += __shfl_xor_sync(~0u, sum, 2);
        float inv = __fdividef(1.f, sum);
        #pragma unroll
        for (int i = 0; i < 5; i++) P[i][rr] = pack2(sc[i][2*rr] * inv, sc[i][2*rr+1] * inv);
      }
      uint32_t sV = sb + st * 49152; mbar_wait(full + st * 8, ph); uint32_t eV = empty + st * 8; if (++st == 4) { st = 0; ph ^= 1; }
      #pragma unroll
      for (int i = 0; i < 64; i++) d[i] = 0.f;
      #pragma unroll
      for (int n2 = 0; n2 < 8; n2++) {
        #pragma unroll
        for (int kk = 0; kk < 2; kk++) {
          if (kk == 1 && half == 0) continue;
          uint32_t b[4]; int r = seg * 32 + 16 * kk + 8 * (lm & 1) + lr, c8 = 2 * n2 + (lm >> 1);
          ldsm4t(b, sV + (c8 >> 3) * 16384 + r * 128 + (((c8 & 7) ^ (r & 7)) << 4));
          mma16(d + 8 * n2, P[2*kk][0], P[2*kk][1], P[2*kk+1][0], P[2*kk+1][1], b[0], b[1]);
          mma16(d + 8 * n2 + 4, P[2*kk][0], P[2*kk][1], P[2*kk+1][0], P[2*kk+1][1], b[2], b[3]);
        }
        mma8(d + 8 * n2, P[4][0], P[4][1], vmr[2*n2]); mma8(d + 8 * n2 + 4, P[4][0], P[4][1], vmr[2*n2+1]);
      }
      __syncwarp(); if (lane == 0) mbar_arrive(eV);
      #pragma unroll
      for (int ch = 0; ch < 2; ch++) {
        #pragma unroll
        for (int i = 0; i < 8; i++) { const float* a = d + ch * 32 + i * 4;
          sts32(stg + g * 144 + i * 16 + t * 4, pack2(a[0], a[1])); sts32(stg + (g + 8) * 144 + i * 16 + t * 4, pack2(a[2], a[3])); }
        __syncwarp();
        #pragma unroll
        for (int i = 0; i < 4; i++) { int r = i * 4 + lm; uint4 v = lds128(stg + r * 144 + lr * 16);
          *(uint4*)(g_o + (size_t)(row0 + r) * 4096 + h * 128 + ch * 64 + lr * 8) = v; }
        __syncwarp();
      }
      bar_arrive(6 + (n & 1), 288);
      continue;
    }
    const int nkb = I.type == 2 ? 28 : I.type == 4 ? 64 : 8;
    uint32_t prev = 0;
    for (int kb = 0; kb < nkb; kb++) {
      mbar_wait(full + st * 8, ph);
      uint32_t sa = sb + st * 49152;
      asm volatile("wgmma.fence.sync.aligned;" ::: "memory");
      #pragma unroll
      for (int k = 0; k < 4; k++)
        wgmma256(d, mkdesc(sa + wg * 8192 + k * 32, 16, 1024), mkdesc(sa + 16384 + k * 2048, 8192, 1024), (kb | k) != 0);
      asm volatile("wgmma.commit_group.sync.aligned;" ::: "memory");
      if (kb > 0) { asm volatile("wgmma.wait_group.sync.aligned 1;" ::: "memory"); if (lane == 0) mbar_arrive(prev); }
      prev = empty + st * 8;
      if (++st == 4) { st = 0; ph ^= 1; }
    }
    asm volatile("wgmma.wait_group.sync.aligned 0;" ::: "memory");
    if (lane == 0) mbar_arrive(prev);
    TB(1);
    auto epi = [&](auto tc) {
      constexpr int TY = decltype(tc)::v;
      bf16* dst; int ld;
      if (TY == 0) { dst = g_qkv + (size_t)row0 * QW + I.nt * 256; ld = QW; } else if (TY == 1) { dst = g_hid + (size_t)row0 * FF + I.nt * 256; ld = FF; }
      else { dst = (TY == 2 ? g_g : out) + (size_t)row0 * DM + I.nt * 256; ld = DM; }
      #pragma unroll
      for (int ch = 0; ch < 4; ch++) {
        #pragma unroll
        for (int i = 0; i < 8; i++) { float* a = d + ch * 32 + i * 4;
          if (TY == 1) { float2 bb = __bfloat1622float2(*(const __nv_bfloat162*)(b1 + I.nt * 256 + ch * 64 + i * 8 + 2 * t));
            a[0] = gelu_t(rbf(rbf(a[0]) + bb.x)); a[1] = gelu_t(rbf(rbf(a[1]) + bb.y)); a[2] = gelu_t(rbf(rbf(a[2]) + bb.x)); a[3] = gelu_t(rbf(rbf(a[3]) + bb.y)); }
          if (TY == 2) { float2 bb = __bfloat1622float2(*(const __nv_bfloat162*)(b2 + I.nt * 256 + ch * 64 + i * 8 + 2 * t));
            #pragma unroll
            for (int e = 0; e < 4; e++) { float u = rbf(rbf(a[e]) + ((e & 1) ? bb.y : bb.x)); a[e] = __fdividef(u, 1.f + __expf(-u)); } }
          sts32(stg + g * 144 + i * 16 + t * 4, pack2(a[0], a[1])); sts32(stg + (g + 8) * 144 + i * 16 + t * 4, pack2(a[2], a[3])); }
        __syncwarp();
        #pragma unroll
        for (int i = 0; i < 4; i++) { int r = i * 4 + lm; uint4 v = lds128(stg + r * 144 + lr * 16);
          if (TY == 4) { const size_t off = (size_t)(row0 + r) * DM + I.nt * 256 + ch * 64 + lr * 8;
            uint4 xv = *(const uint4*)(x + off), gv = __ldcg((const uint4*)(g_g + off)); float q[8];
            #pragma unroll
            for (int e = 0; e < 8; e++) q[e] = __bfloat162float(((const bf16*)&xv)[e]) + rbf(__bfloat162float(((const bf16*)&v)[e]) * __bfloat162float(((const bf16*)&gv)[e]));
            v = make_uint4(pack2(q[0], q[1]), pack2(q[2], q[3]), pack2(q[4], q[5]), pack2(q[6], q[7])); }
          *(uint4*)(dst + (size_t)r * ld + ch * 64 + lr * 8) = v; }
        __syncwarp();
      }
    };
    if (I.type == 0) epi(IC<0>{}); else if (I.type == 1) epi(IC<1>{}); else if (I.type == 2) epi(IC<2>{}); else if (I.type == 4) epi(IC<4>{});
    else {
      float4* dst = (float4*)g_sp + (size_t)(((I.rb - NFULL) * 8 + I.ks) * 2 + I.nt) * 8192 + tid;
      #pragma unroll
      for (int i = 0; i < 32; i++) __stcg(dst + i * 256, make_float4(d[4*i], d[4*i+1], d[4*i+2], d[4*i+3]));
    }
    bar_arrive(6 + (n & 1), 288);
  }
}

__global__ void __cluster_dims__(2, 1, 1) __launch_bounds__(384, 1)
main_kernel(const __grid_constant__ Maps mp, const bf16* x, const bf16* Wq, const bf16* Wk, const bf16* Wv, const bf16* Wo, const bf16* b1, const bf16* b2, bf16* out, int dyn) {
  const uint32_t sb = smem_u32(smem_raw);
  if (sb & 1023) __trap();
  int role = -1;
  if (threadIdx.x == 0) {
    { mbar_init(sb + R_BAR, 1); mbar_init(sb + R_BAR + 8, 1); mbar_init(sb + R_BAR + 16, 1); }
    { for (int i = 0; i < 4; i++) { mbar_init(sb + B_BAR + i * 8, 1); mbar_init(sb + B_BAR + 32 + i * 8, 8); }
      for (int i = 0; i < 2; i++) { mbar_init(sb + B_BAR + 64 + i * 8, 1); mbar_init(sb + B_BAR + 80 + i * 8, 9); } }
    asm volatile("fence.mbarrier_init.release.cluster;" ::: "memory");
    if (!(blockIdx.x & 1) && !dyn) role = blockIdx.x >> 1;
    if (!(blockIdx.x & 1) && dyn) {
      asm volatile("griddepcontrol.wait;" ::: "memory");
      uint32_t sm; asm volatile("mov.u32 %0, %%smid;" : "=r"(sm));
      const int tpc = sm >> 1; int c = (tpc >= 34) ? 0 : 1;
      int tk = atomicAdd(&g_fl.role[c], 1);
      if (tk >= (c ? 34 : 32)) { c ^= 1; tk = atomicAdd(&g_fl.role[c], 1); }
      role = c ? 32 + tk : tk;
    }
  }
  asm volatile("barrier.cluster.arrive.release.aligned; barrier.cluster.wait.acquire.aligned;" ::: "memory");
  if (role >= 0) { sts32(sb + 232448 - 32, role); asm volatile("st.shared::cluster.u32 [%0], %1;" ::"r"(mapa(sb + 232448 - 32, 1)), "r"(role) : "memory"); }
  asm volatile("barrier.cluster.arrive.release.aligned; barrier.cluster.wait.acquire.aligned;" ::: "memory");
  if (vbid() < NREC) recurrence(sb, Wq, Wk, Wv, Wo);
  else bulk(sb, mp, x, b1, b2, out);
}

typedef CUresult (*EncFn)(CUtensorMap*, CUtensorMapDataType, cuuint32_t, void*, const cuuint64_t*, const cuuint64_t*, const cuuint32_t*, const cuuint32_t*, CUtensorMapInterleave, CUtensorMapSwizzle, CUtensorMapL2promotion, CUtensorMapFloatOOBfill);
static void mk(EncFn f, CUtensorMap* m, const void* p, uint64_t rows, uint64_t cols, uint32_t boxr) {
  cuuint64_t dims[2] = {cols, rows}, str[1] = {cols * 2}; cuuint32_t box[2] = {64, boxr}, es[2] = {1, 1};
  f(m, CU_TENSOR_MAP_DATA_TYPE_BFLOAT16, 2, (void*)p, dims, str, box, es, CU_TENSOR_MAP_INTERLEAVE_NONE, CU_TENSOR_MAP_SWIZZLE_128B, CU_TENSOR_MAP_L2_PROMOTION_L2_256B, CU_TENSOR_MAP_FLOAT_OOB_FILL_NONE);
}
extern "C" void kernel_launch(void* const* d_in, const int* in_sizes, int n_in, void* d_out, int out_size) {
  const bf16 *x = (const bf16*)d_in[0], *mem0 = (const bf16*)d_in[1], *Wq = (const bf16*)d_in[2], *Wk = (const bf16*)d_in[3], *Wv = (const bf16*)d_in[4], *Wo = (const bf16*)d_in[5];
  const bf16 *w1 = (const bf16*)d_in[8], *b1 = (const bf16*)d_in[9], *w2 = (const bf16*)d_in[10], *b2 = (const bf16*)d_in[11];
  void* fn = nullptr; cudaDriverEntryPointQueryResult qr;
  cudaGetDriverEntryPoint("cuTensorMapEncodeTiled", &fn, cudaEnableDefault, &qr);
  EncFn f = (EncFn)fn;
  void *pxn, *py, *ph, *po, *pq;
  cudaGetSymbolAddress(&pxn, g_xn); cudaGetSymbolAddress(&py, g_y); cudaGetSymbolAddress(&ph, g_hid); cudaGetSymbolAddress(&po, g_o); cudaGetSymbolAddress(&pq, g_qkv);
  Maps mp;
  mk(f, &mp.xn, pxn, SEQ, DM, 128); mk(f, &mp.y, py, SEQ, DM, 128); mk(f, &mp.hid, ph, SEQ, FF, 128); mk(f, &mp.o, po, SEQ, 4096, 128); mk(f, &mp.qkv, pq, SEQ, QW, 128);
  mk(f, &mp.wk, Wk, DM, 4096, 64); mk(f, &mp.wv, Wv, DM, 4096, 64); mk(f, &mp.wq, Wq, DM, 4096, 64);
  mk(f, &mp.w1, w1, DM, FF, 64); mk(f, &mp.w2, w2, FF, DM, 64); mk(f, &mp.wo, Wo, 4096, DM, 64);
  cudaFuncSetAttribute(main_kernel, cudaFuncAttributeMaxDynamicSharedMemorySize, SMEM_BYTES);
  prologue_kernel<<<256, 256, 0, cudaStreamPerThread>>>(x, mem0, Wq, Wk, Wv, Wo);
  cudaLaunchConfig_t cfg = {};
  cfg.gridDim = dim3(NCTA); cfg.blockDim = dim3(384); cfg.dynamicSmemBytes = SMEM_BYTES; cfg.stream = cudaStreamPerThread;
  cudaLaunchAttribute at[1]; at[0].id = cudaLaunchAttributeProgrammaticStreamSerialization; at[0].val.programmaticStreamSerializationAllowed = 1;
  int ncl = 0;
  { cudaLaunchAttribute ca[1]; ca[0].id = cudaLaunchAttributeClusterDimension; ca[0].val.clusterDim.x = 2; ca[0].val.clusterDim.y = 1; ca[0].val.clusterDim.z = 1;
    cfg.attrs = ca; cfg.numAttrs = 1;
    if (cudaOccupancyMaxActiveClusters(&ncl, main_kernel, &cfg) != cudaSuccess) { ncl = 0; cudaGetLastError(); } }
  cfg.attrs = at; cfg.numAttrs = 1;
  cudaLaunchKernelEx(&cfg, main_kernel, mp, x, Wq, Wk, Wv, Wo, b1, b2, (bf16*)d_out, ncl >= NCTA / 2 ? 1 : 0);
}
```
